```python
import torch

def _softmax(x, axis=-1):
    return torch.softmax(x, dim=axis)
def _gelu(x):
    return torch.nn.functional.gelu(x, approximate="tanh")
def _silu(x):
    return torch.nn.functional.silu(x)
def _sigmoid(x):
    return torch.sigmoid(x)
def _layernorm(x, axis=-1, eps=1e-5):
    m = x.mean(dim=axis, keepdim=True)
    v = x.var(dim=axis, keepdim=True, unbiased=False)
    return (x - m) / torch.sqrt(v + eps)
def _scatter_add(tgt, idx, src, axis=0):
    return tgt.clone().index_add_(axis, idx, src)
def _segment_sum(src, seg, n):
    out = torch.zeros((n,) + src.shape[1:], dtype=src.dtype)
    return out.index_add_(0, seg, src)
def _pad(x, pw):
    flat = tuple(v for pair in reversed(pw) for v in pair)
    return torch.nn.functional.pad(x, flat)

kernel_name = 'standalone__w8a8_smoothquant_per_tensor_per_channel_int8_activations_weights__prompt'

def setup_inputs():

    _w = (lambda a: (lambda t: t.to(torch.bfloat16) if t.is_floating_point() else t)(torch.as_tensor(a)))
    B, S, D, F = 1, 2048, 1024, 3584
    x = abs((lambda *s: torch.randn(*s, dtype=torch.bfloat16) * 0.05)(B, S, D))
    w = (lambda *s: torch.randn(*s, dtype=torch.bfloat16) * 0.05)(D, F)
    x_min, x_max = float(x.min()), float(x.max())
    sx = (x_max - x_min) / 255.0 + 1e-6
    zx = int(torch.as_tensor(-128.0 - x_min / sx).round())
    qx = torch.clamp(torch.as_tensor(x / sx).round() + zx, -128, 127).to(torch.int32)
    sw = (torch.abs(w).amax(dim=0) / 127.0 + 1e-6).to(float)
    qw = torch.clamp(torch.as_tensor(w / sw[None, :]).round(), -127, 127).to(torch.int32)
    return {
        "qx": _w(qx),
        "qw": _w(qw),
        "scale_x": _w(torch.tensor(sx, dtype=float)),
        "zero_x": _w(torch.tensor(zx, dtype=torch.int32)),
        "scale_w": _w(sw),
        "bias": _w((lambda *s: torch.randn(*s, dtype=torch.bfloat16) * 0.05)(F)),
    }

def reference(qx, qw, scale_x, zero_x, scale_w, bias):
    dt = scale_w.dtype
    acc = torch.einsum("bsd,df->bsf", (lambda x, dt: x.to(dt))(qx, dt), (lambda x, dt: x.to(dt))(qw, dt))
    w_colsum = torch.sum((lambda x, dt: x.to(dt))(qw, dt), axis=0)
    acc = acc - (lambda x, dt: x.to(dt))(zero_x, dt) * w_colsum[None, None, :]
    return acc * scale_x * scale_w[None, None, :] + bias[None, None, :]
```

```cpp
#include <cuda_runtime.h>
#include <cuda.h>
#include <cuda_bf16.h>
#include <stdint.h>

#define CFG_X1 13
#define CFG_P1 44
#define CFG_P2 39
#define CFG_PT 110
#define CFG_L0 32
#define CFG_T0 0
#define CFG_ACQ 0
#define CFG_MODE 1
#define CFG_PF 1
#define CFG_MC 16
#define CFG_NP 2
#define CFG_D 0
#define CFG_NL 2
#define CFG_R4 2
#define CFG_TD 30
#define CFG_TD0 1200
#define CFG_TDS 600
#define CFG_EPI 2
#define CFG_SLEEP 0
#define CFG_POLL2 0
#define CFG_PF2 0
#define CFG_PREG 56
#define CFG_CREG 200
#define STR2(x) #x
#define STR(x) STR2(x)
#define CFG_WF 1
#define CFG_FL 2
#define CFG_TB 8
#define CFG_Q2 66
#define CFG_PF7 0
#define CFG_Q0 40
#define CFG_NS 2
#define CFG_TS 8
#define CFG_Q3 20
#define CFG_RA 32
#define CFG_SH 4
#define DBG 0

namespace w8 {

constexpr int M_ = 2048, K_ = 1024, N_ = 3584;
constexpr int CS = 16, NCL = 7, NCTA = CS * NCL;
constexpr int WA = 160, WB = 64;
constexpr int NP = CFG_NP, TN = 2 * WA + NP * WB;
constexpr int DA = CFG_D, NL = CFG_NL, R4 = CFG_R4;
constexpr int NAJ = (16 - DA) * 64, NBJ = 10 + 2 * NP, NF = 10 + 2 * NP;
constexpr int X1 = CFG_X1;
constexpr int NSLOT = 7, SLOT = WA * 64;
constexpr int NU = 32 + 8 * NP;
constexpr int NCONV = 4;
constexpr int L0 = CFG_L0, NS = CFG_NS;

constexpr int SM_A = 0;
constexpr int SM_RING = 131072;
constexpr int SM_STG = SM_RING + NSLOT * SLOT;
constexpr int SM_PAR = SM_STG + 3 * 8192;
constexpr int SM_CS = SM_PAR + 3 * TN * 2;
constexpr int SM_BAR = SM_CS + 128;
constexpr int B_FULLB = 0, B_FULLA = 56, B_PAR = 72, B_SW = 77, B_AFREE = 79 - 5  , B_FREE = 90, B_NINIT = 104,
              B_GO = 104, B_FILL = 128, B_CS = 131, B_RAWA = 132, B_RAWB = 145, B_RAWS = 162, B_END = 163;
constexpr int SM_TOTAL = SM_BAR + B_END * 8;
static_assert(SM_TOTAL <= 232448, "");

__device__ uint4 g_s8[(1024 + 8 * 256) * 128];
__device__ unsigned g_flag[16 * 32 + 96];
__device__ int g_cs[16][TN];
__device__ unsigned g_epoch[128];
#define TLREC(i) do {} while (0)
#define TLCLK(i) do {} while (0)
#define TLEND() do {} while (0)
constexpr int SM_ALLOC = SM_TOTAL;

__device__ __forceinline__ void mbar_init(uint32_t bar, uint32_t cnt) {
    asm volatile("mbarrier.init.shared::cta.b64 [%0], %1;" :: "r"(bar), "r"(cnt) : "memory");
}
__device__ __forceinline__ void mbar_expect_tx(uint32_t bar, uint32_t bytes) {
    asm volatile("mbarrier.arrive.expect_tx.shared::cta.b64 _, [%0], %1;" :: "r"(bar), "r"(bytes) : "memory");
}
__device__ __forceinline__ void mbar_arrive(uint32_t bar) {
    asm volatile("mbarrier.arrive.shared::cta.b64 _, [%0];" :: "r"(bar) : "memory");
}
__device__ __forceinline__ void mbar_arrive_cluster(uint32_t bar) {
    asm volatile("mbarrier.arrive.shared::cluster.b64 _, [%0];" :: "r"(bar) : "memory");
}
__device__ __forceinline__ void mbar_wait(uint32_t bar, uint32_t parity = 0) {
    asm volatile("{\n.reg .pred p;\n.reg .u32 c;\n"
                 "mbarrier.try_wait.parity.shared::cta.b64 p, [%0], %1;\n"
                 "@p bra WAIT_DONE;\n"
                 "mov.u32 c, 0;\n"
                 "WAIT_LOOP:\n"
                 "mbarrier.try_wait.parity.shared::cta.b64 p, [%0], %1;\n"
                 "@p bra WAIT_DONE;\n"
                 "add.u32 c, c, 1;\nsetp.lt.u32 p, c, 0x100000;\n"
                 "@p bra WAIT_LOOP;\n"
                 "trap;\n"
                 "WAIT_DONE:\n}" :: "r"(bar), "r"(parity) : "memory");
}
__device__ __forceinline__ void mbar_wait2(uint32_t bar0, uint32_t bar1) {
    asm volatile("{\n.reg .pred p, q;\n.reg .u32 c;\nmov.u32 c, 0;\n"
                 "WAIT_LOOP:\n"
                 "mbarrier.try_wait.parity.shared::cta.b64 p, [%0], 0;\n"
                 "mbarrier.try_wait.parity.shared::cta.b64 q, [%1], 0;\n"
                 "and.pred p, p, q;\n"
                 "@p bra WAIT_DONE;\n"
                 "add.u32 c, c, 1;\nsetp.lt.u32 p, c, 0x100000;\n"
                 "@p bra WAIT_LOOP;\n"
                 "trap;\n"
                 "WAIT_DONE:\n}" :: "r"(bar0), "r"(bar1) : "memory");
}
__device__ __forceinline__ bool mbar_test(uint32_t bar) {
    uint32_t ok;
    asm volatile("{\n.reg .pred p;\nmbarrier.test_wait.parity.shared::cta.b64 p, [%1], 0;\nselp.u32 %0, 1, 0, p;\n}" : "=r"(ok) : "r"(bar) : "memory");
    return ok;
}
__device__ __forceinline__ bool mbar_test2(uint32_t bar0, uint32_t bar1) {
    uint32_t ok;
    asm volatile("{\n.reg .pred p, q;\nmbarrier.test_wait.parity.shared::cta.b64 p, [%1], 0;\n"
                 "mbarrier.test_wait.parity.shared::cta.b64 q, [%2], 0;\nand.pred p, p, q;\nselp.u32 %0, 1, 0, p;\n}"
                 : "=r"(ok) : "r"(bar0), "r"(bar1) : "memory");
    return ok;
}
__device__ __forceinline__ bool elect_one() {
    uint32_t ok;
    asm volatile("{\n.reg .pred p;\nelect.sync _|p, 0xffffffff;\nselp.u32 %0, 1, 0, p;\n}" : "=r"(ok));
    return ok;
}
__device__ __forceinline__ unsigned ld_acquire(const unsigned* p) {
    unsigned v;
    asm volatile("ld.acquire.gpu.global.u32 %0, [%1];" : "=r"(v) : "l"(p) : "memory");
    return v;
}
__device__ __forceinline__ unsigned ld_flag(const unsigned* p) {
    unsigned v;
    asm volatile("ld.relaxed.gpu.global.u32 %0, [%1];" : "=r"(v) : "l"(p) : "memory");
    return v;
}
__device__ __forceinline__ uint4 lds128(uint32_t a) {
    uint4 v;
    asm volatile("ld.shared.v4.b32 {%0,%1,%2,%3}, [%4];" : "=r"(v.x), "=r"(v.y), "=r"(v.z), "=r"(v.w) : "r"(a) : "memory");
    return v;
}
__device__ __forceinline__ void sts128(uint32_t a, uint4 v) {
    asm volatile("st.shared.v4.b32 [%0], {%1,%2,%3,%4};" :: "r"(a), "r"(v.x), "r"(v.y), "r"(v.z), "r"(v.w) : "memory");
}
__device__ __forceinline__ uint32_t lds32(uint32_t a) {
    uint32_t v;
    asm volatile("ld.shared.b32 %0, [%1];" : "=r"(v) : "r"(a) : "memory");
    return v;
}
__device__ __forceinline__ void sts32(uint32_t a, uint32_t v) {
    asm volatile("st.shared.b32 [%0], %1;" :: "r"(a), "r"(v) : "memory");
}
__device__ __forceinline__ void stg128(void* p, uint4 v) {
    asm volatile("st.global.v4.b32 [%0], {%1,%2,%3,%4};" :: "l"(p), "r"(v.x), "r"(v.y), "r"(v.z), "r"(v.w) : "memory");
}
__device__ __forceinline__ unsigned pack4(unsigned a, unsigned b, unsigned c, unsigned d) {
    unsigned lo, r;
    asm("cvt.pack.sat.s8.s32.b32 %0, %1, %2, 0;" : "=r"(lo) : "r"(d), "r"(c));
    asm("cvt.pack.sat.s8.s32.b32 %0, %1, %2, %3;" : "=r"(r) : "r"(b), "r"(a), "r"(lo));
    return r;
}

constexpr uint32_t DESC_A_HI = 0x80000000u | (512 >> 4);
constexpr uint32_t DESC_B_HI = 512 >> 4;
template <int NR> __device__ __forceinline__ void wgmma_n160(int (&d)[NR], uint32_t alo, uint32_t blo, int scale_d) {
    asm volatile("{\n.reg .pred p;\n.reg .b64 da, db;\nsetp.ne.b32 p, %82, 0;\n"
        "mov.b64 da, {%80, %83};\nmov.b64 db, {%81, %84};\n"
        "wgmma.mma_async.sync.aligned.m64n160k32.s32.s8.s8 "
        "{%0, %1, %2, %3, %4, %5, %6, %7, %8, %9, %10, %11, %12, %13, %14, %15, "
        "%16, %17, %18, %19, %20, %21, %22, %23, %24, %25, %26, %27, %28, %29, %30, %31, "
        "%32, %33, %34, %35, %36, %37, %38, %39, %40, %41, %42, %43, %44, %45, %46, %47, "
        "%48, %49, %50, %51, %52, %53, %54, %55, %56, %57, %58, %59, %60, %61, %62, %63, "
        "%64, %65, %66, %67, %68, %69, %70, %71, %72, %73, %74, %75, %76, %77, %78, %79}, "
        "da, db, p;\n}\n"
        : "+r"(d[0]), "+r"(d[1]), "+r"(d[2]), "+r"(d[3]), "+r"(d[4]), "+r"(d[5]), "+r"(d[6]), "+r"(d[7]),
          "+r"(d[8]), "+r"(d[9]), "+r"(d[10]), "+r"(d[11]), "+r"(d[12]), "+r"(d[13]), "+r"(d[14]), "+r"(d[15]),
          "+r"(d[16]), "+r"(d[17]), "+r"(d[18]), "+r"(d[19]), "+r"(d[20]), "+r"(d[21]), "+r"(d[22]), "+r"(d[23]),
          "+r"(d[24]), "+r"(d[25]), "+r"(d[26]), "+r"(d[27]), "+r"(d[28]), "+r"(d[29]), "+r"(d[30]), "+r"(d[31]),
          "+r"(d[32]), "+r"(d[33]), "+r"(d[34]), "+r"(d[35]), "+r"(d[36]), "+r"(d[37]), "+r"(d[38]), "+r"(d[39]),
          "+r"(d[40]), "+r"(d[41]), "+r"(d[42]), "+r"(d[43]), "+r"(d[44]), "+r"(d[45]), "+r"(d[46]), "+r"(d[47]),
          "+r"(d[48]), "+r"(d[49]), "+r"(d[50]), "+r"(d[51]), "+r"(d[52]), "+r"(d[53]), "+r"(d[54]), "+r"(d[55]),
          "+r"(d[56]), "+r"(d[57]), "+r"(d[58]), "+r"(d[59]), "+r"(d[60]), "+r"(d[61]), "+r"(d[62]), "+r"(d[63]),
          "+r"(d[64]), "+r"(d[65]), "+r"(d[66]), "+r"(d[67]), "+r"(d[68]), "+r"(d[69]), "+r"(d[70]), "+r"(d[71]),
          "+r"(d[72]), "+r"(d[73]), "+r"(d[74]), "+r"(d[75]), "+r"(d[76]), "+r"(d[77]), "+r"(d[78]), "+r"(d[79])
        : "r"(alo), "r"(blo), "r"(scale_d), "r"(DESC_A_HI), "r"(DESC_B_HI));
}
template <int NR> __device__ __forceinline__ void wgmma_t128(int (&d)[NR], uint32_t alo, uint32_t blo, int scale_d) {
    asm volatile("{\n.reg .pred p;\n.reg .b64 da, db;\nsetp.ne.b32 p, %66, 0;\n"
        "mov.b64 da, {%64, %67};\nmov.b64 db, {%65, %68};\n"
        "wgmma.mma_async.sync.aligned.m64n128k32.s32.s8.s8 "
        "{%0, %1, %2, %3, %4, %5, %6, %7, %8, %9, %10, %11, %12, %13, %14, %15, "
        "%16, %17, %18, %19, %20, %21, %22, %23, %24, %25, %26, %27, %28, %29, %30, %31, "
        "%32, %33, %34, %35, %36, %37, %38, %39, %40, %41, %42, %43, %44, %45, %46, %47, "
        "%48, %49, %50, %51, %52, %53, %54, %55, %56, %57, %58, %59, %60, %61, %62, %63}, "
        "da, db, p;\n}\n"
        : "+r"(d[0]), "+r"(d[1]), "+r"(d[2]), "+r"(d[3]), "+r"(d[4]), "+r"(d[5]), "+r"(d[6]), "+r"(d[7]),
          "+r"(d[8]), "+r"(d[9]), "+r"(d[10]), "+r"(d[11]), "+r"(d[12]), "+r"(d[13]), "+r"(d[14]), "+r"(d[15]),
          "+r"(d[16]), "+r"(d[17]), "+r"(d[18]), "+r"(d[19]), "+r"(d[20]), "+r"(d[21]), "+r"(d[22]), "+r"(d[23]),
          "+r"(d[24]), "+r"(d[25]), "+r"(d[26]), "+r"(d[27]), "+r"(d[28]), "+r"(d[29]), "+r"(d[30]), "+r"(d[31]),
          "+r"(d[32]), "+r"(d[33]), "+r"(d[34]), "+r"(d[35]), "+r"(d[36]), "+r"(d[37]), "+r"(d[38]), "+r"(d[39]),
          "+r"(d[40]), "+r"(d[41]), "+r"(d[42]), "+r"(d[43]), "+r"(d[44]), "+r"(d[45]), "+r"(d[46]), "+r"(d[47]),
          "+r"(d[48]), "+r"(d[49]), "+r"(d[50]), "+r"(d[51]), "+r"(d[52]), "+r"(d[53]), "+r"(d[54]), "+r"(d[55]),
          "+r"(d[56]), "+r"(d[57]), "+r"(d[58]), "+r"(d[59]), "+r"(d[60]), "+r"(d[61]), "+r"(d[62]), "+r"(d[63])
        : "r"(alo), "r"(blo), "r"(scale_d), "r"(DESC_B_HI), "r"(DESC_A_HI));
}

__device__ __forceinline__ void wg_fence() { asm volatile("wgmma.fence.sync.aligned;" ::: "memory"); }
__device__ __forceinline__ void wg_commit() { asm volatile("wgmma.commit_group.sync.aligned;" ::: "memory"); }
template <int N> __device__ __forceinline__ void wg_wait() { asm volatile("wgmma.wait_group.sync.aligned %0;" :: "n"(N) : "memory"); }

__device__ __forceinline__ uint32_t mapa(uint32_t a, uint32_t r) {
    uint32_t o;
    asm("mapa.shared::cluster.u32 %0, %1, %2;" : "=r"(o) : "r"(a), "r"(r));
    return o;
}
__device__ __forceinline__ unsigned clk() {
    unsigned t;
    asm volatile("mov.u32 %0, %clock;" : "=r"(t));
    return t;
}
__host__ __device__ constexpr int unit_of(int piece, int slab) {
    return piece < 2 ? (slab < X1 ? 2 * slab + piece : (piece ? 16 : X1) + slab) : 32 + (piece - 2) * 8 + (slab >> 1);
}
__host__ __device__ constexpr int col_of(int G) { return G == 4 ? 256 : (G > 4 && G < 9) ? 32 * G - 32 : 32 * G; }
struct BJob { int u, slab, G, pos; };
__host__ __device__ constexpr BJob decode_b(int q) {
    BJob j = {};
    if (q < 160) {
        j.u = q / 5; j.pos = q - j.u * 5;
        const int piece = j.u < 2 * X1 ? (j.u & 1) : (j.u >= X1 + 16);
        j.slab = j.u < 2 * X1 ? (j.u >> 1) : j.u - (piece ? 16 : X1);
        j.G = piece * 5 + j.pos;
    } else {
        q -= 160;
        j.u = 32 + (q >> 2); j.pos = q & 3;
        j.slab = (q >> 1) & 15;
        j.G = 10 + (q >> 5) * 2 + (q & 1);
    }
    return j;
}
__host__ __device__ constexpr int fb_of(int u) {
    return u < 2 * X1 ? (u & 1) * 32 + (u >> 1) : u < X1 + 16 ? u - X1 : u < 32 ? 16 + u : u < 40 ? u - 16 : u < 48 ? u + 8 : u - 24;
}
template <bool k2> __device__ __forceinline__ int stage_w(int t) { return (k2 && t < NBJ - 3) ? SM_A + (5 + t) * 8192 : SM_STG + (t % 3) * 8192; }
constexpr int RA = CFG_RA, RB64 = 64 * RA / (RA - 16);
__device__ __forceinline__ int time_x(int x) { return max(x, L0 + (((x - L0) * RA) >> 4)) + (x >= 16 ? CFG_SH : 0); }
__device__ __forceinline__ int time_w(int q) { return min(L0 + ((q * RB64) >> 6), NAJ / NCL + q) + CFG_SH; }
__device__ __forceinline__ int sched2(int x) { return (min(x, 160) - CFG_Q0) * CFG_Q2 + max(x - 160, 0) * CFG_Q3; }
__device__ __forceinline__ unsigned sched(int T) { return T * CFG_P2 + min(T, CFG_PT) * (CFG_P1 - CFG_P2); }
__device__ __forceinline__ void raw_load(const void* map, int y, int z, uint32_t dst, uint32_t bar) {
    asm volatile("cp.async.bulk.tensor.3d.shared::cluster.global.tile.mbarrier::complete_tx::bytes [%0], [%1, {0, %2, %3}], [%4];"
                 :: "r"(dst), "l"(map), "r"(y), "r"(z), "r"(bar) : "memory");
}
__host__ __device__ constexpr uint64_t slot_table(int piece) {
    uint64_t t = 0;
    if (piece < 2) for (int s = 0; s < 16; s++) t |= (uint64_t)(unit_of(piece, s) % NSLOT) << (4 * s);
    else for (int s = 0; s < 8; s++) t |= (uint64_t)(unit_of(piece, 2 * s) % NSLOT) << (4 * s);
    return t;
}
struct Maps { CUtensorMap m[4]; };

__device__ __forceinline__ uint32_t bf2_op_epi(int a, int b, uint32_t zc, uint32_t sx, uint32_t sw, uint32_t bi) {
    uint32_t v;
    if (DBG & 1) return a ^ b ^ zc;
    float fa = __int2float_rn(a), fb = __int2float_rn(b);
    asm("cvt.rn.bf16x2.f32 %0, %1, %2;" : "=r"(v) : "f"(fb), "f"(fa));
    asm("sub.rn.bf16x2 %0, %0, %1;" : "+r"(v) : "r"(zc));
    if (CFG_EPI < 2) asm("mul.rn.bf16x2 %0, %0, %1;" : "+r"(v) : "r"(sx));
    if (CFG_EPI == 0) {
        asm("mul.rn.bf16x2 %0, %0, %1;" : "+r"(v) : "r"(sw));
        asm("add.rn.bf16x2 %0, %0, %1;" : "+r"(v) : "r"(bi));
    } else {
        asm("fma.rn.bf16x2 %0, %0, %1, %2;" : "+r"(v) : "r"(sw), "r"(bi));
    }
    return v;
}
struct Par { uint4 zc, sw, bi; };
__device__ __forceinline__ Par ld_par(uint32_t p) { return {lds128(p), lds128(p + TN * 2), lds128(p + TN * 4)}; }
__device__ __forceinline__ uint4 epi_row(const int (&a)[WA / 2], int o, const Par& p, uint32_t sx2) {
    uint4 r;
    r.x = bf2_op_epi(a[o + 0], a[o + 4], p.zc.x, sx2, p.sw.x, p.bi.x);
    r.y = bf2_op_epi(a[o + 8], a[o + 12], p.zc.y, sx2, p.sw.y, p.bi.y);
    r.z = bf2_op_epi(a[o + 1], a[o + 5], p.zc.z, sx2, p.sw.z, p.bi.z);
    r.w = bf2_op_epi(a[o + 9], a[o + 13], p.zc.w, sx2, p.sw.w, p.bi.w);
    return r;
}
__device__ __forceinline__ void release(uint32_t go, int u, int lane, bool k2) {
    const int v = u + NSLOT, n = k2 ? 1 : v < 32 ? 5 : 4, sh = k2 ? 1 : 4;
    const int q = n * v + (n == 4 ? 32 : 0) + lane;
    if (lane < (v < NU ? n : 0)) mbar_arrive_cluster(mapa(go + (q >> sh) * 8, q & ((1 << sh) - 1)));
}

template <bool k2>
__global__ void __launch_bounds__(512, 1)
w8a8_kernel(const __grid_constant__ Maps maps, const char* __restrict__ qx, const char* __restrict__ qw, const __nv_bfloat16* __restrict__ scale_x, const int* __restrict__ zero_x,
            const __nv_bfloat16* __restrict__ scale_w, const __nv_bfloat16* __restrict__ bias,
            __nv_bfloat16* __restrict__ out) {
    extern __shared__ __align__(1024) unsigned char smem_raw[];
    if (!k2) asm volatile("griddepcontrol.launch_dependents;");
    const int b = blockIdx.x + (k2 ? NCTA : 0), r = b & 15, c = k2 ? NCL : b >> 4;
    const unsigned tc = clk();
    if (threadIdx.x < CFG_PF * 64 && !k2) {
        const int a = DA * 64 + (threadIdx.x >> 6) * NCTA + r * NCL + c;
        asm volatile("prefetch.global.L2 [%0];" :: "l"(qx + ((a & 63) * 32 + ((threadIdx.x >> 1) & 31)) * (K_ * 4) + (a >> 6) * 256 + (threadIdx.x & 1) * 128));
    }
    const uint32_t sb = (uint32_t)__cvta_generic_to_shared(smem_raw);
    const uint32_t bars = sb + SM_BAR;
    const unsigned tw = __shfl_sync(~0u, (tc & ~15u) | threadIdx.x >> 5, 0), t0 = tw + CFG_T0;
    const int warp = tw & 15, lane = threadIdx.x & 31;

    if (warp >= 12) {
        asm volatile("barrier.cluster.arrive.relaxed.aligned;" ::: "memory");
        if (warp == 12 && lane == 0) TLREC(0);
        const int t = k2 ? NS + warp - 12 : warp == 13, isw = k2 || warp >= 14, sp = !k2 && warp == 15;
        const int x = sp ? r * NCL + c - (NCTA - NS * 16) : t * 16 + r, a = x * NCL + c, sx = (x * 205) >> 11;
        static_assert(X1 * 10 >= (NS + 4) * 16, "");
        const uint32_t bar = bars + (sp ? B_RAWS : (isw ? B_RAWB : B_RAWA) + 3 + t) * 8;
        if (x >= 0 && elect_one()) {
            mbar_init(bar, 1);
            mbar_expect_tx(bar, 8192);
            const unsigned te = t0 + (k2 ? sched2(x) : (sp ? CFG_TS + (x >> 1) : isw ? time_w(x) : time_x(x)) * CFG_P1);
            while ((int)(te - clk()) > 0) ;
            raw_load(maps.m + isw, isw ? sx * 64 : (a >> 6) * 2,
                     isw ? (sp ? NCL : c) * (TN / 32) + (int)((0x9765483210ull >> ((x - sx * 10) * 4)) & 15) : (a & 63) * 32,
                     sb + (k2 ? SM_A + (5 + t) * 8192 : sp ? SM_A + 12 * 8192 : isw ? SM_STG : SM_A + (13 + (r * NCL + c >= NAJ % NCTA ? t : 2 - 2 * t)) * 8192), bar);
            TLREC(sp ? 249 : 224 + isw * 10 + t);
        }
        __syncwarp();
    }
    if (warp < 8) {
        const uint32_t p = bars + warp * 104;
        if (elect_one()) {
#pragma unroll
            for (int i = 0; i < 13; i++) mbar_init(p + i * 8, 1);
        }
        __syncwarp();
        const int i = warp * 13 + lane;
        if (lane < 13 && i < B_SW) mbar_expect_tx(p + lane * 8, i >= B_PAR ? (i < B_PAR + 2 ? WA * 2 : WB * 2) : (i & 16) || i >= 48 ? 8192 : WA * 64);
        asm volatile("fence.mbarrier_init.release.cluster;" ::: "memory");
    }
    if (warp < 8 || warp == 10) asm volatile("barrier.cluster.arrive.relaxed.aligned;" ::: "memory");

    if (warp < 8) {
        if (warp < 2 && elect_one()) asm volatile("prefetch.tensormap [%0];" :: "l"(maps.m + 2 + warp) : "memory");
        if (CFG_PF7 && warp == 2 && lane < 18 && !k2) {
            const int n = b * 18 + lane + NS * 1024, row = n / 10;
            asm volatile("prefetch.global.L2 [%0];" :: "l"(qw + row * (N_ * 4) + NCL * TN * 4 + (n - row * 10) * 128));
        }
        asm volatile("setmaxnreg.inc.sync.aligned.u32 " STR(CFG_CREG) ";");
        const int wg = warp >> 2;
        const uint32_t sd = (sb & 0x3FFFF) >> 4;
        const unsigned short sxr = __ldg((const unsigned short*)scale_x);
        const uint32_t sx2 = (uint32_t)sxr * 0x10001u;
        const uint32_t par = sb + SM_PAR + (lane & 3) * 16 + wg * 256;
        const uint32_t go = bars + B_GO * 8;
        const int w = warp & 3, pq = (lane >> 2) ^ (lane & 4);
        uint32_t so = (w * 16 + pq) * 128 + (((lane & 3) ^ pq) << 4);
        const int c0 = (w >> 1) * 32 + (lane >> 2) * 4 + (w & 1) * 2, r0 = (lane & 3) * 2;
        uint32_t pp = sb + SM_PAR + (2 * WA + wg * WB + c0) * 2, st0 = r0 * 128 + (((c0 >> 3) ^ r0) << 4) + (c0 & 7) * 2;
        int rq = lane < (k2 ? 1 : 4) ? (k2 ? 1 : 4) * (32 + wg * 8 + NSLOT) + (k2 ? 0 : 32) + lane : 1000;
        asm volatile("" : "+r"(so), "+r"(pp), "+r"(st0), "+r"(rq));
        asm volatile("barrier.cluster.wait.aligned;" ::: "memory");
        if (threadIdx.x == 0) { TLREC(250); TLCLK(251); }
        int a0[WA / 2], a1[WA / 2];
        uint32_t barB = bars + (B_FULLB + wg * 32) * 8;
        wg_fence();
        {
            uint64_t tbl = wg ? slot_table(1) : slot_table(0);
            uint32_t da = (sd + (SM_A >> 4)) | (1 << 16);
            int up = 99;
#pragma unroll 1
            for (int s = 0; s < 16; s++) {
                const uint32_t db = ((sd + (SM_RING >> 4)) | (8 << 16)) + ((uint32_t)tbl & 15) * (SLOT >> 4);
                if (!mbar_test2(bars + (B_FULLA + s) * 8, barB)) {
                    wg_wait<0>();
                    release(go, up, lane, k2); up = 99;
                    mbar_wait2(bars + (B_FULLA + s) * 8, barB);
                }
                wgmma_n160(a0, da, db, s);
                wgmma_n160(a1, da + 256, db, s);
                wg_commit();
                wg_wait<1>();
                release(go, up, lane, k2);
                wgmma_n160(a0, da + 2, db + 16, 1);
                wgmma_n160(a1, da + 258, db + 16, 1);
                wg_commit();
                if (threadIdx.x % 128 == 0) TLREC(256 + wg * 32 + s);
                up = s < X1 ? 2 * s + wg : (wg ? 16 : X1) + s;
                tbl >>= 4; da += 512; barB += 8;
                wg_wait<1>();
            }
            wg_wait<0>();
            release(go, up, lane, k2);
        }
        if (threadIdx.x % 128 == 0) TLREC(1 + wg);
        mbar_wait2(bars + (B_PAR + wg) * 8, bars + B_SW * 8);
        Par P = ld_par(par);
        bool ready = mbar_test(barB);
#define FILL_BEGIN(n0, n1) mbar_wait(bars + (B_FREE + (wg ? n1 : n0)) * 8);                                              \
                           const uint32_t buf = sb + SM_STG + (wg ? (n1 + NBJ) % 3 : (n0 + NBJ) % 3) * 8192;
#define FILL_END(n0, n1) __syncwarp(); if (elect_one()) mbar_arrive(bars + (B_FILL + (wg ? n1 % 3 : n0 % 3)) * 8);        \
                         if (threadIdx.x % 128 == 0) TLREC(16 + (wg ? n1 : n0));
#define FILL_PAIR(a, J, PN, n0, n1)                                                                                     \
        {                                                                                                               \
            const uint4 v0 = epi_row(a, J * 16, P, sx2);                                                                \
            const Par Q = ld_par(par + J * 64 + 64);                                                                    \
            const uint4 v1 = epi_row(a, J * 16 + 2, P, sx2);                                                            \
            FILL_BEGIN(n0, n1)                                                                                          \
            sts128(buf + so, v0); sts128(buf + so + 1024, v1);                                                          \
            if ((PN) >= 0) P = ld_par(par + (PN));                                                                      \
            sts128(buf + (so ^ 64), epi_row(a, J * 16 + 16, Q, sx2));                                                   \
            sts128(buf + (so ^ 64) + 1024, epi_row(a, J * 16 + 18, Q, sx2));                                            \
            FILL_END(n0, n1)                                                                                            \
        }
        constexpr int rn = k2 ? 1 : 4;
#define RELEASE_N() { if (rq < (k2 ? NU : NBJ * 16)) mbar_arrive_cluster(mapa(go + (rq >> rn) * 8, rq & ((1 << rn) - 1))); rq += rn; nrel++; }
#define NARROW(p)                                                                                                       \
        {                                                                                                               \
            uint32_t tbl = (uint32_t)slot_table(p), da = (sd + (SM_A >> 4)) | (1 << 16);                                \
            int nrel = 0;                                                                     \
            wg_fence();                                                                                                 \
            _Pragma("unroll 1") for (int i = 0; i < 8; i++) {                                                           \
                const uint32_t db = ((sd + (SM_RING >> 4)) | (8 << 16)) + (tbl & 15) * (SLOT >> 4);                     \
                if (!ready && !mbar_test(barB)) {                                                                       \
                    if (nrel < i - 1) RELEASE_N()                                                                       \
                    wg_wait<0>();                                                                                       \
                    if (nrel < i) RELEASE_N()                                                                           \
                    mbar_wait(barB);                                                                                    \
                }                                                                                                       \
                _Pragma("unroll") for (int kk = 0; kk < 4; kk++)                                                        \
                    wgmma_t128(t, db + (kk >> 1) * 256 + (kk & 1) * 16, da + (kk >> 1) * 512 + (kk & 1) * 2, kk ? 1 : i); \
                wg_commit();                                                                                            \
                if (threadIdx.x % 128 == 0) TLREC(256 + (p == 2 ? 16 : 48) + i);                                        \
                barB += 8;                                                                                              \
                ready = mbar_test(barB);                                                                                \
                if (nrel < i - 1) RELEASE_N()                                                                           \
                tbl >>= 4; da += 1024;                                                                                  \
                wg_wait<1>();                                                                                           \
            }                                                                                                           \
            if (p == 2) { if (nrel < 7) RELEASE_N() P = ld_par(par); }                                                  \
            else { zc = lds32(pp); sw = lds32(pp + TN * 2); bi = lds32(pp + TN * 4); }                                  \
            wg_wait<0>();                                                                                               \
            if (p == 2) RELEASE_N()                                                                                     \
            if (threadIdx.x % 128 == 0) TLREC(3 + p);                                                                   \
        }
        FILL_PAIR(a0, 0, 128, 0, 2) FILL_PAIR(a0, 2, -1, 1, 3)
        int t[64];
        uint32_t zc, sw, bi;
        if (wg == 0) NARROW(2) else P = ld_par(par);
        FILL_PAIR(a1, 0, 128, 7, 4) FILL_PAIR(a1, 2, 512 - wg * 192, 8, 5)
        {
            const uint4 v0 = epi_row(a0, 64, P, sx2), v1 = epi_row(a0, 66, P, sx2);
            mbar_wait(bars + (B_PAR + 2 + wg) * 8);
            FILL_BEGIN(9, 6)
            const uint32_t s4 = buf + ((so >> 1) & ~63u) + (lane & 3) * 16;
            sts128(s4, v0); sts128(s4 + 512, v1);
            sts128(s4 + 4096, epi_row(a1, 64, P, sx2)); sts128(s4 + 4608, epi_row(a1, 66, P, sx2));
            FILL_END(9, 6)
        }
        if (wg == 1) NARROW(3) else { zc = lds32(pp); sw = lds32(pp + TN * 2); bi = lds32(pp + TN * 4); }
#define FILL_T(h)                                                                                                       \
        {                                                                                                               \
            FILL_BEGIN((10 + h), (12 + h))                                                                              \
            _Pragma("unroll") for (int j = 0; j < 8; j++) {                                                             \
                const int o = h * 32 + j * 4;                                                                           \
                sts32(buf + st0 + j * 1024, bf2_op_epi(t[o], t[o + 2], zc, sx2, sw, bi));                               \
                sts32(buf + (st0 ^ (5 * 128 + 5 * 16)) + j * 1024, bf2_op_epi(t[o + 1], t[o + 3], zc, sx2, sw, bi));    \
            }                                                                                                           \
            FILL_END((10 + h), (12 + h))                                                                                \
        }
        FILL_T(0) FILL_T(1)
        if (DBG & 4) for (int i = 0; i < 56; i++) mbar_wait(bars + i * 8);
        if (threadIdx.x == 0) { TLREC(252); TLCLK(253); }
        TLEND();
        if (threadIdx.x == 128) asm volatile("red.relaxed.gpu.global.add.u32 [%0], 1;" :: "l"(g_epoch + b) : "memory");
    } else {
        const int g = r * NCL + c, na = k2 ? 0 : NAJ / NCTA + (g < NAJ % NCTA);
        int cw = NF;
        if (warp >= 12) {
            asm volatile("setmaxnreg.dec.sync.aligned.u32 72;");
            if (warp < 14) {
                const int c4 = (lane ^ (lane >> 3)) & 3, ln = ((lane >> 2) ^ (lane & 4)) * 2 + (c4 >> 1);
                const uint32_t rd0 = sb + SM_A + 13 * 8192 + ln * 128 + ((((c4 & 1) << 2) ^ (ln & 7)) << 4);
#pragma unroll 1
                for (int t = warp - 12, sl = na == 9 ? t : 2 - 2 * t; t < na; t += 2, sl = sl ? sl - 1 : 2) {
                    const uint32_t rdA = rd0 + sl * 8192;
                    const int a = t * NCTA + g, f = (a & 60) * 4 + (a >> 6);
                    uint4* const d = g_s8 + (f * 4 + (a & 3)) * 128 + lane;
                    uint4 o[4];
                    mbar_wait(bars + (B_RAWA + 3 + t) * 8);
                    if (lane == 0) TLREC(128 + t);
#pragma unroll
                    for (int i = 0; i < 4; i++) {
                        uint4 v0 = lds128(rdA + i * 2048), v1 = lds128((rdA ^ 16) + i * 2048);
                        uint4 v2 = lds128((rdA ^ 32) + i * 2048), v3 = lds128((rdA ^ 48) + i * 2048);
                        o[i].x = pack4(v0.x, v0.y, v0.z, v0.w); o[i].y = pack4(v1.x, v1.y, v1.z, v1.w);
                        o[i].z = pack4(v2.x, v2.y, v2.z, v2.w); o[i].w = pack4(v3.x, v3.y, v3.z, v3.w);
                    }
#pragma unroll
                    for (int i = 0; i < 4; i++) stg128(d + i * 32, o[i]);
                    unsigned rb;
                    if (CFG_WF) asm volatile("fence.proxy.async.global;" ::: "memory");
                    __syncwarp();
                    asm volatile("ld.relaxed.gpu.global.u32 %0, [%1];" : "=r"(rb) : "l"(d + lane * 3) : "memory");
                    if (t < 2) asm volatile("barrier.cluster.wait.aligned;" ::: "memory");
                    if (elect_one()) mbar_arrive(bars + ((t < na - 3 ? B_RAWA : B_AFREE + 13) + sl) * 8);
                    if (lane == 0) TLREC(160 + t);
                    if (__shfl_sync(~0u, rb ^ o[0].x, 0)) asm volatile("fence.acq_rel.gpu;" ::: "memory");
                    if (elect_one()) asm volatile("red.relaxed.gpu.global.add.u32 [%0], 1;" :: "l"(g_flag + (a & 60) * 8 + (a >> 6)) : "memory");
                    if (lane == 0) TLREC(192 + t);
                }
                cw = warp - 12;
            }
            {
                const uint32_t rd0 = sb + (lane >> 3) * 2048 + (lane & 7) * 16;
                const int q7 = g - (NCTA - NS * 16);
                const BJob mb = decode_b(lane == 31 ? q7 & 255 : (lane & 15) * 16 + r);
                const int myG = mb.G | mb.u << 8 | mb.slab << 16;
                bool first = k2 || warp >= 14;
#pragma unroll 1
                for (int t = k2 ? NS + warp - 12 : warp < 14 ? CFG_TB + warp - 10 : (warp == 15 && q7 >= 0) ? -1 : warp - 14; t < NBJ; t += (!k2 && t < CFG_TB) ? 2 : 4) {
                    const bool far = k2 || t < 0;
                    const uint32_t rdB = rd0 + (t < 0 ? SM_A + 12 * 8192 : stage_w<k2>(t));
                    uint4* const d = g_s8 + (1024 + (t < 0 ? NCL * 256 + q7 : c * 256 + t * 16 + r)) * 128 + lane;
                    uint4 o[4];
                    if (!k2 && t == 1 && first) { asm volatile("barrier.cluster.wait.aligned;" ::: "memory"); first = false; }
                    mbar_wait(bars + (t < 0 ? B_RAWS : B_RAWB + 3 + t) * 8);
                    if (lane == 0) TLREC(138 + (t & 15));
#define CV_B(m, f)                                                                                    \
                    {                                                                                 \
                        uint4 v0 = lds128(rdB + m * 512), v1 = lds128(rdB + m * 512 + 128);           \
                        uint4 v2 = lds128(rdB + m * 512 + 256), v3 = lds128(rdB + m * 512 + 384);     \
                        o[0].f = pack4(v0.x, v1.x, v2.x, v3.x); o[1].f = pack4(v0.y, v1.y, v2.y, v3.y); \
                        o[2].f = pack4(v0.z, v1.z, v2.z, v3.z); o[3].f = pack4(v0.w, v1.w, v2.w, v3.w); \
                    }
                    CV_B(0, x) CV_B(1, y) CV_B(2, z) CV_B(3, w)
#pragma unroll
                    for (int i = 0; i < 4; i++) stg128(d + i * 32, o[i]);
                    if (first) { asm volatile("barrier.cluster.wait.aligned;" ::: "memory"); first = false; }
                    if (elect_one()) mbar_arrive(bars + (t < 0 ? B_AFREE + 12 : (k2 || t >= NBJ - 3) ? B_FREE + t - (NBJ - 3) : B_RAWB + t % 3) * 8);
                    asm volatile("fence.proxy.async.global;" ::: "memory");
                    __syncwarp();
                    if (!far && elect_one()) mbar_arrive(bars + (B_GO + t) * 8);
                    if (lane == 0) TLREC(170 + (t & 15));
                    int cs[4];
#pragma unroll
                    for (int i = 0; i < 4; i++)
                        cs[i] = __dp4a((int)o[i].x, 0x01010101, __dp4a((int)o[i].y, 0x01010101,
                                __dp4a((int)o[i].z, 0x01010101, __dp4a((int)o[i].w, 0x01010101, 0))));
                    const bool h = lane & 16, odd = lane & 8;
                    int x = (h ? cs[2] : cs[0]) + __shfl_xor_sync(~0u, h ? cs[0] : cs[2], 16);
                    int y = (h ? cs[3] : cs[1]) + __shfl_xor_sync(~0u, h ? cs[1] : cs[3], 16);
                    const int v = (odd ? y : x) + __shfl_xor_sync(~0u, odd ? x : y, 8);
                    const int gu = __shfl_sync(~0u, myG, t), G = gu & 255;
                    if (far) {
                        int* const p = g_cs[gu >> 16] + col_of(G) + (lane & 7) * 4 + (lane >> 3);
                        *p = v;
                        unsigned rb, rc;
                        asm volatile("ld.relaxed.gpu.global.u32 %0, [%1];" : "=r"(rb) : "l"(d + lane * 3) : "memory");
                        asm volatile("ld.relaxed.gpu.global.u32 %0, [%1];" : "=r"(rc) : "l"(p) : "memory");
                        if (__shfl_sync(~0u, (rb ^ o[0].x) | (rc ^ v), 0)) asm volatile("fence.acq_rel.gpu;" ::: "memory");
                        if (elect_one()) asm volatile("red.relaxed.gpu.global.add.u32 [%0], 1;" :: "l"(g_flag + 512 + ((gu >> 8) & 255)) : "memory");
                    } else if (G != r) {
                        asm volatile("red.async.relaxed.cluster.shared::cluster.mbarrier::complete_tx::bytes.add.s32 [%0], %1, [%2];"
                                     :: "r"(mapa(sb + SM_CS + lane * 4, G)), "r"(v), "r"(mapa(bars + B_CS * 8, G)) : "memory");
                    } else {
                        asm volatile("red.shared.add.s32 [%0], %1;" :: "r"(sb + SM_CS + lane * 4), "r"(v) : "memory");
                        __syncwarp();
                        if (elect_one()) mbar_arrive(bars + B_CS * 8);
                    }
                    if (lane == 0) TLREC(202 + (t & 15));
                }
                if (k2) {
                    const float zxf = __bfloat162float(__float2bfloat16_rn((float)__ldg(zero_x)));
                    const int col = (warp == 15 ? 320 : (warp - 12) * 128) + lane * 4;
                    mbar_wait(bars + (B_RAWA + (warp == 15)) * 8);
                    if (warp != 14 || lane < 16) {
                        int4 a = {0, 0, 0, 0};
#pragma unroll
                        for (int h = 0; h < 16; h += 8) {
                            int4 v[8];
#pragma unroll
                            for (int i = 0; i < 8; i++) v[i] = __ldcg((const int4*)(g_cs[h + i] + col));
#pragma unroll
                            for (int i = 0; i < 8; i++) { a.x += v[i].x; a.y += v[i].y; a.z += v[i].z; a.w += v[i].w; }
                        }
                        uint32_t z0, z1;
#define ZC(x) (__bfloat162float(__float2bfloat16_rn((float)(x))) * zxf)
                        asm("cvt.rn.bf16x2.f32 %0, %1, %2;" : "=r"(z0) : "f"(ZC(a.y)), "f"(ZC(a.x)));
                        asm("cvt.rn.bf16x2.f32 %0, %1, %2;" : "=r"(z1) : "f"(ZC(a.w)), "f"(ZC(a.z)));
                        asm volatile("st.async.weak.shared::cluster.mbarrier::complete_tx::bytes.v2.b32 [%0], {%1, %2}, [%3];"
                                     :: "r"(sb + SM_PAR + col * 2), "r"(z0), "r"(z1),
                                        "r"(bars + (B_PAR + (col < 256 ? col >> 7 : col < 320 ? (col >> 5) & 1 : (col >> 6) - 3)) * 8) : "memory");
                    }
                    __syncwarp();
                    if (lane == 0 && warp >= 14) TLREC(warp - 6);
                }
            }
        } else {
            asm volatile("setmaxnreg.dec.sync.aligned.u32 40;");
            if (warp == 11) {
            if (elect_one()) {
#pragma unroll
                for (int i = 0; i < (k2 ? NU / 2 : NBJ); i++) mbar_init(bars + (B_GO + i) * 8, k2 ? (i * 2 + (r & 1) >= NSLOT ? 9 : 1) : i * 16 + r >= NSLOT * 5 ? 1 + 4 * CS : 1);
#pragma unroll
                for (int i = 0; i < 3; i++) mbar_init(bars + (B_FILL + i) * 8, 4);
            }
            const int u2 = lane * 2 + (r & 1), q = k2 ? (u2 < 32 ? 5 * u2 : 4 * u2 + 32) : (lane & 15) * 16 + r;
            const BJob bj = decode_b(q);
            const int nself = __popc(__ballot_sync(~0u, lane < NBJ && bj.G == r));
            sts32(sb + SM_CS + lane * 4, 0);
            if (lane == 0) {
                mbar_init(bars + B_CS * 8, 1 + nself);
                mbar_expect_tx(bars + B_CS * 8, (16 - nself) * 128);
            }

            asm volatile("fence.mbarrier_init.release.cluster;" ::: "memory");
            asm volatile("barrier.cluster.arrive.relaxed.aligned;" :: "r"(lds32(sb + SM_CS + lane * 4)) : "memory");
            const char* src = (const char*)g_s8 + (1024 + c * 256 + q) * 2048;
            const uint32_t dst = sb + SM_RING + (bj.u % NSLOT) * SLOT + bj.pos * 2048;
            const uint32_t fb = bars + (B_FULLB + fb_of(bj.u)) * 8;
            asm volatile("barrier.cluster.wait.aligned;" ::: "memory");
            {
                const uint32_t sx2 = (uint32_t)__ldg((const unsigned short*)scale_x) * 0x10001u;
#pragma unroll
                for (int i = lane; i < TN / 4; i += 32) {
                    const bool hi = i >= TN / 8;
                    uint4 v = __ldg((const uint4*)((hi ? bias : scale_w) + c * TN) + (hi ? i - TN / 8 : i));
                    if (CFG_EPI == 2 && !hi) {
                        asm("mul.rn.bf16x2 %0, %0, %1;" : "+r"(v.x) : "r"(sx2)); asm("mul.rn.bf16x2 %0, %0, %1;" : "+r"(v.y) : "r"(sx2));
                        asm("mul.rn.bf16x2 %0, %0, %1;" : "+r"(v.z) : "r"(sx2)); asm("mul.rn.bf16x2 %0, %0, %1;" : "+r"(v.w) : "r"(sx2));
                    }
                    sts128(sb + SM_PAR + TN * 2 + i * 16, v);
                }
                __syncwarp();
                if (elect_one()) mbar_arrive(bars + B_SW * 8);
            }
#pragma unroll 1
            for (int i = 0; i < (k2 ? NU / 2 : NBJ); i++) {
                mbar_wait(bars + (B_GO + i) * 8);
                if (lane == i) {
                    asm volatile("cp.async.bulk.shared::cluster.global.mbarrier::complete_tx::bytes.multicast::cluster [%0], [%1], %2, [%3], %4;"
                                 :: "r"(dst), "l"(src), "r"(k2 ? (u2 < 32 ? SLOT : 8192) : 2048), "r"(fb), "h"((uint16_t)(k2 ? 3 : 0xFFFF)) : "memory");
                    TLREC(64 + i);
                }
                __syncwarp();
            }
            } else if (warp == 10) {
            const unsigned ep = (*(volatile unsigned*)&g_epoch[b] + 1) * 4;
            const float zxf = __bfloat162float(__float2bfloat16_rn((float)__ldg(zero_x)));
            const unsigned* f = g_flag + r * 32 + (lane & 15);
            bool dn = lane >= 16;
            const bool fr = lane < (k2 ? 5 + NS : g >= NCTA - NS * 16 ? 12 : 13);
            asm volatile("barrier.cluster.wait.aligned;" ::: "memory");
            if (lane == 0) TLREC(15);
#define CHECK(v)                                                                                                        \
                if (!dn && (int)(v - ep) >= 0 && (fr || mbar_test(bars + (B_AFREE + lane) * 8))) {                 \
                    dn = true;                                                                                          \
                    if (!CFG_WF) asm volatile("fence.proxy.async.global;" ::: "memory");                                \
                    asm volatile("cp.async.bulk.shared::cluster.global.mbarrier::complete_tx::bytes [%0], [%1], %2, [%3];" \
                                 :: "r"(sb + SM_A + lane * 8192), "l"((const char*)g_s8 + (r * 16 + lane) * 8192),      \
                                    "r"(8192), "r"(bars + (B_FULLA + lane) * 8) : "memory");                            \
                    TLREC(112 + lane);                                                                                  \
                }                                                                                                       \
                if (__all_sync(~0u, dn)) break;
            for (int it = 0;; it++) {
                const unsigned v = ld_flag(f);
                CHECK(v)
                if (it > (1 << 22)) __trap();
            }
            if (r < NBJ && !k2) {
            mbar_wait(bars + B_CS * 8);
            const int w = lane & 15;
            const uint32_t ca = sb + SM_CS + ((w >> 1) + (w & 1) * 16) * 4;
            const float lo = __bfloat162float(__float2bfloat16_rn((float)(int)lds32(ca))) * zxf;
            const float hi = __bfloat162float(__float2bfloat16_rn((float)(int)lds32(ca + 32))) * zxf;
            uint32_t z;
            asm("cvt.rn.bf16x2.f32 %0, %1, %2;" : "=r"(z) : "f"(hi), "f"(lo));
            const int piece = r < 10 ? (r >= 5) : (r - 6) >> 1;
#pragma unroll 1
            for (int i = lane >> 4; i < CS; i += 2)
                asm volatile("st.async.weak.shared::cluster.mbarrier::complete_tx::bytes.b32 [%0], %1, [%2];"
                             :: "r"(mapa(sb + SM_PAR + col_of(r) * 2 + w * 4, i)), "r"(z), "r"(mapa(bars + (B_PAR + piece) * 8, i)) : "memory");
            if (lane == 0) TLREC(8);
            }
            } else {
                const bool isw = warp == 9;
                const uint32_t rb = bars + (isw ? B_RAWB : B_RAWA) * 8;
                if (elect_one()) {
#pragma unroll
                    for (int i = 0; i < 13; i++) if (k2 ? (i < 3 + NS || i >= 7 + NS) : (i != 3 && i != 4)) mbar_init(rb + i * 8, 1);
                    if (isw) {
                        asm volatile("prefetch.tensormap [%0];" :: "l"(maps.m + 1) : "memory");
#pragma unroll
                        for (int i = 13; i < 17; i++) mbar_init(rb + i * 8, 1);
                        if (!k2) mbar_init(rb + 4 * 8, 1);
                    }
                }
                __syncwarp();
                const int nj = isw ? NBJ : na, j0 = k2 ? NS + 4 : isw ? 1 : 2;
                if (lane >= j0 && lane < nj) mbar_expect_tx(rb + (3 + lane) * 8, 8192);
                asm volatile("fence.mbarrier_init.release.cluster;" ::: "memory");
                asm volatile("barrier.cluster.arrive.relaxed.aligned;" ::: "memory");
                const int k = lane / 3, x = lane * 16 + r;
                int sl = lane - k * 3, y, z, T;
                if (isw) {
                    const BJob bj = decode_b(x & 255);
                    y = bj.slab * 64; z = (c * TN + col_of(bj.G)) >> 5; T = time_w(x);
                } else {
                    const int a = lane * NCTA + g;
                    y = (a >> 6) * 2; z = (a & 63) * 32; T = time_x(x);
                    if (na == 10) sl = sl ? sl - 1 : 2;
                }
                const unsigned te = t0 + (k2 ? sched2(x) : sched(T));
                const uint32_t sd = sb + (isw ? stage_w<k2>(lane) : SM_A + (13 + sl) * 8192);
#pragma unroll 1
                for (int t = j0; t < nj; t++) {
                    if (lane == t) {
                        if (t >= 3 && !k2) mbar_wait(rb + sl * 8, (k & 1) ^ 1);
                        while ((int)(te - clk()) > 0) ;
                        raw_load(maps.m + isw, y, z, sd, rb + (3 + t) * 8);
                        TLREC(224 + isw * 10 + t);
                    }
                    __syncwarp();
                }
                asm volatile("barrier.cluster.wait.aligned;" ::: "memory");
                if (!isw) cw = 2;
                if (k2 && !isw) {
                    const unsigned ep = *(volatile unsigned*)&g_epoch[b] + 1;
#pragma unroll 1
                    for (int h = 0; h < 2; h++) {
                        bool dn = h && lane >= NU - 32;
                        for (int it = 0;; it++) {
                            if (!dn && (int)(ld_flag(g_flag + 512 + h * 32 + lane) - ep * (5 - h)) >= 0) {
                                dn = true;
                                if ((lane & 1) == (r & 1)) mbar_arrive(bars + (B_GO + h * 16 + (lane >> 1)) * 8);
                            }
                            if (__all_sync(~0u, dn)) break;
                            if (it > (1 << 22)) __trap();
                        }
                        if (elect_one()) mbar_arrive(bars + (B_RAWA + h) * 8);
                    }
                }
            }
        }
#pragma unroll 1
            for (int n = cw, k = 0; n < NF; n += 3, k ^= 1) {
                const int g = n >= 2 && n < 7, m = n < 2 ? n : n < 7 ? n - 2 : n - 5;
                const int x = n >= 10 ? (n >> 1) * 64 : m == 4 ? 256 + g * 32 : g * 128 + (m & 1) * 64;
                const int y = n >= 10 ? (n & 1) * 64 : (m & 2) * 32;
                mbar_wait(bars + (B_FILL + cw) * 8, k);
                asm volatile("fence.proxy.async.shared::cta;" ::: "memory");
                if (!(DBG & 2) && elect_one())
                    asm volatile("cp.async.bulk.tensor.2d.global.shared::cta.tile.bulk_group [%0, {%1, %2}], [%3];"
                                 :: "l"(maps.m + (n < 10 && m == 4 ? 3 : 2)), "r"(c * TN + x), "r"(r * 128 + y), "r"(sb + SM_STG + ((cw + NBJ) % 3) * 8192) : "memory");
                asm volatile("cp.async.bulk.commit_group;" ::: "memory");
                if (lane == 0) TLREC(32 + n);
                asm volatile("cp.async.bulk.wait_group.read 0;" ::: "memory");
                __syncwarp();
                if (n < NF - 3 && elect_one()) mbar_arrive(bars + (B_FREE + 3 + n) * 8);
                if (lane == 0) TLREC(48 + n);
            }
        TLEND();
    }
}

}

typedef CUresult (*EncodeFn)(CUtensorMap*, CUtensorMapDataType, cuuint32_t, void*, const cuuint64_t*, const cuuint64_t*,
                             const cuuint32_t*, const cuuint32_t*, CUtensorMapInterleave, CUtensorMapSwizzle,
                             CUtensorMapL2promotion, CUtensorMapFloatOOBfill);

extern "C" void kernel_launch(void* const* d_in, const int* in_sizes, int n_in, void* d_out, int out_size) {
    using namespace w8;
    static EncodeFn encode = nullptr;
    if (!encode) {
        void* fn = nullptr;
        cudaDriverEntryPointQueryResult qr;
        cudaGetDriverEntryPoint("cuTensorMapEncodeTiled", &fn, cudaEnableDefault, &qr);
        encode = (EncodeFn)fn;
        cudaFuncSetAttribute(w8a8_kernel<false>, cudaFuncAttributeMaxDynamicSharedMemorySize, SM_ALLOC);
        cudaFuncSetAttribute(w8a8_kernel<true>, cudaFuncAttributeMaxDynamicSharedMemorySize, SM_ALLOC);
        cudaFuncSetAttribute(w8a8_kernel<false>, cudaFuncAttributeNonPortableClusterSizeAllowed, 1);
    }
    Maps maps;
    {
        const cuuint64_t dim[3] = {32, K_ / 32, M_}, str[2] = {128, K_ * 4};
        const cuuint32_t box[3] = {32, 2, 32}, es[3] = {1, 1, 1};
        encode(&maps.m[0], CU_TENSOR_MAP_DATA_TYPE_INT32, 3, d_in[0], dim, str, box, es, CU_TENSOR_MAP_INTERLEAVE_NONE,
               CU_TENSOR_MAP_SWIZZLE_128B, CU_TENSOR_MAP_L2_PROMOTION_NONE, CU_TENSOR_MAP_FLOAT_OOB_FILL_NONE);
    }
    {
        const cuuint64_t dim[3] = {32, K_, N_ / 32}, str[2] = {N_ * 4, 128};
        const cuuint32_t box[3] = {32, 64, 1}, es[3] = {1, 1, 1};
        encode(&maps.m[1], CU_TENSOR_MAP_DATA_TYPE_INT32, 3, d_in[1], dim, str, box, es, CU_TENSOR_MAP_INTERLEAVE_NONE,
               CU_TENSOR_MAP_SWIZZLE_NONE, CU_TENSOR_MAP_L2_PROMOTION_NONE, CU_TENSOR_MAP_FLOAT_OOB_FILL_NONE);
    }
    {
        const cuuint64_t dim[2] = {N_, M_}, str[1] = {N_ * 2};
        const cuuint32_t box[2] = {WB, 64}, es[2] = {1, 1};
        encode(&maps.m[2], CU_TENSOR_MAP_DATA_TYPE_BFLOAT16, 2, d_out, dim, str, box, es, CU_TENSOR_MAP_INTERLEAVE_NONE,
               CU_TENSOR_MAP_SWIZZLE_128B, CU_TENSOR_MAP_L2_PROMOTION_NONE, CU_TENSOR_MAP_FLOAT_OOB_FILL_NONE);
    }
    {
        const cuuint64_t dim[2] = {N_, M_}, str[1] = {N_ * 2};
        const cuuint32_t box[2] = {32, 128}, es[2] = {1, 1};
        encode(&maps.m[3], CU_TENSOR_MAP_DATA_TYPE_BFLOAT16, 2, d_out, dim, str, box, es, CU_TENSOR_MAP_INTERLEAVE_NONE,
               CU_TENSOR_MAP_SWIZZLE_NONE, CU_TENSOR_MAP_L2_PROMOTION_NONE, CU_TENSOR_MAP_FLOAT_OOB_FILL_NONE);
    }
    for (int k = 0; k < ((DBG & 32) ? 1 : 2); k++) {
        cudaLaunchConfig_t cfg = {};
        cfg.gridDim = dim3(k ? 16 : NCTA); cfg.blockDim = dim3(512); cfg.dynamicSmemBytes = SM_ALLOC; cfg.stream = cudaStreamPerThread;
        cudaLaunchAttribute at[2];
        at[0].id = cudaLaunchAttributeClusterDimension; at[0].val.clusterDim.x = k ? 2 : CS; at[0].val.clusterDim.y = 1; at[0].val.clusterDim.z = 1;
        at[1].id = cudaLaunchAttributeProgrammaticStreamSerialization; at[1].val.programmaticStreamSerializationAllowed = 1;
        cfg.attrs = at; cfg.numAttrs = 1 + k;
        cudaLaunchKernelEx(&cfg, k ? w8a8_kernel<true> : w8a8_kernel<false>, maps, (const char*)d_in[0], (const char*)d_in[1], (const __nv_bfloat16*)d_in[2], (const int*)d_in[3],
                           (const __nv_bfloat16*)d_in[4], (const __nv_bfloat16*)d_in[5], (__nv_bfloat16*)d_out);
    }
}
```

```cpp
#include <cuda_runtime.h>
#include <cuda.h>
#include <cuda_bf16.h>
#include <stdint.h>

#define CFG_X1 13
#define CFG_P1 46
#define CFG_P2 38
#define CFG_PT 100
#define CFG_L0 32
#define CFG_T0 0
#define CFG_ACQ 0
#define CFG_MODE 1
#define CFG_PF 0
#define CFG_MC 16
#define CFG_NP 2
#define CFG_D 0
#define CFG_NL 2
#define CFG_R4 2
#define CFG_TD 30
#define CFG_TD0 1200
#define CFG_TDS 600
#define CFG_EPI 2
#define CFG_SLEEP 0
#define CFG_POLL2 1
#define CFG_PF2 0
#define CFG_PREG 56
#define CFG_CREG 200
#define STR2(x) #x
#define STR(x) STR2(x)
#define CFG_WF 1
#define CFG_FL 2
#define CFG_TB 8
#define CFG_Q2 60
#define CFG_PF7 0
#define CFG_Q0 16
#define CFG_NS 1
#define CFG_TS 8
#define CFG_Q3 30
#define CFG_RA 34
#define CFG_SH 0
#define CFG_WIN 2
#define CFG_HOLD 14
#define CFG_HS CFG_X1
#define CFG_PRE 1
#define CFG_P3 CFG_P2
#define CFG_PT3 210
#define CFG_LC 1
#define CFG_T3 0
#define CFG_K3L 1
#define CFG_H2 0
#define CFG_D3 3
#define CFG_PROMO 0
#define CFG_RC 80
#define CFG_RO 32
#define CFG_PFIRST 1
#define CFG_CD 1
#define CLUSTER_ATTR __cluster_dims__(k2 ? 2 : 16, 1, 1)
#define CFG_ETM 1
#define CFG_EF 0
#define CFG_RB16 0
#define DBG 0

namespace w8 {

constexpr int M_ = 2048, K_ = 1024, N_ = 3584;
constexpr int CS = 16, NCL = 7, NCTA = CS * NCL;
constexpr int WA = 160, WB = 64;
constexpr int NP = CFG_NP, TN = 2 * WA + NP * WB;
constexpr int DA = CFG_D, NL = CFG_NL, R4 = CFG_R4;
constexpr int NAJ = 1024;
constexpr int X1 = CFG_X1;
constexpr int NSLOT = 7, SLOT = WA * 64;
constexpr int NU1 = 48;
constexpr int NCONV = 4;
constexpr int L0 = CFG_L0, NS = CFG_NS;

constexpr int SM_A = 0;
constexpr int SM_RING = 131072;
constexpr int SM_STG = SM_RING + NSLOT * SLOT;
constexpr int SM_PAR = SM_STG + 3 * 8192;
constexpr int SM_CS = SM_PAR + 3 * TN * 2;
constexpr int SM_BAR = SM_CS + 128;
constexpr int B_FULLB = 0, B_FULLA = 56, B_PAR = 72, B_SW = 77, B_AFREE = 79 - 5  , B_FREE = 90, B_NINIT = 104,
              B_GO = 104, B_FILL = 128, B_CS = 131, B_RAWA = 132, B_RAWB = 145, B_RAWS = 162, B_END = 163;
constexpr int SM_TOTAL = SM_BAR + B_END * 8;
static_assert(SM_TOTAL <= 232448, "");

__device__ uint4 g_s8[(1024 + 8 * 256) * 128];
__device__ unsigned g_flag[1024 + 8192];
__device__ int g_cs[2][TN];
__device__ int g_sink;
__device__ unsigned g_epoch[132];
#define TLE_REC(b, i) do {} while (0)
#define TLREC(i) do {} while (0)
#define TLCLK(i) do {} while (0)
#define TLEND() do {} while (0)
constexpr int SM_ALLOC = SM_TOTAL;

__device__ __forceinline__ void mbar_init(uint32_t bar, uint32_t cnt) {
    asm volatile("mbarrier.init.shared::cta.b64 [%0], %1;" :: "r"(bar), "r"(cnt) : "memory");
}
__device__ __forceinline__ void mbar_expect_tx(uint32_t bar, uint32_t bytes) {
    asm volatile("mbarrier.arrive.expect_tx.shared::cta.b64 _, [%0], %1;" :: "r"(bar), "r"(bytes) : "memory");
}
__device__ __forceinline__ void mbar_arrive(uint32_t bar) {
    asm volatile("mbarrier.arrive.shared::cta.b64 _, [%0];" :: "r"(bar) : "memory");
}
__device__ __forceinline__ void mbar_arrive_cluster(uint32_t bar) {
    asm volatile("mbarrier.arrive.shared::cluster.b64 _, [%0];" :: "r"(bar) : "memory");
}
__device__ __forceinline__ void mbar_wait(uint32_t bar, uint32_t parity = 0) {
    asm volatile("{\n.reg .pred p;\n.reg .u32 c;\n"
                 "mbarrier.try_wait.parity.shared::cta.b64 p, [%0], %1;\n"
                 "@p bra WAIT_DONE;\n"
                 "mov.u32 c, 0;\n"
                 "WAIT_LOOP:\n"
                 "mbarrier.try_wait.parity.shared::cta.b64 p, [%0], %1;\n"
                 "@p bra WAIT_DONE;\n"
                 "add.u32 c, c, 1;\nsetp.lt.u32 p, c, 0x100000;\n"
                 "@p bra WAIT_LOOP;\n"
                 "trap;\n"
                 "WAIT_DONE:\n}" :: "r"(bar), "r"(parity) : "memory");
}
__device__ __forceinline__ void mbar_wait2(uint32_t bar0, uint32_t bar1) {
    asm volatile("{\n.reg .pred p, q;\n.reg .u32 c;\nmov.u32 c, 0;\n"
                 "WAIT_LOOP:\n"
                 "mbarrier.try_wait.parity.shared::cta.b64 p, [%0], 0;\n"
                 "mbarrier.try_wait.parity.shared::cta.b64 q, [%1], 0;\n"
                 "and.pred p, p, q;\n"
                 "@p bra WAIT_DONE;\n"
                 "add.u32 c, c, 1;\nsetp.lt.u32 p, c, 0x100000;\n"
                 "@p bra WAIT_LOOP;\n"
                 "trap;\n"
                 "WAIT_DONE:\n}" :: "r"(bar0), "r"(bar1) : "memory");
}
__device__ __forceinline__ bool mbar_test(uint32_t bar) {
    uint32_t ok;
    asm volatile("{\n.reg .pred p;\nmbarrier.test_wait.parity.shared::cta.b64 p, [%1], 0;\nselp.u32 %0, 1, 0, p;\n}" : "=r"(ok) : "r"(bar) : "memory");
    return ok;
}
__device__ __forceinline__ bool mbar_test2(uint32_t bar0, uint32_t bar1) {
    uint32_t ok;
    asm volatile("{\n.reg .pred p, q;\nmbarrier.test_wait.parity.shared::cta.b64 p, [%1], 0;\n"
                 "mbarrier.test_wait.parity.shared::cta.b64 q, [%2], 0;\nand.pred p, p, q;\nselp.u32 %0, 1, 0, p;\n}"
                 : "=r"(ok) : "r"(bar0), "r"(bar1) : "memory");
    return ok;
}
__device__ __forceinline__ bool elect_one() {
    uint32_t ok;
    asm volatile("{\n.reg .pred p;\nelect.sync _|p, 0xffffffff;\nselp.u32 %0, 1, 0, p;\n}" : "=r"(ok));
    return ok;
}
__device__ __forceinline__ unsigned ld_acquire(const unsigned* p) {
    unsigned v;
    asm volatile("ld.acquire.gpu.global.u32 %0, [%1];" : "=r"(v) : "l"(p) : "memory");
    return v;
}
__device__ __forceinline__ unsigned ld_flag(const unsigned* p) {
    unsigned v;
    asm volatile("ld.relaxed.gpu.global.u32 %0, [%1];" : "=r"(v) : "l"(p) : "memory");
    return v;
}
__device__ __forceinline__ uint4 lds128(uint32_t a) {
    uint4 v;
    asm volatile("ld.shared.v4.b32 {%0,%1,%2,%3}, [%4];" : "=r"(v.x), "=r"(v.y), "=r"(v.z), "=r"(v.w) : "r"(a) : "memory");
    return v;
}
__device__ __forceinline__ void sts128(uint32_t a, uint4 v) {
    asm volatile("st.shared.v4.b32 [%0], {%1,%2,%3,%4};" :: "r"(a), "r"(v.x), "r"(v.y), "r"(v.z), "r"(v.w) : "memory");
}
__device__ __forceinline__ uint32_t lds32(uint32_t a) {
    uint32_t v;
    asm volatile("ld.shared.b32 %0, [%1];" : "=r"(v) : "r"(a) : "memory");
    return v;
}
__device__ __forceinline__ void sts32(uint32_t a, uint32_t v) {
    asm volatile("st.shared.b32 [%0], %1;" :: "r"(a), "r"(v) : "memory");
}
__device__ __forceinline__ void stg128(void* p, uint4 v) {
    asm volatile("st.global.v4.b32 [%0], {%1,%2,%3,%4};" :: "l"(p), "r"(v.x), "r"(v.y), "r"(v.z), "r"(v.w) : "memory");
}
__device__ __forceinline__ unsigned pack4(unsigned a, unsigned b, unsigned c, unsigned d) {
    unsigned lo, r;
    asm("cvt.pack.sat.s8.s32.b32 %0, %1, %2, 0;" : "=r"(lo) : "r"(d), "r"(c));
    asm("cvt.pack.sat.s8.s32.b32 %0, %1, %2, %3;" : "=r"(r) : "r"(b), "r"(a), "r"(lo));
    return r;
}

constexpr uint32_t DESC_A_HI = 0x80000000u | (512 >> 4);
constexpr uint32_t DESC_B_HI = 512 >> 4;
template <int NR> __device__ __forceinline__ void wgmma_n160(int (&d)[NR], uint32_t alo, uint32_t blo, int scale_d) {
    asm volatile("{\n.reg .pred p;\n.reg .b64 da, db;\nsetp.ne.b32 p, %82, 0;\n"
        "mov.b64 da, {%80, %83};\nmov.b64 db, {%81, %84};\n"
        "wgmma.mma_async.sync.aligned.m64n160k32.s32.s8.s8 "
        "{%0, %1, %2, %3, %4, %5, %6, %7, %8, %9, %10, %11, %12, %13, %14, %15, "
        "%16, %17, %18, %19, %20, %21, %22, %23, %24, %25, %26, %27, %28, %29, %30, %31, "
        "%32, %33, %34, %35, %36, %37, %38, %39, %40, %41, %42, %43, %44, %45, %46, %47, "
        "%48, %49, %50, %51, %52, %53, %54, %55, %56, %57, %58, %59, %60, %61, %62, %63, "
        "%64, %65, %66, %67, %68, %69, %70, %71, %72, %73, %74, %75, %76, %77, %78, %79}, "
        "da, db, p;\n}\n"
        : "+r"(d[0]), "+r"(d[1]), "+r"(d[2]), "+r"(d[3]), "+r"(d[4]), "+r"(d[5]), "+r"(d[6]), "+r"(d[7]),
          "+r"(d[8]), "+r"(d[9]), "+r"(d[10]), "+r"(d[11]), "+r"(d[12]), "+r"(d[13]), "+r"(d[14]), "+r"(d[15]),
          "+r"(d[16]), "+r"(d[17]), "+r"(d[18]), "+r"(d[19]), "+r"(d[20]), "+r"(d[21]), "+r"(d[22]), "+r"(d[23]),
          "+r"(d[24]), "+r"(d[25]), "+r"(d[26]), "+r"(d[27]), "+r"(d[28]), "+r"(d[29]), "+r"(d[30]), "+r"(d[31]),
          "+r"(d[32]), "+r"(d[33]), "+r"(d[34]), "+r"(d[35]), "+r"(d[36]), "+r"(d[37]), "+r"(d[38]), "+r"(d[39]),
          "+r"(d[40]), "+r"(d[41]), "+r"(d[42]), "+r"(d[43]), "+r"(d[44]), "+r"(d[45]), "+r"(d[46]), "+r"(d[47]),
          "+r"(d[48]), "+r"(d[49]), "+r"(d[50]), "+r"(d[51]), "+r"(d[52]), "+r"(d[53]), "+r"(d[54]), "+r"(d[55]),
          "+r"(d[56]), "+r"(d[57]), "+r"(d[58]), "+r"(d[59]), "+r"(d[60]), "+r"(d[61]), "+r"(d[62]), "+r"(d[63]),
          "+r"(d[64]), "+r"(d[65]), "+r"(d[66]), "+r"(d[67]), "+r"(d[68]), "+r"(d[69]), "+r"(d[70]), "+r"(d[71]),
          "+r"(d[72]), "+r"(d[73]), "+r"(d[74]), "+r"(d[75]), "+r"(d[76]), "+r"(d[77]), "+r"(d[78]), "+r"(d[79])
        : "r"(alo), "r"(blo), "r"(scale_d), "r"(DESC_A_HI), "r"(DESC_B_HI));
}
template <int NR> __device__ __forceinline__ void wgmma_t128(int (&d)[NR], uint32_t alo, uint32_t blo, int scale_d) {
    asm volatile("{\n.reg .pred p;\n.reg .b64 da, db;\nsetp.ne.b32 p, %66, 0;\n"
        "mov.b64 da, {%64, %67};\nmov.b64 db, {%65, %68};\n"
        "wgmma.mma_async.sync.aligned.m64n128k32.s32.s8.s8 "
        "{%0, %1, %2, %3, %4, %5, %6, %7, %8, %9, %10, %11, %12, %13, %14, %15, "
        "%16, %17, %18, %19, %20, %21, %22, %23, %24, %25, %26, %27, %28, %29, %30, %31, "
        "%32, %33, %34, %35, %36, %37, %38, %39, %40, %41, %42, %43, %44, %45, %46, %47, "
        "%48, %49, %50, %51, %52, %53, %54, %55, %56, %57, %58, %59, %60, %61, %62, %63}, "
        "da, db, p;\n}\n"
        : "+r"(d[0]), "+r"(d[1]), "+r"(d[2]), "+r"(d[3]), "+r"(d[4]), "+r"(d[5]), "+r"(d[6]), "+r"(d[7]),
          "+r"(d[8]), "+r"(d[9]), "+r"(d[10]), "+r"(d[11]), "+r"(d[12]), "+r"(d[13]), "+r"(d[14]), "+r"(d[15]),
          "+r"(d[16]), "+r"(d[17]), "+r"(d[18]), "+r"(d[19]), "+r"(d[20]), "+r"(d[21]), "+r"(d[22]), "+r"(d[23]),
          "+r"(d[24]), "+r"(d[25]), "+r"(d[26]), "+r"(d[27]), "+r"(d[28]), "+r"(d[29]), "+r"(d[30]), "+r"(d[31]),
          "+r"(d[32]), "+r"(d[33]), "+r"(d[34]), "+r"(d[35]), "+r"(d[36]), "+r"(d[37]), "+r"(d[38]), "+r"(d[39]),
          "+r"(d[40]), "+r"(d[41]), "+r"(d[42]), "+r"(d[43]), "+r"(d[44]), "+r"(d[45]), "+r"(d[46]), "+r"(d[47]),
          "+r"(d[48]), "+r"(d[49]), "+r"(d[50]), "+r"(d[51]), "+r"(d[52]), "+r"(d[53]), "+r"(d[54]), "+r"(d[55]),
          "+r"(d[56]), "+r"(d[57]), "+r"(d[58]), "+r"(d[59]), "+r"(d[60]), "+r"(d[61]), "+r"(d[62]), "+r"(d[63])
        : "r"(alo), "r"(blo), "r"(scale_d), "r"(DESC_B_HI), "r"(DESC_A_HI));
}

__device__ __forceinline__ void wg_fence() { asm volatile("wgmma.fence.sync.aligned;" ::: "memory"); }
__device__ __forceinline__ void wg_commit() { asm volatile("wgmma.commit_group.sync.aligned;" ::: "memory"); }
template <int N> __device__ __forceinline__ void wg_wait() { asm volatile("wgmma.wait_group.sync.aligned %0;" :: "n"(N) : "memory"); }

__device__ __forceinline__ uint32_t mapa(uint32_t a, uint32_t r) {
    uint32_t o;
    asm("mapa.shared::cluster.u32 %0, %1, %2;" : "=r"(o) : "r"(a), "r"(r));
    return o;
}
__device__ __forceinline__ unsigned clk() {
    unsigned t;
    asm volatile("mov.u32 %0, %clock;" : "=r"(t));
    return t;
}
__host__ __device__ constexpr int unit_of(int piece, int slab) {
    return piece < 2 ? (slab < X1 ? 2 * slab + piece : (piece ? 16 : X1) + slab) : 32 + (piece - 2) * 8 + (slab >> 1);
}
__host__ __device__ constexpr int col_of(int G) { return G == 4 ? 256 : (G > 4 && G < 9) ? 32 * G - 32 : 32 * G; }
struct BJob { int u, slab, G, pos; };
__host__ __device__ constexpr BJob decode_b(int q) {
    BJob j = {};
    if (q < 160) {
        j.u = q / 5; j.pos = q - j.u * 5;
        const int piece = j.u < 2 * X1 ? (j.u & 1) : (j.u >= X1 + 16);
        j.slab = j.u < 2 * X1 ? (j.u >> 1) : j.u - (piece ? 16 : X1);
        j.G = piece * 5 + j.pos;
    } else {
        q -= 160;
        j.u = 32 + (q >> 2); j.pos = q & 3;
        j.slab = (q >> 1) & 15;
        j.G = 10 + (q >> 5) * 2 + (q & 1);
    }
    return j;
}
__host__ __device__ constexpr int fb_of(int u) {
    return u < 2 * X1 ? (u & 1) * 32 + (u >> 1) : u < X1 + 16 ? u - X1 : u < 32 ? 16 + u : u < 40 ? u - 16 : u < 48 ? u + 8 : u - 24;
}
template <bool k2> __device__ __forceinline__ int stage_w(int t) { return (k2 && t < 9) ? SM_A + (7 + t) * 8192 : SM_STG + (t % 3) * 8192; }
constexpr int RA = CFG_RA, RB64 = 64 * RA / (RA - 16);
__device__ __forceinline__ int time_x(int x) { return max(x, L0 + (((x - L0) * RA) >> 4)) + (x >= 16 ? CFG_SH : 0); }
__device__ __forceinline__ int time_w(int q) { return min(L0 + ((q * RB64) >> 6), NAJ / NCL + q) + CFG_SH; }
__device__ __forceinline__ int sched2(int x) { return (min(x, 160) - CFG_Q0) * CFG_Q2 + max(x - 160, 0) * CFG_Q3; }
__device__ __forceinline__ unsigned sched(int T) { return T * CFG_P2 + min(T, CFG_PT) * (CFG_P1 - CFG_P2) + max(T - CFG_PT3, 0) * (CFG_P3 - CFG_P2); }
__device__ __forceinline__ void raw_load(const void* map, int y, int z, uint32_t dst, uint32_t bar) {
    asm volatile("cp.async.bulk.tensor.3d.shared::cluster.global.tile.mbarrier::complete_tx::bytes [%0], [%1, {0, %2, %3}], [%4];"
                 :: "r"(dst), "l"(map), "r"(y), "r"(z), "r"(bar) : "memory");
}
__host__ __device__ constexpr uint64_t slot_table(int piece) {
    uint64_t t = 0;
    if (piece < 2) for (int s = 0; s < 16; s++) t |= (uint64_t)(unit_of(piece, s) % NSLOT) << (4 * s);
    else for (int s = 0; s < 8; s++) t |= (uint64_t)(unit_of(piece, 2 * s) % NSLOT) << (4 * s);
    return t;
}
struct Maps { CUtensorMap m[4]; };

__device__ __forceinline__ uint32_t bf2_op_epi(int a, int b, uint32_t zc, uint32_t sx, uint32_t sw, uint32_t bi) {
    uint32_t v;
    if (DBG & 1) return a ^ b ^ zc;
    float fa = __int2float_rn(a), fb = __int2float_rn(b);
    asm("cvt.rn.bf16x2.f32 %0, %1, %2;" : "=r"(v) : "f"(fb), "f"(fa));
    asm("sub.rn.bf16x2 %0, %0, %1;" : "+r"(v) : "r"(zc));
    if (CFG_EPI < 2) asm("mul.rn.bf16x2 %0, %0, %1;" : "+r"(v) : "r"(sx));
    if (CFG_EPI == 0) {
        asm("mul.rn.bf16x2 %0, %0, %1;" : "+r"(v) : "r"(sw));
        asm("add.rn.bf16x2 %0, %0, %1;" : "+r"(v) : "r"(bi));
    } else {
        asm("fma.rn.bf16x2 %0, %0, %1, %2;" : "+r"(v) : "r"(sw), "r"(bi));
    }
    return v;
}
struct Par { uint4 zc, sw, bi; };
__device__ __forceinline__ Par ld_par(uint32_t p) { return {lds128(p), lds128(p + TN * 2), lds128(p + TN * 4)}; }
__device__ __forceinline__ uint4 epi_row(const int (&a)[WA / 2], int o, const Par& p, uint32_t sx2) {
    uint4 r;
    r.x = bf2_op_epi(a[o + 0], a[o + 4], p.zc.x, sx2, p.sw.x, p.bi.x);
    r.y = bf2_op_epi(a[o + 8], a[o + 12], p.zc.y, sx2, p.sw.y, p.bi.y);
    r.z = bf2_op_epi(a[o + 1], a[o + 5], p.zc.z, sx2, p.sw.z, p.bi.z);
    r.w = bf2_op_epi(a[o + 9], a[o + 13], p.zc.w, sx2, p.sw.w, p.bi.w);
    return r;
}
__device__ __forceinline__ void release(uint32_t go, int u, int lane, bool k2) {
    const int v = u + NSLOT, n = k2 ? 1 : v < 32 ? 5 : 4, sh = k2 ? 1 : 4;
    const int q = n * v + (n == 4 ? 32 : 0) + lane;
    if (lane < (v < NU1 ? n : 0)) mbar_arrive_cluster(mapa(go + (q >> sh) * 8, q & ((1 << sh) - 1)));
}

#define READ_BACK asm volatile("ld.relaxed.gpu.global.u32 %0, [%1];" : "=r"(rb) : "l"(d + lane * 3) : "memory");
#define CV_B(m, f)                                                                                    \
                    {                                                                                 \
                        uint4 v0 = lds128(rdB + m * 512), v1 = lds128(rdB + m * 512 + 128);           \
                        uint4 v2 = lds128(rdB + m * 512 + 256), v3 = lds128(rdB + m * 512 + 384);     \
                        o[0].f = pack4(v0.x, v1.x, v2.x, v3.x); o[1].f = pack4(v0.y, v1.y, v2.y, v3.y); \
                        o[2].f = pack4(v0.z, v1.z, v2.z, v3.z); o[3].f = pack4(v0.w, v1.w, v2.w, v3.w); \
                    }

__device__ __forceinline__ void last_columns(const Maps& maps, const __nv_bfloat16* scale_x, const int* zero_x, const __nv_bfloat16* scale_w,
                                             const __nv_bfloat16* bias, uint32_t sb, int warp, int lane, unsigned t0) {
    constexpr int C_FULL = 0, C_EMPTY = 32, C_RAW = 64, C_GO = 72;
    const uint32_t bars = sb + SM_BAR;
    const int j = blockIdx.x & 3;
    if (warp < 8) {
        if (elect_one()) {
#pragma unroll
            for (int i = 0; i < 4; i++) { mbar_init(bars + (C_FULL + warp * 4 + i) * 8, 1); mbar_expect_tx(bars + (C_FULL + warp * 4 + i) * 8, 16384); }
#pragma unroll
            for (int i = 0; i < 4; i++) mbar_init(bars + (C_EMPTY + warp * 4 + i) * 8, 4);
            mbar_init(bars + (C_RAW + warp) * 8, 1);
            if (warp == 0) mbar_init(bars + C_GO * 8, 8);
        }
        if (warp < 2) sts32(sb + SM_PAR + threadIdx.x * 4, 0);
    }
    __syncthreads();
    if (warp >= 8) {
        asm volatile("setmaxnreg.dec.sync.aligned.u32 40;");
        if (warp < 12) {
            const unsigned ep = (*(volatile unsigned*)&g_epoch[128 + j] + 1) * 4;
            const int mb = j * 4 + warp - 8, wg = (warp >> 1) & 1;
            unsigned rdy = 0;
            mbar_wait(bars + C_GO * 8);
#pragma unroll 1
            for (int s = 0; s < 16; s++) {
                for (int it = 0; !((rdy >> s) & 1); it++) {
                    rdy = __ballot_sync(~0u, (int)(ld_flag(g_flag + mb * 32 + (lane & 15)) - ep) >= 0);
                    if (it > (1 << 22)) __trap();
                }
                if (s >= CFG_D3) mbar_wait(bars + (C_EMPTY + (s - CFG_D3) * 2 + wg) * 8);
                if (elect_one())
                    asm volatile("cp.async.bulk.shared::cluster.global.mbarrier::complete_tx::bytes [%0], [%1], %2, [%3];"
                                 :: "r"(sb + SM_A + ((s & 3) * 4 + warp - 8) * 8192), "l"((const char*)g_s8 + (mb * 16 + s) * 8192),
                                    "r"(8192), "r"(bars + (C_FULL + s * 2 + wg) * 8) : "memory");
            }
        }
    } else {
        asm volatile("setmaxnreg.inc.sync.aligned.u32 200;");
        const int wg = warp >> 2, w = warp & 3;
        const int c0 = (w >> 1) * 32 + (lane >> 2) * 4 + (w & 1) * 2, r0 = (lane & 3) * 2;
        const uint32_t sx2 = (uint32_t)__ldg((const unsigned short*)scale_x) * 0x10001u;
        uint32_t sw = __ldg((const unsigned*)(scale_w + N_ - WB + c0));
        const uint32_t bi = __ldg((const unsigned*)(bias + N_ - WB + c0));
        const float zxf = __bfloat162float(__float2bfloat16_rn((float)__ldg(zero_x)));
        if (CFG_EPI == 2) asm("mul.rn.bf16x2 %0, %0, %1;" : "+r"(sw) : "r"(sx2));
        const uint32_t rdB = sb + SM_A + warp * 8192 + (lane >> 3) * 2048 + (lane & 7) * 16;
        int cs[4] = {0, 0, 0, 0};
        while ((int)(t0 + CFG_T3 - clk()) > 0) ;
#pragma unroll 1
        for (int i = 0; i < 4; i++) {
            const int s = (warp >> 1) * 4 + ((i + j) & 3);
            if (elect_one()) {
                mbar_expect_tx(bars + (C_RAW + warp) * 8, 8192);
                raw_load(maps.m + 1, s * 64, N_ / 32 - 2 + (warp & 1), sb + SM_A + warp * 8192, bars + (C_RAW + warp) * 8);
            }
            mbar_wait(bars + (C_RAW + warp) * 8, i & 1);
            uint4 o[4];
            CV_B(0, x) CV_B(1, y) CV_B(2, z) CV_B(3, w)
#pragma unroll
            for (int k = 0; k < 4; k++) {
                sts128(sb + SM_RING + s * 4096 + (warp & 1) * 2048 + k * 512 + lane * 16, o[k]);
                cs[k] = __dp4a((int)o[k].x, 0x01010101, __dp4a((int)o[k].y, 0x01010101,
                        __dp4a((int)o[k].z, 0x01010101, __dp4a((int)o[k].w, 0x01010101, cs[k]))));
            }
            __syncwarp();
        }
        if (elect_one()) mbar_arrive(bars + C_GO * 8);
#pragma unroll
        for (int k = 0; k < 4; k++)
            asm volatile("red.shared.add.s32 [%0], %1;" :: "r"(sb + SM_PAR + ((warp & 1) * 32 + (lane & 7) * 4 + k) * 4), "r"(cs[k]) : "memory");
        asm volatile("fence.proxy.async.shared::cta;" ::: "memory");
        asm volatile("bar.sync 1, 256;" ::: "memory");
        if (threadIdx.x == 0) TLE_REC(128 + j, 4);
        uint32_t zc;
        asm("cvt.rn.bf16x2.f32 %0, %1, %2;" : "=r"(zc) : "f"(__bfloat162float(__float2bfloat16_rn((float)(int)lds32(sb + SM_PAR + c0 * 4 + 4))) * zxf),
                                                         "f"(__bfloat162float(__float2bfloat16_rn((float)(int)lds32(sb + SM_PAR + c0 * 4))) * zxf));
        const uint32_t sd = (sb & 0x3FFFF) >> 4;
        int t[2][64];
        wg_fence();
#pragma unroll 1
        for (int s = 0; s < 16; s++) {
            const uint32_t db = ((sd + (SM_RING >> 4)) | (8 << 16)) + s * 256, da = ((sd + (SM_A >> 4)) | (1 << 16)) + ((s & 3) * 4 + wg * 2) * 512;
            mbar_wait(bars + (C_FULL + s * 2 + wg) * 8);
            wgmma_t128(t[0], db, da, s);
            wgmma_t128(t[1], db, da + 512, s);
            wgmma_t128(t[0], db + 16, da + 2, 1);
            wgmma_t128(t[1], db + 16, da + 514, 1);
            wg_commit();
            wg_wait<0>();
            if (elect_one()) mbar_arrive(bars + (C_EMPTY + s * 2 + wg) * 8);
        }
        asm volatile("bar.sync %0, 128;" :: "r"(3 + wg) : "memory");
        if (threadIdx.x == 0) TLE_REC(128 + j, 5);
        const uint32_t st0 = sb + SM_A + wg * 16384 + r0 * 128 + (((c0 >> 3) ^ r0) << 4) + (c0 & 7) * 2;
#pragma unroll
        for (int h = 0; h < 4; h++) {
            const uint32_t off = (h >> 1) * 32768 + (h & 1) * 8192;
#pragma unroll
            for (int q = 0; q < 8; q++) {
                const int o = (h & 1) * 32 + q * 4;
                sts32(st0 + off + q * 1024, bf2_op_epi(t[h >> 1][o], t[h >> 1][o + 2], zc, sx2, sw, bi));
                sts32((st0 ^ (5 * 128 + 5 * 16)) + off + q * 1024, bf2_op_epi(t[h >> 1][o + 1], t[h >> 1][o + 3], zc, sx2, sw, bi));
            }
            asm volatile("fence.proxy.async.shared::cta;" ::: "memory");
            asm volatile("bar.sync %0, 128;" :: "r"(3 + wg) : "memory");
            if (w == 0 && elect_one())
                asm volatile("cp.async.bulk.tensor.2d.global.shared::cta.tile.bulk_group [%0, {%1, %2}], [%3];"
                             :: "l"(maps.m + 2), "r"(N_ - WB), "r"(j * 512 + wg * 256 + h * 64), "r"(sb + SM_A + wg * 16384 + off) : "memory");
        }
        if (w == 0) {
            asm volatile("cp.async.bulk.commit_group;" ::: "memory");
            asm volatile("cp.async.bulk.wait_group.read 0;" ::: "memory");
        }
        asm volatile("bar.sync 1, 256;" ::: "memory");
        if (threadIdx.x == 0) asm volatile("red.relaxed.gpu.global.add.u32 [%0], 1;" :: "l"(g_epoch + 128 + j) : "memory");
        if (threadIdx.x == 0) TLE_REC(128 + j, 1);
    }
}

template <bool k2>
__global__ void CLUSTER_ATTR __launch_bounds__(512, 1)
w8a8_kernel(
            const char* __restrict__ qx, const __nv_bfloat16* __restrict__ scale_x, const int* __restrict__ zero_x,
            const __nv_bfloat16* __restrict__ scale_w, const __nv_bfloat16* __restrict__ bias
            , const __grid_constant__ Maps maps
            ) {
    extern __shared__ __align__(1024) unsigned char smem_raw[];
    if (!k2 && !CFG_LC) asm volatile("griddepcontrol.launch_dependents;");
    constexpr int NBJ = k2 ? 12 : 14, NF = NBJ, NU = k2 ? 40 : NU1;
    const int b = blockIdx.x + (k2 ? NCTA - (CFG_K3L ? 0 : 4) : 0), r = b & 15, c = k2 ? NCL : b >> 4;
    const unsigned tc = clk();
    if (threadIdx.x < CFG_PF * 64 && !k2) {
        const int a = (threadIdx.x >> 6) * NCTA + r * NCL + c;
        asm volatile("prefetch.global.L2 [%0];" :: "l"(qx + ((a & 63) * 32 + ((threadIdx.x >> 1) & 31)) * (K_ * 4) + (a >> 6) * 256 + (threadIdx.x & 1) * 128));
    }
    const uint32_t sb = (uint32_t)__cvta_generic_to_shared(smem_raw);
    const uint32_t bars = sb + SM_BAR;
    const unsigned tw = __shfl_sync(~0u, (tc & ~15u) | threadIdx.x >> 5, 0), t0 = tw + CFG_T0;
    const int warp = tw & 15, lane = threadIdx.x & 31;

    if (CFG_ETM && warp >= 8 && warp < 10 && elect_one()) asm volatile("prefetch.tensormap [%0];" :: "l"(maps.m + (warp & 1)) : "memory");
    if (k2 && (CFG_K3L ? blockIdx.x >= 16 : blockIdx.x < 4)) {
        if (!(DBG & 64)) last_columns(maps, scale_x, zero_x, scale_w, bias, sb, warp, lane, t0);
        return;
    }
    if (warp >= 12) {
        asm volatile("barrier.cluster.arrive.relaxed.aligned;" ::: "memory");
        if (warp == 12 && lane == 0) TLREC(0);
        const int t = k2 ? warp - 12 : warp & 1, isw = k2 || warp >= 14;
        const int x = t * 16 + r, a = x * NCL + c, sx = (x * 26) >> 8;
        static_assert(X1 >= 7, "");
        const uint32_t bar = bars + ((isw ? B_RAWB : B_RAWA) + 3 + t) * 8;
        if (elect_one()) {
            mbar_init(bar, 1);
            mbar_expect_tx(bar, 8192);
            const unsigned te = t0 + (k2 ? sched2(x) : (isw ? time_w(x) : time_x(x)) * CFG_P1);
            while ((int)(te - clk()) > 0) ;
            raw_load(maps.m + isw, isw ? sx * 64 : (a >> 6) * 2,
                     isw ? c * (TN / 32) + (int)((0x9765483210ull >> ((x - sx * 10) * 4)) & 15) : (a & 63) * 32,
                     sb + (k2 ? SM_A + 7 * 8192 : isw ? SM_STG : SM_A + 13 * 8192) + ((isw || r * NCL + c >= NAJ % NCTA) ? t : 2 - 2 * t) * 8192, bar);
            TLREC(224 + isw * 10 + t);
        }
        __syncwarp();
    }
    if (threadIdx.x == 0) TLE_REC(b, 0);
    if (warp < 8) {
        const uint32_t p = bars + warp * 104;
        if (elect_one()) {
#pragma unroll
            for (int i = 0; i < 13; i++) mbar_init(p + i * 8, 1);
        }
        __syncwarp();
        const int i = warp * 13 + lane;
        if (lane < 13 && i < B_SW) mbar_expect_tx(p + lane * 8, i >= B_PAR ? (i < B_PAR + 2 ? WA * 2 : WB * 2) : (i & 16) || i >= 48 ? 8192 : WA * 64);
        asm volatile("fence.mbarrier_init.release.cluster;" ::: "memory");
    }
    if (warp < 8 || warp == 10) asm volatile("barrier.cluster.arrive.relaxed.aligned;" ::: "memory");

    if (warp < 8) {
        if (warp < 2 && elect_one()) asm volatile("prefetch.tensormap [%0];" :: "l"(maps.m + 2 + warp) : "memory");
        asm volatile("setmaxnreg.inc.sync.aligned.u32 " STR(CFG_CREG) ";");
        const int wg = warp >> 2;
        const uint32_t sd = (sb & 0x3FFFF) >> 4;
        const unsigned short sxr = __ldg((const unsigned short*)scale_x);
        const uint32_t sx2 = (uint32_t)sxr * 0x10001u;
        const uint32_t par = sb + SM_PAR + (lane & 3) * 16 + wg * 256;
        const uint32_t go = bars + B_GO * 8;
        const int w = warp & 3, pq = (lane >> 2) ^ (lane & 4);
        uint32_t so = (w * 16 + pq) * 128 + (((lane & 3) ^ pq) << 4);
        const int c0 = (w >> 1) * 32 + (lane >> 2) * 4 + (w & 1) * 2, r0 = (lane & 3) * 2;
        uint32_t pp = sb + SM_PAR + (2 * WA + wg * WB + c0) * 2, st0 = r0 * 128 + (((c0 >> 3) ^ r0) << 4) + (c0 & 7) * 2;
        int rq = lane < (k2 ? 1 : 4) ? (k2 ? 1 : 4) * (32 + wg * 8 + NSLOT) + (k2 ? 0 : 32) + lane : 1000;
        asm volatile("" : "+r"(so), "+r"(pp), "+r"(st0), "+r"(rq));
        asm volatile("barrier.cluster.wait.aligned;" ::: "memory");
        if (threadIdx.x == 0) { TLREC(250); TLCLK(251); }
        int a0[WA / 2], a1[WA / 2];
        uint32_t barB = bars + (B_FULLB + wg * 32) * 8;
        wg_fence();
        {
            uint64_t tbl = wg ? slot_table(1) : slot_table(0);
            uint32_t da = (sd + (SM_A >> 4)) | (1 << 16);
            int up = 99;
#pragma unroll 1
            for (int s = 0; s < 16; s++) {
                const uint32_t db = ((sd + (SM_RING >> 4)) | (8 << 16)) + ((uint32_t)tbl & 15) * (SLOT >> 4);
                const bool hold = CFG_HOLD && (CFG_H2 || !k2) && wg && s == CFG_HS;
                if (hold || !mbar_test2(bars + (B_FULLA + s) * 8, barB)) {
                    wg_wait<0>();
                    release(go, up, lane, k2); up = 99;
                    mbar_wait2(bars + (B_FULLA + s) * 8, barB);
                    if (hold) asm volatile("bar.sync 7, 256;" ::: "memory");
                }
                wgmma_n160(a0, da, db, s);
                wgmma_n160(a1, da + 256, db, s);
                wg_commit();
                if (CFG_HOLD && (CFG_H2 || !k2) && !wg && s == CFG_HOLD) asm volatile("bar.arrive 7, 256;" ::: "memory");
                wg_wait<1>();
                release(go, up, lane, k2);
                wgmma_n160(a0, da + 2, db + 16, 1);
                wgmma_n160(a1, da + 258, db + 16, 1);
                wg_commit();
                if (threadIdx.x % 128 == 0) TLREC(256 + wg * 32 + s);
                up = s < X1 ? 2 * s + wg : (wg ? 16 : X1) + s;
                tbl >>= 4; da += 512; barB += 8;
                if (s < 15) wg_wait<1>();
            }
        }
        mbar_wait2(bars + (B_PAR + wg) * 8, bars + B_SW * 8);
        Par P = ld_par(par);
        wg_wait<0>();
        release(go, wg ? 31 : X1 + 15, lane, k2);
        if (threadIdx.x % 128 == 0) { TLREC(1 + wg); TLE_REC(b, 4 + wg); }
        bool ready = mbar_test(barB);
#define FILL_BEGIN(n0, n1) mbar_wait(bars + (B_FREE + (wg ? n1 : n0)) * 8);                                              \
                           const uint32_t buf = sb + SM_STG + (wg ? (n1 + NBJ) % 3 : (n0 + NBJ) % 3) * 8192;
#define FILL_END(n0, n1) __syncwarp(); if (elect_one()) mbar_arrive(bars + (B_FILL + (wg ? n1 % 3 : n0 % 3)) * 8);        \
                         if (threadIdx.x % 128 == 0) TLREC(16 + (wg ? n1 : n0));
#define FILL_PAIR(a, J, PN, n0, n1)                                                                                     \
        {                                                                                                               \
            const uint4 v0 = epi_row(a, J * 16, P, sx2);                                                                \
            const Par Q = ld_par(par + J * 64 + 64);                                                                    \
            const uint4 v1 = epi_row(a, J * 16 + 2, P, sx2);                                                            \
            FILL_BEGIN(n0, n1)                                                                                          \
            sts128(buf + so, v0); sts128(buf + so + 1024, v1);                                                          \
            if ((PN) >= 0) P = ld_par(par + (PN));                                                                      \
            sts128(buf + (so ^ 64), epi_row(a, J * 16 + 16, Q, sx2));                                                   \
            sts128(buf + (so ^ 64) + 1024, epi_row(a, J * 16 + 18, Q, sx2));                                            \
            FILL_END(n0, n1)                                                                                            \
        }
        constexpr int rn = k2 ? 1 : 4;
#define RELEASE_N() { if (rq < (k2 ? NU : NBJ * 16)) mbar_arrive_cluster(mapa(go + (rq >> rn) * 8, rq & ((1 << rn) - 1))); rq += rn; nrel++; }
#define NARROW(p)                                                                                                       \
        {                                                                                                               \
            uint32_t tbl = (uint32_t)slot_table(p), da = (sd + (SM_A >> 4)) | (1 << 16);                                \
            int nrel = 0;                                                                     \
            wg_fence();                                                                                                 \
            _Pragma("unroll 1") for (int i = 0; i < 8; i++) {                                                           \
                const uint32_t db = ((sd + (SM_RING >> 4)) | (8 << 16)) + (tbl & 15) * (SLOT >> 4);                     \
                if (!ready && !mbar_test(barB)) {                                                                       \
                    if (nrel < i - 1) RELEASE_N()                                                                       \
                    wg_wait<0>();                                                                                       \
                    if (nrel < i) RELEASE_N()                                                                           \
                    mbar_wait(barB);                                                                                    \
                }                                                                                                       \
                _Pragma("unroll") for (int kk = 0; kk < 4; kk++)                                                        \
                    wgmma_t128(t, db + (kk >> 1) * 256 + (kk & 1) * 16, da + (kk >> 1) * 512 + (kk & 1) * 2, kk ? 1 : i); \
                wg_commit();                                                                                            \
                if (threadIdx.x % 128 == 0) TLREC(256 + (p == 2 ? 16 : 48) + i);                                        \
                barB += 8;                                                                                              \
                ready = mbar_test(barB);                                                                                \
                if (nrel < i - 1) RELEASE_N()                                                                           \
                tbl >>= 4; da += 1024;                                                                                  \
                wg_wait<1>();                                                                                           \
            }                                                                                                           \
            if (p == 2) { if (nrel < 7) RELEASE_N() P = ld_par(par); }                                                  \
            else { zc = lds32(pp); sw = lds32(pp + TN * 2); bi = lds32(pp + TN * 4); }                                  \
            wg_wait<0>();                                                                                               \
            if (p == 2) RELEASE_N()                                                                                     \
            if (threadIdx.x % 128 == 0) TLREC(3 + p);                                                                   \
        }
        FILL_PAIR(a0, 0, 128, 0, 2) FILL_PAIR(a0, 2, -1, 1, 3)
        int t[64];
        uint32_t zc, sw, bi;
        if (wg == 0) NARROW(2) else P = ld_par(par);
        FILL_PAIR(a1, 0, 128, 7, 4) FILL_PAIR(a1, 2, 512 - wg * 192, 8, 5)
        {
            const uint4 v0 = epi_row(a0, 64, P, sx2), v1 = epi_row(a0, 66, P, sx2);
            if (!(k2 && wg)) mbar_wait(bars + (B_PAR + 2 + wg) * 8);
            FILL_BEGIN(9, 6)
            const uint32_t s4 = buf + ((so >> 1) & ~63u) + (lane & 3) * 16;
            sts128(s4, v0); sts128(s4 + 512, v1);
            sts128(s4 + 4096, epi_row(a1, 64, P, sx2)); sts128(s4 + 4608, epi_row(a1, 66, P, sx2));
            FILL_END(9, 6)
        }
        if (!(k2 && wg)) {
        if (!k2 && wg == 1) NARROW(3) else { zc = lds32(pp); sw = lds32(pp + TN * 2); bi = lds32(pp + TN * 4); }
#define FILL_T(h)                                                                                                       \
        {                                                                                                               \
            FILL_BEGIN((10 + h), (12 + h))                                                                              \
            _Pragma("unroll") for (int j = 0; j < 8; j++) {                                                             \
                const int o = h * 32 + j * 4;                                                                           \
                sts32(buf + st0 + j * 1024, bf2_op_epi(t[o], t[o + 2], zc, sx2, sw, bi));                               \
                sts32(buf + (st0 ^ (5 * 128 + 5 * 16)) + j * 1024, bf2_op_epi(t[o + 1], t[o + 3], zc, sx2, sw, bi));    \
            }                                                                                                           \
            FILL_END((10 + h), (12 + h))                                                                                \
        }
        FILL_T(0) FILL_T(1)
        }
        if (DBG & 4) for (int i = 0; i < 56; i++) mbar_wait(bars + i * 8);
        if (threadIdx.x == 0) { TLREC(252); TLCLK(253); }
        TLEND();
        if (threadIdx.x == 128) asm volatile("red.relaxed.gpu.global.add.u32 [%0], 1;" :: "l"(g_epoch + b) : "memory");
    } else {
        const int g = r * NCL + c, na = k2 ? 0 : NAJ / NCTA + (g < NAJ % NCTA);
        int cw = NF;
        if (warp >= 12) {
            asm volatile("setmaxnreg.dec.sync.aligned.u32 " STR(CFG_RC) ";");
            if (warp < 14) {
                const int c4 = (lane ^ (lane >> 3)) & 3, ln = ((lane >> 2) ^ (lane & 4)) * 2 + (c4 >> 1);
                const uint32_t rd0 = sb + SM_A + 13 * 8192 + ln * 128 + ((((c4 & 1) << 2) ^ (ln & 7)) << 4);
#pragma unroll 1
                for (int t = warp - 12, sl = na == 9 ? t : 2 - 2 * t; t < na; t += 2, sl = sl ? sl - 1 : 2) {
                    const uint32_t rdA = rd0 + sl * 8192;
                    const int a = t * NCTA + g, f = (a & 60) * 4 + (a >> 6);
                    uint4* const d = g_s8 + (f * 4 + (a & 3)) * 128 + lane;
                    uint4 o[4];
                    mbar_wait(bars + (B_RAWA + 3 + t) * 8);
                    if (lane == 0) TLREC(128 + t);
#pragma unroll
                    for (int i = 0; i < 4; i++) {
                        uint4 v0 = lds128(rdA + i * 2048), v1 = lds128((rdA ^ 16) + i * 2048);
                        uint4 v2 = lds128((rdA ^ 32) + i * 2048), v3 = lds128((rdA ^ 48) + i * 2048);
                        o[i].x = pack4(v0.x, v0.y, v0.z, v0.w); o[i].y = pack4(v1.x, v1.y, v1.z, v1.w);
                        o[i].z = pack4(v2.x, v2.y, v2.z, v2.w); o[i].w = pack4(v3.x, v3.y, v3.z, v3.w);
                    }
#pragma unroll
                    for (int i = 0; i < 4; i++) stg128(d + i * 32, o[i]);
                    unsigned rb;
                    if (CFG_WF) asm volatile("fence.proxy.async.global;" ::: "memory");
                    __syncwarp();
                    READ_BACK
                    if (t < 2) asm volatile("barrier.cluster.wait.aligned;" ::: "memory");
                    if (elect_one()) mbar_arrive(bars + ((t < na - 3 ? B_RAWA : B_AFREE + 13) + sl) * 8);
                    if (lane == 0) TLREC(160 + t);
                    if (__shfl_sync(~0u, rb ^ o[0].x, CFG_RB16 ? 6 : 0)) asm volatile("fence.acq_rel.gpu;" ::: "memory");
                    if (elect_one()) asm volatile("red.relaxed.gpu.global.add.u32 [%0], 1;" :: "l"(g_flag + (a & 60) * 8 + (a >> 6)) : "memory");
                    if (lane == 0) TLREC(192 + t);
                }
                cw = warp - 12;
            }
            {
                const uint32_t rd0 = sb + (lane >> 3) * 2048 + (lane & 7) * 16;
                const BJob mb = decode_b((lane & 15) * 16 + r);
                const int myG = mb.G | mb.u << 8;
#pragma unroll 1
                for (int t = k2 ? warp - 12 : warp < 14 ? CFG_TB + warp - 10 : warp - 14; t < NBJ; t += (!k2 && t < CFG_TB) ? 2 : 4) {
                    const uint32_t rdB = rd0 + stage_w<k2>(t);
                    uint4* const d = g_s8 + (1024 + c * 256 + t * 16 + r) * 128 + lane;
                    uint4 o[4];
                    mbar_wait(bars + (B_RAWB + 3 + t) * 8);
                    if (lane == 0) TLREC(138 + t);
                    CV_B(0, x) CV_B(1, y) CV_B(2, z) CV_B(3, w)
#pragma unroll
                    for (int i = 0; i < 4; i++) stg128(d + i * 32, o[i]);
                    if (t < (k2 ? 4 : 2)) asm volatile("barrier.cluster.wait.aligned;" ::: "memory");
                    if (elect_one()) mbar_arrive(bars + ((k2 || t >= NBJ - 3) ? B_FREE + t - (NBJ - 3) : B_RAWB + t % 3) * 8);
                    asm volatile("fence.proxy.async.global;" ::: "memory");
                    __syncwarp();
                    unsigned rb = 0, ep = 0;
                    if (k2) {
                        READ_BACK
                        ep = ld_flag(g_epoch + b);
                    } else if (elect_one()) mbar_arrive(bars + (B_GO + t) * 8);
                    if (lane == 0) TLREC(170 + t);
                    int cs[4];
#pragma unroll
                    for (int i = 0; i < 4; i++)
                        cs[i] = __dp4a((int)o[i].x, 0x01010101, __dp4a((int)o[i].y, 0x01010101,
                                __dp4a((int)o[i].z, 0x01010101, __dp4a((int)o[i].w, 0x01010101, 0))));
                    const bool h = lane & 16, odd = lane & 8;
                    int x = (h ? cs[2] : cs[0]) + __shfl_xor_sync(~0u, h ? cs[0] : cs[2], 16);
                    int y = (h ? cs[3] : cs[1]) + __shfl_xor_sync(~0u, h ? cs[1] : cs[3], 16);
                    const int v = (odd ? y : x) + __shfl_xor_sync(~0u, odd ? x : y, 8);
                    const int gu = __shfl_sync(~0u, myG, t), G = gu & 255;
                    if (k2) {
                        if (__shfl_sync(~0u, rb ^ o[0].x, CFG_RB16 ? 6 : 0)) asm volatile("fence.acq_rel.gpu;" ::: "memory");
                        if (elect_one()) asm volatile("red.relaxed.gpu.global.add.u32 [%0], 1;" :: "l"(g_flag + 512 + (gu >> 8)) : "memory");
                        if (lane == 0) TLREC(202 + t);
                        const int old = atomicAdd(g_cs[ep & 1] + col_of(G) + (lane & 7) * 4 + (lane >> 3), v);
                        if (old == 0x7FFFFFFF) g_sink = old;
                        __syncwarp();
                        if (elect_one()) asm volatile("red.relaxed.gpu.global.add.u32 [%0], 1;" :: "l"(g_flag + 576 + (t >= 10)) : "memory");
                    } else if (G != r) {
                        asm volatile("red.async.relaxed.cluster.shared::cluster.mbarrier::complete_tx::bytes.add.s32 [%0], %1, [%2];"
                                     :: "r"(mapa(sb + SM_CS + lane * 4, G)), "r"(v), "r"(mapa(bars + B_CS * 8, G)) : "memory");
                    } else {
                        asm volatile("red.shared.add.s32 [%0], %1;" :: "r"(sb + SM_CS + lane * 4), "r"(v) : "memory");
                        __syncwarp();
                        if (elect_one()) mbar_arrive(bars + B_CS * 8);
                    }
                    if (lane == 0 && !k2) TLREC(202 + t);
                }
            }
        } else {
            asm volatile("setmaxnreg.dec.sync.aligned.u32 " STR(CFG_RO) ";");
            if (warp == 11) {
            if (elect_one()) {
#pragma unroll
                for (int i = 0; i < (k2 ? NU / 2 : NBJ); i++) mbar_init(bars + (B_GO + i) * 8, k2 ? (i * 2 + (r & 1) >= NSLOT ? 9 : 1) : i * 16 + r >= NSLOT * 5 ? 1 + 4 * CS : 1);
#pragma unroll
                for (int i = 0; i < 3; i++) mbar_init(bars + (B_FILL + i) * 8, 4);
            }
            const int u2 = lane * 2 + (r & 1), q = k2 ? (u2 < 32 ? 5 * u2 : 4 * u2 + 32) : (lane & 15) * 16 + r;
            const BJob bj = decode_b(q);
            const int nself = __popc(__ballot_sync(~0u, lane < NBJ && bj.G == r));
            sts32(sb + SM_CS + lane * 4, 0);
            if (lane == 0) {
                mbar_init(bars + B_CS * 8, 1 + nself);
                mbar_expect_tx(bars + B_CS * 8, (16 - nself) * 128);
            }

            asm volatile("fence.mbarrier_init.release.cluster;" ::: "memory");
            asm volatile("barrier.cluster.arrive.relaxed.aligned;" :: "r"(lds32(sb + SM_CS + lane * 4)) : "memory");
            const char* src = (const char*)g_s8 + (1024 + c * 256 + q) * 2048;
            const uint32_t dst = sb + SM_RING + (bj.u % NSLOT) * SLOT + bj.pos * 2048;
            const uint32_t fb = bars + (B_FULLB + fb_of(bj.u)) * 8;
            asm volatile("barrier.cluster.wait.aligned;" ::: "memory");
            {
                const uint32_t sx2 = (uint32_t)__ldg((const unsigned short*)scale_x) * 0x10001u;
#pragma unroll
                for (int i = lane; i < TN / 4; i += 32) {
                    const bool hi = i >= TN / 8;
                    uint4 v = __ldg((const uint4*)((hi ? bias : scale_w) + c * TN) + (hi ? i - TN / 8 : i));
                    if (CFG_EPI == 2 && !hi) {
                        asm("mul.rn.bf16x2 %0, %0, %1;" : "+r"(v.x) : "r"(sx2)); asm("mul.rn.bf16x2 %0, %0, %1;" : "+r"(v.y) : "r"(sx2));
                        asm("mul.rn.bf16x2 %0, %0, %1;" : "+r"(v.z) : "r"(sx2)); asm("mul.rn.bf16x2 %0, %0, %1;" : "+r"(v.w) : "r"(sx2));
                    }
                    sts128(sb + SM_PAR + TN * 2 + i * 16, v);
                }
                __syncwarp();
                if (elect_one()) mbar_arrive(bars + B_SW * 8);
            }
#pragma unroll 1
            for (int i = 0; i < (k2 ? NU / 2 : NBJ); i++) {
                mbar_wait(bars + (B_GO + i) * 8);
                if (lane == i) {
                    asm volatile("cp.async.bulk.shared::cluster.global.mbarrier::complete_tx::bytes.multicast::cluster [%0], [%1], %2, [%3], %4;"
                                 :: "r"(dst), "l"(src), "r"(k2 ? (u2 < 32 ? SLOT : 8192) : 2048), "r"(fb), "h"((uint16_t)(k2 ? 3 : 0xFFFF)) : "memory");
                    TLREC(64 + i);
                }
                __syncwarp();
            }
            } else if (warp == 10) {
            const unsigned ep = (*(volatile unsigned*)&g_epoch[b] + 1) * 4;
            const unsigned* f = g_flag + (CFG_FL == 1 ? 1024 + b * 32 + (lane & 15) : CFG_FL == 3 ? 1024 + (r * 16 + (lane & 15)) * 32 : r * 32 + (lane & 15));
            bool dn = lane >= 16;
            const bool fr = lane < (k2 ? 7 : 13);
            asm volatile("barrier.cluster.wait.aligned;" ::: "memory");
            if (lane == 0) TLREC(15);
#define CHECK(v)                                                                                                        \
                if (!dn && (int)(v - ep) >= 0 && (fr || mbar_test(bars + (B_AFREE + lane) * 8))) {                 \
                    dn = true;                                                                                          \
                    if (!CFG_WF) asm volatile("fence.proxy.async.global;" ::: "memory");                                \
                    asm volatile("cp.async.bulk.shared::cluster.global.mbarrier::complete_tx::bytes [%0], [%1], %2, [%3];" \
                                 :: "r"(sb + SM_A + lane * 8192), "l"((const char*)g_s8 + (r * 16 + lane) * 8192),      \
                                    "r"(8192), "r"(bars + (B_FULLA + lane) * 8) : "memory");                            \
                    TLREC(112 + lane);                                                                                  \
                }                                                                                                       \
                if (__all_sync(~0u, dn)) break;
            unsigned v0 = ld_flag(f), v1;
            __nanosleep(150);
            for (int it = 0;; it++) {
                v1 = ld_flag(f);
                CHECK(v0)
                v0 = ld_flag(f);
                CHECK(v1)
                if (it > (1 << 22)) __trap();
            }
            } else {
                const bool isw = warp == 9;
                const uint32_t rb = bars + (isw ? B_RAWB : B_RAWA) * 8;
                if (elect_one()) {
#pragma unroll
                    for (int i = 0; i < 13; i++) if (i < 3 || i >= (k2 ? 7 : 5)) mbar_init(rb + i * 8, 1);
                    if (isw) {
                        if (!CFG_ETM) asm volatile("prefetch.tensormap [%0];" :: "l"(maps.m + 1) : "memory");
#pragma unroll
                        for (int i = 13; i < 17; i++) mbar_init(rb + i * 8, 1);
                    }
                }
                __syncwarp();
                const int nj = isw ? NBJ : na, j0 = k2 ? 4 : 2;
                if (lane >= j0 && lane < nj) mbar_expect_tx(rb + (3 + lane) * 8, 8192);
                asm volatile("fence.mbarrier_init.release.cluster;" ::: "memory");
                asm volatile("barrier.cluster.arrive.relaxed.aligned;" ::: "memory");
                const int k = lane / 3, x = lane * 16 + r;
                int sl = lane - k * 3, y, z, T;
                if (isw) {
                    const BJob bj = decode_b(x & 255);
                    y = bj.slab * 64; z = (c * TN + col_of(bj.G)) >> 5; T = time_w(x);
                } else {
                    const int a = lane * NCTA + g;
                    y = (a >> 6) * 2; z = (a & 63) * 32; T = time_x(x);
                    if (na == 10) sl = sl ? sl - 1 : 2;
                }
                const unsigned te = t0 + (k2 ? sched2(x) : sched(T));
                const uint32_t sd = sb + (isw ? stage_w<k2>(lane) : SM_A + (13 + sl) * 8192);
#pragma unroll 1
                for (int t = j0; t < nj; t++) {
                    if (lane == t) {
                        if (t >= 3 && !k2) mbar_wait(rb + sl * 8, (k & 1) ^ 1);
                        while ((int)(te - clk()) > 0) ;
                        raw_load(maps.m + isw, y, z, sd, rb + (3 + t) * 8);
                        TLREC(224 + isw * 10 + t);
                    }
                    __syncwarp();
                }
                asm volatile("barrier.cluster.wait.aligned;" ::: "memory");
                if (!isw) cw = 2;
                if (k2) {
                    const unsigned e0 = *(volatile unsigned*)&g_epoch[b];
                    if (!isw) {
                        if (lane < TN / 16) g_cs[(e0 & 1) ^ 1][r * (TN / 16) + lane] = 0;
                        const int u = lane * 2 + (r & 1);
                        const unsigned tg = (e0 + 1) * (u < 32 ? 5 : 4);
                        bool dn = u >= NU;
                        for (int it = 0;; it++) {
                            if (!dn && (int)(ld_flag(g_flag + 512 + u) - tg) >= 0) {
                                dn = true;
                                mbar_arrive(bars + (B_GO + lane) * 8);
                            }
                            if (__all_sync(~0u, dn)) break;
                            if (it > (1 << 22)) __trap();
                        }
                    } else {
                        const float zxf = __bfloat162float(__float2bfloat16_rn((float)__ldg(zero_x)));
#pragma unroll 1
                        for (int h = 0; h < 2; h++) {
                            for (int it = 0; (int)(ld_flag(g_flag + 576 + h) - (e0 + 1) * (h ? 32 : 160)) < 0; it++) if (it > (1 << 22)) __trap();
                            int2 v[5];
#pragma unroll
                            for (int j = 0; j < 5; j++) v[j] = __ldcg((const int2*)g_cs[e0 & 1] + min(h * 160 + j * 32 + lane, TN / 2 - 1));
#pragma unroll
                            for (int j = 0; j < 5; j++) {
                                const int i = h * 160 + j * 32 + lane;
                                const float lo = __bfloat162float(__float2bfloat16_rn((float)v[j].x)) * zxf;
                                const float hi = __bfloat162float(__float2bfloat16_rn((float)v[j].y)) * zxf;
                                uint32_t z;
                                asm("cvt.rn.bf16x2.f32 %0, %1, %2;" : "=r"(z) : "f"(hi), "f"(lo));
                                if (i < TN / 2 - 32)
                                    asm volatile("st.async.weak.shared::cluster.mbarrier::complete_tx::bytes.b32 [%0], %1, [%2];"
                                                 :: "r"(sb + SM_PAR + i * 4), "r"(z), "r"(bars + (B_PAR + (i < 128 ? i >> 6 : i < 160 ? (i >> 4) & 1 : (i >> 5) - 3)) * 8) : "memory");
                            }
                            if (lane == 0) TLREC(8 + h);
                        }
                    }
                }
            }
            if (!k2 && r < NBJ && warp == (r < 10 ? 8 : 10)) {
            const float zxf = __bfloat162float(__float2bfloat16_rn((float)__ldg(zero_x)));
            mbar_wait(bars + B_CS * 8);
            const int w = lane & 15;
            const uint32_t ca = sb + SM_CS + ((w >> 1) + (w & 1) * 16) * 4;
            const float lo = __bfloat162float(__float2bfloat16_rn((float)(int)lds32(ca))) * zxf;
            const float hi = __bfloat162float(__float2bfloat16_rn((float)(int)lds32(ca + 32))) * zxf;
            uint32_t z;
            asm("cvt.rn.bf16x2.f32 %0, %1, %2;" : "=r"(z) : "f"(hi), "f"(lo));
            const int piece = r < 10 ? (r >= 5) : (r - 6) >> 1;
#pragma unroll 1
            for (int i = lane >> 4; i < CS; i += 2)
                asm volatile("st.async.weak.shared::cluster.mbarrier::complete_tx::bytes.b32 [%0], %1, [%2];"
                             :: "r"(mapa(sb + SM_PAR + col_of(r) * 2 + w * 4, i)), "r"(z), "r"(mapa(bars + (B_PAR + piece) * 8, i)) : "memory");
            if (lane == 0) TLREC(8);
            }
        }
#pragma unroll 1
            for (int n = cw, k = 0; n < NF; n += 3, k ^= 1) {
                const int g = n >= 2 && n < 7, m = n < 2 ? n : n < 7 ? n - 2 : n - 5;
                const int x = n >= 10 ? (n >> 1) * 64 : m == 4 ? 256 + g * 32 : g * 128 + (m & 1) * 64;
                const int y = n >= 10 ? (n & 1) * 64 : (m & 2) * 32;
                mbar_wait(bars + (B_FILL + cw) * 8, k);
                asm volatile("fence.proxy.async.shared::cta;" ::: "memory");
                if (!(DBG & 2) && elect_one())
                    asm volatile("cp.async.bulk.tensor.2d.global.shared::cta.tile.bulk_group [%0, {%1, %2}], [%3];"
                                 :: "l"(maps.m + (n < 10 && m == 4 ? 3 : 2)), "r"(c * TN + x), "r"(r * 128 + y), "r"(sb + SM_STG + ((cw + NBJ) % 3) * 8192) : "memory");
                asm volatile("cp.async.bulk.commit_group;" ::: "memory");
                if (lane == 0) TLREC(32 + n);
                asm volatile("cp.async.bulk.wait_group.read 0;" ::: "memory");
                __syncwarp();
                if (n < NF - 3 && elect_one()) mbar_arrive(bars + (B_FREE + 3 + n) * 8);
                if (lane == 0) TLREC(48 + n);
            }
        if (cw < 3 && lane == 0) TLE_REC(b, 1 + cw);
        TLEND();
    }
}

}

typedef CUresult (*EncodeFn)(CUtensorMap*, CUtensorMapDataType, cuuint32_t, void*, const cuuint64_t*, const cuuint64_t*,
                             const cuuint32_t*, const cuuint32_t*, CUtensorMapInterleave, CUtensorMapSwizzle,
                             CUtensorMapL2promotion, CUtensorMapFloatOOBfill);

extern "C" void kernel_launch(void* const* d_in, const int* in_sizes, int n_in, void* d_out, int out_size) {
    using namespace w8;
    static EncodeFn encode = nullptr;
    static cudaStream_t side;
    static cudaEvent_t started, joined;
    if (!encode) {
        void* fn = nullptr;
        cudaDriverEntryPointQueryResult qr;
        cudaGetDriverEntryPoint("cuTensorMapEncodeTiled", &fn, cudaEnableDefault, &qr);
        encode = (EncodeFn)fn;
        cudaStreamCreateWithFlags(&side, cudaStreamNonBlocking);
        cudaEventCreateWithFlags(&started, cudaEventDisableTiming);
        cudaEventCreateWithFlags(&joined, cudaEventDisableTiming);
        cudaFuncSetAttribute(w8a8_kernel<false>, cudaFuncAttributeMaxDynamicSharedMemorySize, SM_ALLOC);
        cudaFuncSetAttribute(w8a8_kernel<true>, cudaFuncAttributeMaxDynamicSharedMemorySize, SM_ALLOC);
        cudaFuncSetAttribute(w8a8_kernel<false>, cudaFuncAttributeNonPortableClusterSizeAllowed, 1);
    }
    Maps maps;
    {
        const cuuint64_t dim[3] = {32, K_ / 32, M_}, str[2] = {128, K_ * 4};
        const cuuint32_t box[3] = {32, 2, 32}, es[3] = {1, 1, 1};
        encode(&maps.m[0], CU_TENSOR_MAP_DATA_TYPE_INT32, 3, d_in[0], dim, str, box, es, CU_TENSOR_MAP_INTERLEAVE_NONE,
               CU_TENSOR_MAP_SWIZZLE_128B, CU_TENSOR_MAP_L2_PROMOTION_NONE, CU_TENSOR_MAP_FLOAT_OOB_FILL_NONE);
    }
    {
        const cuuint64_t dim[3] = {32, K_, N_ / 32}, str[2] = {N_ * 4, 128};
        const cuuint32_t box[3] = {32, 64, 1}, es[3] = {1, 1, 1};
        encode(&maps.m[1], CU_TENSOR_MAP_DATA_TYPE_INT32, 3, d_in[1], dim, str, box, es, CU_TENSOR_MAP_INTERLEAVE_NONE,
               CU_TENSOR_MAP_SWIZZLE_NONE, (CUtensorMapL2promotion)CFG_PROMO, CU_TENSOR_MAP_FLOAT_OOB_FILL_NONE);
    }
    {
        const cuuint64_t dim[2] = {N_, M_}, str[1] = {N_ * 2};
        const cuuint32_t box[2] = {WB, 64}, es[2] = {1, 1};
        encode(&maps.m[2], CU_TENSOR_MAP_DATA_TYPE_BFLOAT16, 2, d_out, dim, str, box, es, CU_TENSOR_MAP_INTERLEAVE_NONE,
               CU_TENSOR_MAP_SWIZZLE_128B, CU_TENSOR_MAP_L2_PROMOTION_NONE, CU_TENSOR_MAP_FLOAT_OOB_FILL_NONE);
    }
    {
        const cuuint64_t dim[2] = {N_, M_}, str[1] = {N_ * 2};
        const cuuint32_t box[2] = {32, 128}, es[2] = {1, 1};
        encode(&maps.m[3], CU_TENSOR_MAP_DATA_TYPE_BFLOAT16, 2, d_out, dim, str, box, es, CU_TENSOR_MAP_INTERLEAVE_NONE,
               CU_TENSOR_MAP_SWIZZLE_NONE, CU_TENSOR_MAP_L2_PROMOTION_NONE, CU_TENSOR_MAP_FLOAT_OOB_FILL_NONE);
    }
    for (int k = 0; k < ((DBG & 32) ? 1 : 2); k++) {
        cudaLaunchConfig_t cfg = {};
        cfg.gridDim = dim3(k ? 20 : NCTA); cfg.blockDim = dim3(512); cfg.dynamicSmemBytes = SM_ALLOC; cfg.stream = cudaStreamPerThread;
        cudaLaunchAttribute at[2];
        at[0].id = cudaLaunchAttributeClusterDimension; at[0].val.clusterDim.x = k ? 2 : CS; at[0].val.clusterDim.y = 1; at[0].val.clusterDim.z = 1;
        at[1].id = cudaLaunchAttributeProgrammaticStreamSerialization; at[1].val.programmaticStreamSerializationAllowed = 1;
        cfg.attrs = at; cfg.numAttrs = 1 + k;
        at[1].id = cudaLaunchAttributeLaunchCompletionEvent; at[1].val.launchCompletionEvent.event = started; at[1].val.launchCompletionEvent.flags = 0;
        cfg.numAttrs = 2 - k;
        if (k) { cudaStreamWaitEvent(side, started, 0); cfg.stream = side; }
        cudaLaunchKernelEx(&cfg, k ? w8a8_kernel<true> : w8a8_kernel<false>,
                           (const char*)d_in[0], (const __nv_bfloat16*)d_in[2], (const int*)d_in[3], (const __nv_bfloat16*)d_in[4], (const __nv_bfloat16*)d_in[5]
                           , maps
                           );
        if (k) { cudaEventRecord(joined, side); cudaStreamWaitEvent(cudaStreamPerThread, joined, 0); }
    }
}
```

```cpp
#include <cuda_runtime.h>
#include <cuda.h>
#include <cuda_bf16.h>
#include <stdint.h>

#define CFG_X1 13
#define CFG_P1 46
#define CFG_P2 38
#define CFG_PT 100
#define CFG_L0 32
#define CFG_T0 0
#define CFG_ACQ 0
#define CFG_MODE 1
#define CFG_PF 0
#define CFG_MC 16
#define CFG_NP 2
#define CFG_D 0
#define CFG_NL 2
#define CFG_R4 2
#define CFG_TD 30
#define CFG_TD0 1200
#define CFG_TDS 600
#define CFG_EPI 2
#define CFG_SLEEP 0
#define CFG_POLL2 0
#define CFG_PF2 0
#define CFG_PREG 56
#define CFG_CREG 200
#define STR2(x) #x
#define STR(x) STR2(x)
#define CFG_WF 1
#define CFG_FL 2
#define CFG_TB 8
#define CFG_Q2 66
#define CFG_PF7 0
#define CFG_Q0 10
#define CFG_NS 1
#define CFG_TS 8
#define CFG_Q3 30
#define CFG_RA 34
#define CFG_SH 0
#define CFG_WIN 2
#define CFG_HOLD 14
#define CFG_HS CFG_X1
#define CFG_PRE 1
#define CFG_P3 CFG_P2
#define CFG_PT3 210
#define CFG_LC 1
#define CFG_T3 0
#define CFG_K3L 1
#define CFG_H2 0
#define CFG_D3 3
#define CFG_PROMO 0
#define CFG_RC 80
#define CFG_RO 32
#define CFG_PFIRST 1
#define CFG_CD 1
#define CLUSTER_ATTR __cluster_dims__(k2 ? 2 : 16, 1, 1)
#define CFG_ETM 1
#define CFG_EF 0
#define CFG_RB16 1
#define CFG_R8 1
#define CFG_RDY 1
#define CFG_QD 1
#define CFG_XA 96
#define CFG_RA2 CFG_RA
#define CFG_EARLY 0
#define CFG_REV 60
#define CFG_BURST 0
#define CFG_NA0 3
#define CFG_DOM 0
#define CFG_P3L 1
#define CFG_PFB 14
#define CFG_PFO 0
#define DBG 0

namespace w8 {

constexpr int M_ = 2048, K_ = 1024, N_ = 3584;
constexpr int CS = 16, NCL = 7, NCTA = CS * NCL;
constexpr int WA = 160, WB = 64;
constexpr int NP = CFG_NP, TN = 2 * WA + NP * WB;
constexpr int DA = CFG_D, NL = CFG_NL, R4 = CFG_R4;
constexpr int NAJ = 1024;
constexpr int X1 = CFG_X1;
constexpr int NSLOT = 7, SLOT = WA * 64;
constexpr int NU1 = 48;
constexpr int NCONV = 4;
constexpr int L0 = CFG_L0, NS = CFG_NS;

constexpr int SM_A = 0;
constexpr int SM_RING = 131072;
constexpr int SM_STG = SM_RING + NSLOT * SLOT;
constexpr int SM_PAR = SM_STG + 3 * 8192;
constexpr int SM_CS = SM_PAR + 3 * TN * 2;
constexpr int SM_BAR = SM_CS + 128;
constexpr int B_FULLB = 0, B_FULLA = 56, B_PAR = 72, B_SW = 77, B_AFREE = 79 - 5  , B_FREE = 90, B_NINIT = 104,
              B_GO = 104, B_FILL = 128, B_CS = 131, B_RAWA = 132, B_RAWB = 145, B_RAWS = 162, B_END = 163;
constexpr int SM_TOTAL = SM_BAR + B_END * 8;
static_assert(SM_TOTAL <= 232448, "");

__device__ uint4 g_s8[(1024 + 8 * 256) * 128];
__device__ unsigned g_flag[1024 + 8192];
__device__ int g_cs[2][TN];
__device__ int g_sink;
__device__ unsigned g_epoch[132];
#define TLE_REC(b, i) do {} while (0)
#define TLREC(i) do {} while (0)
#define TLCLK(i) do {} while (0)
#define TLEND() do {} while (0)
constexpr int SM_ALLOC = SM_TOTAL;

#define TL2 0
#define TLJ(i) TLREC(i)
#define TLW(i) do {} while (0)
#define TLVAL(i, v) do {} while (0)
__device__ __forceinline__ void mbar_init(uint32_t bar, uint32_t cnt) {
    asm volatile("mbarrier.init.shared::cta.b64 [%0], %1;" :: "r"(bar), "r"(cnt) : "memory");
}
__device__ __forceinline__ void mbar_expect_tx(uint32_t bar, uint32_t bytes) {
    asm volatile("mbarrier.arrive.expect_tx.shared::cta.b64 _, [%0], %1;" :: "r"(bar), "r"(bytes) : "memory");
}
__device__ __forceinline__ void mbar_arrive(uint32_t bar) {
    asm volatile("mbarrier.arrive.shared::cta.b64 _, [%0];" :: "r"(bar) : "memory");
}
__device__ __forceinline__ void mbar_arrive_cluster(uint32_t bar) {
    asm volatile("mbarrier.arrive.shared::cluster.b64 _, [%0];" :: "r"(bar) : "memory");
}
__device__ __forceinline__ void mbar_wait(uint32_t bar, uint32_t parity = 0) {
    asm volatile("{\n.reg .pred p;\n.reg .u32 c;\n"
                 "mbarrier.try_wait.parity.shared::cta.b64 p, [%0], %1;\n"
                 "@p bra WAIT_DONE;\n"
                 "mov.u32 c, 0;\n"
                 "WAIT_LOOP:\n"
                 "mbarrier.try_wait.parity.shared::cta.b64 p, [%0], %1;\n"
                 "@p bra WAIT_DONE;\n"
                 "add.u32 c, c, 1;\nsetp.lt.u32 p, c, 0x100000;\n"
                 "@p bra WAIT_LOOP;\n"
                 "trap;\n"
                 "WAIT_DONE:\n}" :: "r"(bar), "r"(parity) : "memory");
}
__device__ __forceinline__ void mbar_wait2(uint32_t bar0, uint32_t bar1) {
    asm volatile("{\n.reg .pred p, q;\n.reg .u32 c;\nmov.u32 c, 0;\n"
                 "WAIT_LOOP:\n"
                 "mbarrier.try_wait.parity.shared::cta.b64 p, [%0], 0;\n"
                 "mbarrier.try_wait.parity.shared::cta.b64 q, [%1], 0;\n"
                 "and.pred p, p, q;\n"
                 "@p bra WAIT_DONE;\n"
                 "add.u32 c, c, 1;\nsetp.lt.u32 p, c, 0x100000;\n"
                 "@p bra WAIT_LOOP;\n"
                 "trap;\n"
                 "WAIT_DONE:\n}" :: "r"(bar0), "r"(bar1) : "memory");
}
__device__ __forceinline__ bool mbar_test(uint32_t bar) {
    uint32_t ok;
    asm volatile("{\n.reg .pred p;\nmbarrier.test_wait.parity.shared::cta.b64 p, [%1], 0;\nselp.u32 %0, 1, 0, p;\n}" : "=r"(ok) : "r"(bar) : "memory");
    return ok;
}
__device__ __forceinline__ bool mbar_test2(uint32_t bar0, uint32_t bar1) {
    uint32_t ok;
    asm volatile("{\n.reg .pred p, q;\nmbarrier.test_wait.parity.shared::cta.b64 p, [%1], 0;\n"
                 "mbarrier.test_wait.parity.shared::cta.b64 q, [%2], 0;\nand.pred p, p, q;\nselp.u32 %0, 1, 0, p;\n}"
                 : "=r"(ok) : "r"(bar0), "r"(bar1) : "memory");
    return ok;
}
__device__ __forceinline__ bool elect_one() {
    uint32_t ok;
    asm volatile("{\n.reg .pred p;\nelect.sync _|p, 0xffffffff;\nselp.u32 %0, 1, 0, p;\n}" : "=r"(ok));
    return ok;
}
__device__ __forceinline__ unsigned ld_acquire(const unsigned* p) {
    unsigned v;
    asm volatile("ld.acquire.gpu.global.u32 %0, [%1];" : "=r"(v) : "l"(p) : "memory");
    return v;
}
__device__ __forceinline__ unsigned ld_flag(const unsigned* p) {
    unsigned v;
    asm volatile("ld.relaxed.gpu.global.u32 %0, [%1];" : "=r"(v) : "l"(p) : "memory");
    return v;
}
__device__ __forceinline__ uint4 lds128(uint32_t a) {
    uint4 v;
    asm volatile("ld.shared.v4.b32 {%0,%1,%2,%3}, [%4];" : "=r"(v.x), "=r"(v.y), "=r"(v.z), "=r"(v.w) : "r"(a) : "memory");
    return v;
}
__device__ __forceinline__ void sts128(uint32_t a, uint4 v) {
    asm volatile("st.shared.v4.b32 [%0], {%1,%2,%3,%4};" :: "r"(a), "r"(v.x), "r"(v.y), "r"(v.z), "r"(v.w) : "memory");
}
__device__ __forceinline__ uint32_t lds32(uint32_t a) {
    uint32_t v;
    asm volatile("ld.shared.b32 %0, [%1];" : "=r"(v) : "r"(a) : "memory");
    return v;
}
__device__ __forceinline__ void sts32(uint32_t a, uint32_t v) {
    asm volatile("st.shared.b32 [%0], %1;" :: "r"(a), "r"(v) : "memory");
}
__device__ __forceinline__ void stg128(void* p, uint4 v) {
    asm volatile("st.global.v4.b32 [%0], {%1,%2,%3,%4};" :: "l"(p), "r"(v.x), "r"(v.y), "r"(v.z), "r"(v.w) : "memory");
}
__device__ __forceinline__ unsigned pack4(unsigned a, unsigned b, unsigned c, unsigned d) {
    unsigned lo, r;
    asm("cvt.pack.sat.s8.s32.b32 %0, %1, %2, 0;" : "=r"(lo) : "r"(d), "r"(c));
    asm("cvt.pack.sat.s8.s32.b32 %0, %1, %2, %3;" : "=r"(r) : "r"(b), "r"(a), "r"(lo));
    return r;
}

constexpr uint32_t DESC_A_HI = 0x80000000u | (512 >> 4);
constexpr uint32_t DESC_B_HI = 512 >> 4;
template <int NR> __device__ __forceinline__ void wgmma_n160(int (&d)[NR], uint32_t alo, uint32_t blo, int scale_d) {
    asm volatile("{\n.reg .pred p;\n.reg .b64 da, db;\nsetp.ne.b32 p, %82, 0;\n"
        "mov.b64 da, {%80, %83};\nmov.b64 db, {%81, %84};\n"
        "wgmma.mma_async.sync.aligned.m64n160k32.s32.s8.s8 "
        "{%0, %1, %2, %3, %4, %5, %6, %7, %8, %9, %10, %11, %12, %13, %14, %15, "
        "%16, %17, %18, %19, %20, %21, %22, %23, %24, %25, %26, %27, %28, %29, %30, %31, "
        "%32, %33, %34, %35, %36, %37, %38, %39, %40, %41, %42, %43, %44, %45, %46, %47, "
        "%48, %49, %50, %51, %52, %53, %54, %55, %56, %57, %58, %59, %60, %61, %62, %63, "
        "%64, %65, %66, %67, %68, %69, %70, %71, %72, %73, %74, %75, %76, %77, %78, %79}, "
        "da, db, p;\n}\n"
        : "+r"(d[0]), "+r"(d[1]), "+r"(d[2]), "+r"(d[3]), "+r"(d[4]), "+r"(d[5]), "+r"(d[6]), "+r"(d[7]),
          "+r"(d[8]), "+r"(d[9]), "+r"(d[10]), "+r"(d[11]), "+r"(d[12]), "+r"(d[13]), "+r"(d[14]), "+r"(d[15]),
          "+r"(d[16]), "+r"(d[17]), "+r"(d[18]), "+r"(d[19]), "+r"(d[20]), "+r"(d[21]), "+r"(d[22]), "+r"(d[23]),
          "+r"(d[24]), "+r"(d[25]), "+r"(d[26]), "+r"(d[27]), "+r"(d[28]), "+r"(d[29]), "+r"(d[30]), "+r"(d[31]),
          "+r"(d[32]), "+r"(d[33]), "+r"(d[34]), "+r"(d[35]), "+r"(d[36]), "+r"(d[37]), "+r"(d[38]), "+r"(d[39]),
          "+r"(d[40]), "+r"(d[41]), "+r"(d[42]), "+r"(d[43]), "+r"(d[44]), "+r"(d[45]), "+r"(d[46]), "+r"(d[47]),
          "+r"(d[48]), "+r"(d[49]), "+r"(d[50]), "+r"(d[51]), "+r"(d[52]), "+r"(d[53]), "+r"(d[54]), "+r"(d[55]),
          "+r"(d[56]), "+r"(d[57]), "+r"(d[58]), "+r"(d[59]), "+r"(d[60]), "+r"(d[61]), "+r"(d[62]), "+r"(d[63]),
          "+r"(d[64]), "+r"(d[65]), "+r"(d[66]), "+r"(d[67]), "+r"(d[68]), "+r"(d[69]), "+r"(d[70]), "+r"(d[71]),
          "+r"(d[72]), "+r"(d[73]), "+r"(d[74]), "+r"(d[75]), "+r"(d[76]), "+r"(d[77]), "+r"(d[78]), "+r"(d[79])
        : "r"(alo), "r"(blo), "r"(scale_d), "r"(DESC_A_HI), "r"(DESC_B_HI));
}
template <int NR> __device__ __forceinline__ void wgmma_t128(int (&d)[NR], uint32_t alo, uint32_t blo, int scale_d) {
    asm volatile("{\n.reg .pred p;\n.reg .b64 da, db;\nsetp.ne.b32 p, %66, 0;\n"
        "mov.b64 da, {%64, %67};\nmov.b64 db, {%65, %68};\n"
        "wgmma.mma_async.sync.aligned.m64n128k32.s32.s8.s8 "
        "{%0, %1, %2, %3, %4, %5, %6, %7, %8, %9, %10, %11, %12, %13, %14, %15, "
        "%16, %17, %18, %19, %20, %21, %22, %23, %24, %25, %26, %27, %28, %29, %30, %31, "
        "%32, %33, %34, %35, %36, %37, %38, %39, %40, %41, %42, %43, %44, %45, %46, %47, "
        "%48, %49, %50, %51, %52, %53, %54, %55, %56, %57, %58, %59, %60, %61, %62, %63}, "
        "da, db, p;\n}\n"
        : "+r"(d[0]), "+r"(d[1]), "+r"(d[2]), "+r"(d[3]), "+r"(d[4]), "+r"(d[5]), "+r"(d[6]), "+r"(d[7]),
          "+r"(d[8]), "+r"(d[9]), "+r"(d[10]), "+r"(d[11]), "+r"(d[12]), "+r"(d[13]), "+r"(d[14]), "+r"(d[15]),
          "+r"(d[16]), "+r"(d[17]), "+r"(d[18]), "+r"(d[19]), "+r"(d[20]), "+r"(d[21]), "+r"(d[22]), "+r"(d[23]),
          "+r"(d[24]), "+r"(d[25]), "+r"(d[26]), "+r"(d[27]), "+r"(d[28]), "+r"(d[29]), "+r"(d[30]), "+r"(d[31]),
          "+r"(d[32]), "+r"(d[33]), "+r"(d[34]), "+r"(d[35]), "+r"(d[36]), "+r"(d[37]), "+r"(d[38]), "+r"(d[39]),
          "+r"(d[40]), "+r"(d[41]), "+r"(d[42]), "+r"(d[43]), "+r"(d[44]), "+r"(d[45]), "+r"(d[46]), "+r"(d[47]),
          "+r"(d[48]), "+r"(d[49]), "+r"(d[50]), "+r"(d[51]), "+r"(d[52]), "+r"(d[53]), "+r"(d[54]), "+r"(d[55]),
          "+r"(d[56]), "+r"(d[57]), "+r"(d[58]), "+r"(d[59]), "+r"(d[60]), "+r"(d[61]), "+r"(d[62]), "+r"(d[63])
        : "r"(alo), "r"(blo), "r"(scale_d), "r"(DESC_B_HI), "r"(DESC_A_HI));
}

__device__ __forceinline__ void wg_fence() { asm volatile("wgmma.fence.sync.aligned;" ::: "memory"); }
__device__ __forceinline__ void wg_commit() { asm volatile("wgmma.commit_group.sync.aligned;" ::: "memory"); }
template <int N> __device__ __forceinline__ void wg_wait() { asm volatile("wgmma.wait_group.sync.aligned %0;" :: "n"(N) : "memory"); }

__device__ __forceinline__ uint32_t mapa(uint32_t a, uint32_t r) {
    uint32_t o;
    asm("mapa.shared::cluster.u32 %0, %1, %2;" : "=r"(o) : "r"(a), "r"(r));
    return o;
}
__device__ __forceinline__ unsigned clk() {
    unsigned t;
    asm volatile("mov.u32 %0, %clock;" : "=r"(t));
    return t;
}
__host__ __device__ constexpr int unit_of(int piece, int slab) {
    return piece < 2 ? (slab < X1 ? 2 * slab + piece : (piece ? 16 : X1) + slab) : 32 + (piece - 2) * 8 + (slab >> 1);
}
__host__ __device__ constexpr int col_of(int G) { return G == 4 ? 256 : (G > 4 && G < 9) ? 32 * G - 32 : 32 * G; }
struct BJob { int u, slab, G, pos; };
__host__ __device__ constexpr BJob decode_b(int q) {
    BJob j = {};
    if (q < 160) {
        j.u = q / 5; j.pos = q - j.u * 5;
        const int piece = j.u < 2 * X1 ? (j.u & 1) : (j.u >= X1 + 16);
        j.slab = j.u < 2 * X1 ? (j.u >> 1) : j.u - (piece ? 16 : X1);
        j.G = piece * 5 + j.pos;
    } else {
        q -= 160;
        j.u = 32 + (q >> 2); j.pos = q & 3;
        j.slab = (q >> 1) & 15;
        j.G = 10 + (q >> 5) * 2 + (q & 1);
    }
    return j;
}
__host__ __device__ constexpr int fb_of(int u) {
    return u < 2 * X1 ? (u & 1) * 32 + (u >> 1) : u < X1 + 16 ? u - X1 : u < 32 ? 16 + u : u < 40 ? u - 16 : u < 48 ? u + 8 : u - 24;
}
template <bool k2> __device__ __forceinline__ int stage_w(int t) { return (k2 && t < 9) ? SM_A + (7 + t) * 8192 : SM_STG + (t % 3) * 8192; }
constexpr int RA = CFG_RA, RB64 = 64 * RA / (RA - 16);
constexpr int RA2 = CFG_RA2, RB642 = 64 * RA2 / (RA2 - 16), XA = CFG_XA, QA = (XA - L0) * (RA - 16) / 16;
__device__ __forceinline__ int time_x(int x) { return max(x, L0 + (((x - L0) * RA + max(x - XA, 0) * (RA2 - RA)) >> 4)); }
__device__ __forceinline__ int time_w(int q) { return min(L0 + ((q * RB64 + max(q - QA, 0) * (RB642 - RB64)) >> 6), NAJ / NCL + q); }
__device__ __forceinline__ int sched2(int x) { return (min(x, 160) - CFG_Q0) * CFG_Q2 + max(x - 160, 0) * CFG_Q3; }
__device__ __forceinline__ unsigned sched(int T) { return T * CFG_P2 + min(T, CFG_PT) * (CFG_P1 - CFG_P2) + max(T - CFG_PT3, 0) * (CFG_P3 - CFG_P2); }
__device__ __forceinline__ void raw_load(const void* map, int y, int z, uint32_t dst, uint32_t bar) {
    asm volatile("cp.async.bulk.tensor.3d.shared::cluster.global.tile.mbarrier::complete_tx::bytes [%0], [%1, {0, %2, %3}], [%4];"
                 :: "r"(dst), "l"(map), "r"(y), "r"(z), "r"(bar) : "memory");
}
__host__ __device__ constexpr uint64_t slot_table(int piece) {
    uint64_t t = 0;
    if (piece < 2) for (int s = 0; s < 16; s++) t |= (uint64_t)(unit_of(piece, s) % NSLOT) << (4 * s);
    else for (int s = 0; s < 8; s++) t |= (uint64_t)(unit_of(piece, 2 * s) % NSLOT) << (4 * s);
    return t;
}
constexpr int NA0 = CFG_NA0;
__host__ __device__ constexpr int ford(int g, int m) {
    return g ? (m < NA0 - 1 ? 2 + 2 * m : NA0 + m) : (m < 2 ? m : m < NA0 ? 2 * m - 1 : 5 + m);
}
__host__ __device__ constexpr uint64_t ford_table() {
    uint64_t t = 0;
    for (int g = 0; g < 2; g++) for (int m = 0; m < 5; m++) t |= (uint64_t)(g * 8 + m) << (4 * ford(g, m));
    return t;
}
struct Maps { CUtensorMap m[4]; };

__device__ __forceinline__ uint32_t bf2_op_epi(int a, int b, uint32_t zc, uint32_t sx, uint32_t sw, uint32_t bi) {
    uint32_t v;
    if (DBG & 1) return a ^ b ^ zc;
    float fa = __int2float_rn(a), fb = __int2float_rn(b);
    asm("cvt.rn.bf16x2.f32 %0, %1, %2;" : "=r"(v) : "f"(fb), "f"(fa));
    asm("sub.rn.bf16x2 %0, %0, %1;" : "+r"(v) : "r"(zc));
    if (CFG_EPI < 2) asm("mul.rn.bf16x2 %0, %0, %1;" : "+r"(v) : "r"(sx));
    if (CFG_EPI == 0) {
        asm("mul.rn.bf16x2 %0, %0, %1;" : "+r"(v) : "r"(sw));
        asm("add.rn.bf16x2 %0, %0, %1;" : "+r"(v) : "r"(bi));
    } else {
        asm("fma.rn.bf16x2 %0, %0, %1, %2;" : "+r"(v) : "r"(sw), "r"(bi));
    }
    return v;
}
struct Par { uint4 zc, sw, bi; };
__device__ __forceinline__ Par ld_par(uint32_t p) { return {lds128(p), lds128(p + TN * 2), lds128(p + TN * 4)}; }
__device__ __forceinline__ uint4 epi_row(const int (&a)[WA / 2], int o, const Par& p, uint32_t sx2) {
    uint4 r;
    r.x = bf2_op_epi(a[o + 0], a[o + 4], p.zc.x, sx2, p.sw.x, p.bi.x);
    r.y = bf2_op_epi(a[o + 8], a[o + 12], p.zc.y, sx2, p.sw.y, p.bi.y);
    r.z = bf2_op_epi(a[o + 1], a[o + 5], p.zc.z, sx2, p.sw.z, p.bi.z);
    r.w = bf2_op_epi(a[o + 9], a[o + 13], p.zc.w, sx2, p.sw.w, p.bi.w);
    return r;
}
__device__ __forceinline__ void release(uint32_t go, int u, int lane, bool k2) {
    const int v = u + NSLOT;
    if (CFG_R8 && !k2) {
        const int q = 5 * v - (v > 34 ? 3 : 0) + lane;
        if (lane < (v > 38 ? 0 : v == 34 ? 2 : 5)) mbar_arrive_cluster(mapa(go + (q >> 4) * 8, q & 15));
        return;
    }
    const int n = k2 ? 1 : v < 32 ? 5 : 4, sh = k2 ? 1 : 4;
    const int q = n * v + (n == 4 ? 32 : 0) + lane;
    if (lane < (v < NU1 ? n : 0)) mbar_arrive_cluster(mapa(go + (q >> sh) * 8, q & ((1 << sh) - 1)));
}

#define READ_BACK asm volatile("ld.relaxed.gpu.global.u32 %0, [%1];" : "=r"(rb) : "l"(d - lane + ((lane + 10) & 15) * 8 + 6) : "memory");
#define CV_B(m, f)                                                                                    \
                    {                                                                                 \
                        uint4 v0 = lds128(rdB + m * 512), v1 = lds128(rdB + m * 512 + 128);           \
                        uint4 v2 = lds128(rdB + m * 512 + 256), v3 = lds128(rdB + m * 512 + 384);     \
                        o[0].f = pack4(v0.x, v1.x, v2.x, v3.x); o[1].f = pack4(v0.y, v1.y, v2.y, v3.y); \
                        o[2].f = pack4(v0.z, v1.z, v2.z, v3.z); o[3].f = pack4(v0.w, v1.w, v2.w, v3.w); \
                    }

__device__ __forceinline__ void last_columns(const Maps& maps, const __nv_bfloat16* scale_x, const int* zero_x, const __nv_bfloat16* scale_w,
                                             const __nv_bfloat16* bias, uint32_t sb, int warp, int lane, unsigned t0) {
    constexpr int C_FULL = 0, C_EMPTY = 32, C_RAW = 64, C_GO = 80;
    const uint32_t bars = sb + SM_BAR;
    const int j = blockIdx.x & 3;
    if (warp < 8) {
        if (elect_one()) {
#pragma unroll
            for (int i = 0; i < 4; i++) { mbar_init(bars + (C_FULL + warp * 4 + i) * 8, 1); mbar_expect_tx(bars + (C_FULL + warp * 4 + i) * 8, 16384); }
#pragma unroll
            for (int i = 0; i < 4; i++) mbar_init(bars + (C_EMPTY + warp * 4 + i) * 8, 4);
            mbar_init(bars + (C_RAW + warp * 2) * 8, 1); mbar_init(bars + (C_RAW + warp * 2 + 1) * 8, 1);
            if (warp == 0) mbar_init(bars + C_GO * 8, 8);
        }
        if (warp < 2) sts32(sb + SM_PAR + threadIdx.x * 4, 0);
    }
    __syncthreads();
    if (warp >= 8) {
        asm volatile("setmaxnreg.dec.sync.aligned.u32 40;");
        if (warp < 12) {
            const unsigned ep = (*(volatile unsigned*)&g_epoch[128 + j] + 1) * 4;
            const int mb = j * 4 + warp - 8, wg = (warp >> 1) & 1;
            unsigned rdy = 0;
            mbar_wait(bars + C_GO * 8);
#pragma unroll 1
            for (int s = 0; s < 16; s++) {
                for (int it = 0; !((rdy >> s) & 1); it++) {
                    rdy = __ballot_sync(~0u, (int)(ld_flag(g_flag + mb * 32 + (lane & 15)) - ep) >= 0);
                    if (it > (1 << 22)) __trap();
                }
                if (s >= CFG_D3) mbar_wait(bars + (C_EMPTY + (s - CFG_D3) * 2 + wg) * 8);
                if (elect_one())
                    asm volatile("cp.async.bulk.shared::cluster.global.mbarrier::complete_tx::bytes [%0], [%1], %2, [%3];"
                                 :: "r"(sb + SM_A + ((s & 3) * 4 + warp - 8) * 8192), "l"((const char*)g_s8 + (mb * 16 + s) * 8192),
                                    "r"(8192), "r"(bars + (C_FULL + s * 2 + wg) * 8) : "memory");
            }
        }
    } else {
        asm volatile("setmaxnreg.inc.sync.aligned.u32 200;");
        const int wg = warp >> 2, w = warp & 3;
        const int c0 = (w >> 1) * 32 + (lane >> 2) * 4 + (w & 1) * 2, r0 = (lane & 3) * 2;
        const uint32_t sx2 = (uint32_t)__ldg((const unsigned short*)scale_x) * 0x10001u;
        uint32_t sw = __ldg((const unsigned*)(scale_w + N_ - WB + c0));
        const uint32_t bi = __ldg((const unsigned*)(bias + N_ - WB + c0));
        const float zxf = __bfloat162float(__float2bfloat16_rn((float)__ldg(zero_x)));
        if (CFG_EPI == 2) asm("mul.rn.bf16x2 %0, %0, %1;" : "+r"(sw) : "r"(sx2));
        int cs[4] = {0, 0, 0, 0};
        while ((int)(t0 + CFG_T3 - clk()) > 0) ;
#define LOAD3(i) if (elect_one()) {                                                                                     \
                mbar_expect_tx(bars + (C_RAW + warp * 2 + ((i) & 1)) * 8, 8192);                                        \
                raw_load(maps.m + 1, ((warp >> 1) * 4 + (((i) + j) & 3)) * 64, N_ / 32 - 2 + (warp & 1),                \
                         sb + SM_A + (warp * 2 + ((i) & 1)) * 8192, bars + (C_RAW + warp * 2 + ((i) & 1)) * 8); }
        if (CFG_P3L) LOAD3(0)
#pragma unroll 1
        for (int i = 0; i < 4; i++) {
            const int s = (warp >> 1) * 4 + ((i + j) & 3);
            const uint32_t rdB = sb + SM_A + (warp * 2 + (i & 1)) * 8192 + (lane >> 3) * 2048 + (lane & 7) * 16;
            if (!CFG_P3L) LOAD3(i)
            mbar_wait(bars + (C_RAW + warp * 2 + (i & 1)) * 8, (i >> 1) & 1);
            if (CFG_P3L && i < 3) LOAD3(i + 1)
            uint4 o[4];
            CV_B(0, x) CV_B(1, y) CV_B(2, z) CV_B(3, w)
#pragma unroll
            for (int k = 0; k < 4; k++) {
                sts128(sb + SM_RING + s * 4096 + (warp & 1) * 2048 + k * 512 + lane * 16, o[k]);
                cs[k] = __dp4a((int)o[k].x, 0x01010101, __dp4a((int)o[k].y, 0x01010101,
                        __dp4a((int)o[k].z, 0x01010101, __dp4a((int)o[k].w, 0x01010101, cs[k]))));
            }
            __syncwarp();
        }
        if (elect_one()) mbar_arrive(bars + C_GO * 8);
#pragma unroll
        for (int k = 0; k < 4; k++)
            asm volatile("red.shared.add.s32 [%0], %1;" :: "r"(sb + SM_PAR + ((warp & 1) * 32 + (lane & 7) * 4 + k) * 4), "r"(cs[k]) : "memory");
        asm volatile("fence.proxy.async.shared::cta;" ::: "memory");
        asm volatile("bar.sync 1, 256;" ::: "memory");
        if (threadIdx.x == 0) TLE_REC(128 + j, 4);
        uint32_t zc;
        asm("cvt.rn.bf16x2.f32 %0, %1, %2;" : "=r"(zc) : "f"(__bfloat162float(__float2bfloat16_rn((float)(int)lds32(sb + SM_PAR + c0 * 4 + 4))) * zxf),
                                                         "f"(__bfloat162float(__float2bfloat16_rn((float)(int)lds32(sb + SM_PAR + c0 * 4))) * zxf));
        const uint32_t sd = (sb & 0x3FFFF) >> 4;
        int t[2][64];
        wg_fence();
#pragma unroll 1
        for (int s = 0; s < 16; s++) {
            const uint32_t db = ((sd + (SM_RING >> 4)) | (8 << 16)) + s * 256, da = ((sd + (SM_A >> 4)) | (1 << 16)) + ((s & 3) * 4 + wg * 2) * 512;
            mbar_wait(bars + (C_FULL + s * 2 + wg) * 8);
            wgmma_t128(t[0], db, da, s);
            wgmma_t128(t[1], db, da + 512, s);
            wgmma_t128(t[0], db + 16, da + 2, 1);
            wgmma_t128(t[1], db + 16, da + 514, 1);
            wg_commit();
            wg_wait<0>();
            if (elect_one()) mbar_arrive(bars + (C_EMPTY + s * 2 + wg) * 8);
        }
        asm volatile("bar.sync %0, 128;" :: "r"(3 + wg) : "memory");
        if (threadIdx.x == 0) TLE_REC(128 + j, 5);
        const uint32_t st0 = sb + SM_A + wg * 16384 + r0 * 128 + (((c0 >> 3) ^ r0) << 4) + (c0 & 7) * 2;
#pragma unroll
        for (int h = 0; h < 4; h++) {
            const uint32_t off = (h >> 1) * 32768 + (h & 1) * 8192;
#pragma unroll
            for (int q = 0; q < 8; q++) {
                const int o = (h & 1) * 32 + q * 4;
                sts32(st0 + off + q * 1024, bf2_op_epi(t[h >> 1][o], t[h >> 1][o + 2], zc, sx2, sw, bi));
                sts32((st0 ^ (5 * 128 + 5 * 16)) + off + q * 1024, bf2_op_epi(t[h >> 1][o + 1], t[h >> 1][o + 3], zc, sx2, sw, bi));
            }
            asm volatile("fence.proxy.async.shared::cta;" ::: "memory");
            asm volatile("bar.sync %0, 128;" :: "r"(3 + wg) : "memory");
            if (w == 0 && elect_one())
                asm volatile("cp.async.bulk.tensor.2d.global.shared::cta.tile.bulk_group [%0, {%1, %2}], [%3];"
                             :: "l"(maps.m + 2), "r"(N_ - WB), "r"(j * 512 + wg * 256 + h * 64), "r"(sb + SM_A + wg * 16384 + off) : "memory");
        }
        if (w == 0) {
            asm volatile("cp.async.bulk.commit_group;" ::: "memory");
            asm volatile("cp.async.bulk.wait_group.read 0;" ::: "memory");
        }
        asm volatile("bar.sync 1, 256;" ::: "memory");
        if (threadIdx.x == 0) asm volatile("red.relaxed.gpu.global.add.u32 [%0], 1;" :: "l"(g_epoch + 128 + j) : "memory");
        if (threadIdx.x == 0) TLE_REC(128 + j, 1);
    }
}

template <bool k2>
__global__ void CLUSTER_ATTR __launch_bounds__(512, 1)
w8a8_kernel(
            const char* __restrict__ qx, const char* __restrict__ qw, const __nv_bfloat16* __restrict__ scale_x, const int* __restrict__ zero_x,
            const __nv_bfloat16* __restrict__ scale_w, const __nv_bfloat16* __restrict__ bias
            , const __grid_constant__ Maps maps
            ) {
    extern __shared__ __align__(1024) unsigned char smem_raw[];
    if (!k2 && !CFG_LC) asm volatile("griddepcontrol.launch_dependents;");
    constexpr int NBJ = k2 ? 12 : 14, NF = NBJ, NU = k2 ? 40 : NU1;
    const int b = blockIdx.x + (k2 ? NCTA - (CFG_K3L ? 0 : 4) : 0), r = b & 15, c = k2 ? NCL : b >> 4;
    const unsigned tc = clk();
    if (threadIdx.x < CFG_PF * 64 && !k2) {
        const int a = (threadIdx.x >> 6) * NCTA + r * NCL + c;
        asm volatile("prefetch.global.L2 [%0];" :: "l"(qx + ((a & 63) * 32 + ((threadIdx.x >> 1) & 31)) * (K_ * 4) + (a >> 6) * 256 + (threadIdx.x & 1) * 128));
    }
    const uint32_t sb = (uint32_t)__cvta_generic_to_shared(smem_raw);
    const uint32_t bars = sb + SM_BAR;
    const unsigned tw = __shfl_sync(~0u, (tc & ~15u) | threadIdx.x >> 5, 0), t0 = tw + CFG_T0;
    const int warp = tw & 15, lane = threadIdx.x & 31;

    if (CFG_ETM && warp >= 8 && warp < 10 && elect_one()) asm volatile("prefetch.tensormap [%0];" :: "l"(maps.m + (warp & 1)) : "memory");
    if (k2 && (CFG_K3L ? blockIdx.x >= 16 : blockIdx.x < 4)) {
        if (!(DBG & 64)) last_columns(maps, scale_x, zero_x, scale_w, bias, sb, warp, lane, t0);
        return;
    }
    if (warp >= 12) {
        asm volatile("barrier.cluster.arrive.relaxed.aligned;" ::: "memory");
        if (warp == 12 && lane == 0) TLREC(0);
        const int t = k2 ? warp - 12 : warp & 1, isw = k2 || warp >= 14;
        const int x = t * 16 + r, a = (x * NCL + c) ^ CFG_REV, sx = (x * 26) >> 8;
        static_assert(X1 >= 7, "");
        const uint32_t bar = bars + ((isw ? B_RAWB : B_RAWA) + 3 + t) * 8;
        if (elect_one()) {
            mbar_init(bar, 1);
            mbar_expect_tx(bar, 8192);
            const unsigned te = t0 + (k2 ? sched2(x) : (isw ? time_w(x) : time_x(x)) * CFG_P1);
            while ((int)(te - clk()) > 0) ;
            raw_load(maps.m + isw, isw ? sx * 64 : (a >> 6) * 2,
                     isw ? c * (TN / 32) + (int)((0x9765483210ull >> ((x - sx * 10) * 4)) & 15) : (a & 63) * 32,
                     sb + (k2 ? SM_A + 7 * 8192 : isw ? SM_STG : SM_A + 13 * 8192) + ((isw || r * NCL + c >= NAJ % NCTA) ? t : 2 - 2 * t) * 8192, bar);
            TLJ(224 + isw * 10 + t);
        }
        __syncwarp();
    }
    if (warp < 8) {
        const uint32_t p = bars + warp * 104;
        if (elect_one()) {
#pragma unroll
            for (int i = 0; i < 13; i++) mbar_init(p + i * 8, 1);
        }
        __syncwarp();
        const int i = warp * 13 + lane;
        if (lane < 13 && i < B_SW) mbar_expect_tx(p + lane * 8, i >= B_PAR ? (i < B_PAR + 2 ? WA * 2 : WB * 2) : (i & 16) || i >= 48 ? 8192 : WA * 64);
        asm volatile("fence.mbarrier_init.release.cluster;" ::: "memory");
    }
    if (warp < 8 || warp == 10) asm volatile("barrier.cluster.arrive.relaxed.aligned;" ::: "memory");

    if (warp < 8) {
        if (warp < 2 && elect_one()) asm volatile("prefetch.tensormap [%0];" :: "l"(maps.m + 2 + warp) : "memory");
        asm volatile("setmaxnreg.inc.sync.aligned.u32 " STR(CFG_CREG) ";");
        const int wg = warp >> 2;
        const uint32_t sd = (sb & 0x3FFFF) >> 4;
        const unsigned short sxr = __ldg((const unsigned short*)scale_x);
        const uint32_t sx2 = (uint32_t)sxr * 0x10001u;
        const uint32_t par = sb + SM_PAR + (lane & 3) * 16 + wg * 256;
        const uint32_t go = bars + B_GO * 8;
        const int w = warp & 3, pq = (lane >> 2) ^ (lane & 4);
        uint32_t so = (w * 16 + pq) * 128 + (((lane & 3) ^ pq) << 4);
        const int c0 = (w >> 1) * 32 + (lane >> 2) * 4 + (w & 1) * 2, r0 = (lane & 3) * 2;
        uint32_t pp = sb + SM_PAR + (2 * WA + wg * WB + c0) * 2, st0 = r0 * 128 + (((c0 >> 3) ^ r0) << 4) + (c0 & 7) * 2;
        int rq = lane < (k2 ? 1 : 4) ? (k2 ? 1 : 4) * (32 + wg * 8 + ((CFG_R8 && !k2) ? 8 : NSLOT)) + (k2 ? 0 : 32) + lane : 1000;
        asm volatile("" : "+r"(so), "+r"(pp), "+r"(st0), "+r"(rq));
        asm volatile("barrier.cluster.wait.aligned;" ::: "memory");
        if (threadIdx.x == 0) { TLREC(250); TLCLK(251); }
        int a0[WA / 2], a1[WA / 2];
        uint32_t barB = bars + (B_FULLB + wg * 32) * 8;
        wg_fence();
        {
            uint64_t tbl = wg ? slot_table(1) : slot_table(0);
            uint32_t da = (sd + (SM_A >> 4)) | (1 << 16);
            int up = 99;
            bool rdy = false;
#pragma unroll 1
            for (int s = 0; s < 16; s++) {
                const uint32_t db = ((sd + (SM_RING >> 4)) | (8 << 16)) + ((uint32_t)tbl & 15) * (SLOT >> 4);
                const bool hold = CFG_HOLD && (CFG_H2 || !k2) && wg && s == CFG_HS;
                if (hold || (!rdy && !mbar_test2(bars + (B_FULLA + s) * 8, barB))) {
                    wg_wait<0>();
                    release(go, up, lane, k2); up = 99;
                    mbar_wait2(bars + (B_FULLA + s) * 8, barB);
                    if (threadIdx.x % 128 == 0) TLW(160 + wg * 16 + s);
                    if (hold) asm volatile("bar.sync 7, 256;" ::: "memory");
                }
                wgmma_n160(a0, da, db, s);
                wgmma_n160(a1, da + 256, db, s);
                wg_commit();
                if (CFG_HOLD && (CFG_H2 || !k2) && !wg && s == CFG_HOLD) asm volatile("bar.arrive 7, 256;" ::: "memory");
                wg_wait<1>();
                release(go, up, lane, k2);
                wgmma_n160(a0, da + 2, db + 16, 1);
                wgmma_n160(a1, da + 258, db + 16, 1);
                wg_commit();
                if (threadIdx.x % 128 == 0) TLREC(256 + wg * 32 + s);
                up = s < X1 ? 2 * s + wg : (wg ? 16 : X1) + s;
                tbl >>= 4; da += 512; barB += 8;
                if (CFG_RDY) rdy = mbar_test2(bars + (B_FULLA + s + 1) * 8, barB);
                if (s < 15) wg_wait<1>();
            }
        }
        mbar_wait2(bars + (B_PAR + wg) * 8, bars + B_SW * 8);
        Par P = ld_par(par);
        wg_wait<0>();
        release(go, wg ? 31 : X1 + 15, lane, k2);
        if (threadIdx.x % 128 == 0) { TLREC(1 + wg); TLE_REC(b, 4 + wg); }
        bool ready = mbar_test(barB);
#define FILL_BEGIN(n0, n1) mbar_wait(bars + (B_FREE + (wg ? n1 : n0)) * 8);                                              \
                           const uint32_t buf = sb + SM_STG + (wg ? (n1 + NBJ) % 3 : (n0 + NBJ) % 3) * 8192;
#define FILL_END(n0, n1) __syncwarp(); if (elect_one()) mbar_arrive(bars + (B_FILL + (wg ? n1 % 3 : n0 % 3)) * 8);        \
                         if (threadIdx.x % 128 == 0) TLREC(16 + (wg ? n1 : n0));
#define FILL_PAIR(a, J, PN, n0, n1)                                                                                     \
        {                                                                                                               \
            const uint4 v0 = epi_row(a, J * 16, P, sx2);                                                                \
            const Par Q = ld_par(par + J * 64 + 64);                                                                    \
            const uint4 v1 = epi_row(a, J * 16 + 2, P, sx2);                                                            \
            if (CFG_EARLY == 2 && (n0) == ford(0, NA0)) { wg_wait<0>(); if (wg == 0) RELEASE_N() }                      \
            FILL_BEGIN(n0, n1)                                                                                          \
            sts128(buf + so, v0); sts128(buf + so + 1024, v1);                                                          \
            if ((PN) >= 0) P = ld_par(par + (PN));                                                                      \
            sts128(buf + (so ^ 64), epi_row(a, J * 16 + 16, Q, sx2));                                                   \
            sts128(buf + (so ^ 64) + 1024, epi_row(a, J * 16 + 18, Q, sx2));                                            \
            FILL_END(n0, n1)                                                                                            \
        }
        constexpr int rn = k2 ? 1 : 4;
#define RELEASE_N() { if (rq < (k2 ? NU : NBJ * 16)) mbar_arrive_cluster(mapa(go + (rq >> rn) * 8, rq & ((1 << rn) - 1))); rq += rn; nrel++; }
#define NARROW(p)                                                                                                       \
        {                                                                                                               \
            uint32_t tbl = (uint32_t)slot_table(p), da = (sd + (SM_A >> 4)) | (1 << 16);                                \
            wg_fence();                                                                                                 \
            _Pragma("unroll 1") for (int i = 0; i < 8; i++) {                                                           \
                const uint32_t db = ((sd + (SM_RING >> 4)) | (8 << 16)) + ((CFG_R8 && !k2) ? ((i + 5) & 7) * 512 : (tbl & 15) * (SLOT >> 4)); \
                if (!ready && !mbar_test(barB)) {                                                                       \
                    wg_wait<0>();                                                                                       \
                    if (p == 2 || !CFG_R8) { _Pragma("unroll 1") while (nrel < i) RELEASE_N() }                         \
                    mbar_wait(barB);                                                                                    \
                }                                                                                                       \
                _Pragma("unroll") for (int kk = 0; kk < 4; kk++)                                                        \
                    wgmma_t128(t, db + (kk >> 1) * 256 + (kk & 1) * 16, da + (kk >> 1) * 512 + (kk & 1) * 2, kk ? 1 : i); \
                wg_commit();                                                                                            \
                if (threadIdx.x % 128 == 0) TLREC(256 + (p == 2 ? 16 : 48) + i);                                        \
                barB += 8;                                                                                              \
                ready = mbar_test(barB);                                                                                \
                if ((p == 2 || !CFG_R8) && nrel < i - CFG_QD) RELEASE_N()                                               \
                tbl >>= 4; da += 1024;                                                                                  \
                wg_wait<CFG_QD>();                                                                                      \
            }                                                                                                           \
            if (p == 2) { if (nrel < 8 - CFG_QD) RELEASE_N() if (NA0 < 5) P = ld_par(par + pn); }                       \
            else { zc = lds32(pp); sw = lds32(pp + TN * 2); bi = lds32(pp + TN * 4); }                                  \
            if (p == 3 || !CFG_EARLY) wg_wait<0>();                                                                     \
            if (p == 2 && !CFG_EARLY) RELEASE_N()                                                                       \
            if (threadIdx.x % 128 == 0) TLREC(3 + p);                                                                   \
        }
#define FO(m) ford(0, m), ford(1, m)
#define FILL_PAIR2(...) FILL_PAIR(__VA_ARGS__)
#define NARROW_AT(k, PN) if (NA0 == k) { pn = PN; if (wg == 0) NARROW(2) else if (k < 5) P = ld_par(par + pn); }   \
                         if (CFG_EARLY == 1 && NA0 == k - 1) { wg_wait<0>(); if (wg == 0) RELEASE_N() }
        int nrel = 0, pn = 0;
        static_assert(CFG_EARLY != 2 || NA0 < 4, "");
        FILL_PAIR2(a0, 0, 128, FO(0)) FILL_PAIR2(a0, 2, NA0 == 2 ? -1 : 0, FO(1))
        int t[64];
        uint32_t zc, sw, bi;
        NARROW_AT(2, 0)
        FILL_PAIR2(a1, 0, NA0 == 3 ? -1 : 128, FO(2))
        NARROW_AT(3, 128)
        FILL_PAIR2(a1, 2, NA0 == 4 ? -1 : 512 - wg * 192, FO(3))
        NARROW_AT(4, 512 - wg * 192)
        {
            const uint4 v0 = epi_row(a0, 64, P, sx2), v1 = epi_row(a0, 66, P, sx2);
            if (!(k2 && wg) && NA0 < 5) mbar_wait(bars + (B_PAR + 2 + wg) * 8);
            FILL_BEGIN(ford(0, 4), ford(1, 4))
            const uint32_t s4 = buf + ((so >> 1) & ~63u) + (lane & 3) * 16;
            sts128(s4, v0); sts128(s4 + 512, v1);
            sts128(s4 + 4096, epi_row(a1, 64, P, sx2)); sts128(s4 + 4608, epi_row(a1, 66, P, sx2));
            FILL_END(ford(0, 4), ford(1, 4))
        }
        NARROW_AT(5, 0)
        if (!(k2 && wg) && NA0 == 5) mbar_wait(bars + (B_PAR + 2 + wg) * 8);
        NARROW_AT(6, 0)
        if (!(k2 && wg)) {
        if (!k2 && wg == 1) NARROW(3) else { zc = lds32(pp); sw = lds32(pp + TN * 2); bi = lds32(pp + TN * 4); }
#define FILL_T(h)                                                                                                       \
        {                                                                                                               \
            FILL_BEGIN((10 + h), (12 + h))                                                                              \
            _Pragma("unroll") for (int j = 0; j < 8; j++) {                                                             \
                const int o = h * 32 + j * 4;                                                                           \
                sts32(buf + st0 + j * 1024, bf2_op_epi(t[o], t[o + 2], zc, sx2, sw, bi));                               \
                sts32(buf + (st0 ^ (5 * 128 + 5 * 16)) + j * 1024, bf2_op_epi(t[o + 1], t[o + 3], zc, sx2, sw, bi));    \
            }                                                                                                           \
            FILL_END((10 + h), (12 + h))                                                                                \
        }
        FILL_T(0) FILL_T(1)
        }
        if (DBG & 4) for (int i = 0; i < 56; i++) mbar_wait(bars + i * 8);
        if (threadIdx.x == 0) { TLREC(252); TLCLK(253); }
        TLEND();
        if (threadIdx.x == 128) asm volatile("red.relaxed.gpu.global.add.u32 [%0], 1;" :: "l"(g_epoch + b) : "memory");
    } else {
        const int g = r * NCL + c, na = k2 ? 0 : NAJ / NCTA + (g < NAJ % NCTA);
        int cw = NF;
        if (warp >= 12) {
            asm volatile("setmaxnreg.dec.sync.aligned.u32 " STR(CFG_RC) ";");
            if (warp < 14) {
                const int c4 = (lane ^ (lane >> 3)) & 3, ln = ((lane >> 2) ^ (lane & 4)) * 2 + (c4 >> 1);
                const uint32_t rd0 = sb + SM_A + 13 * 8192 + ln * 128 + ((((c4 & 1) << 2) ^ (ln & 7)) << 4);
#pragma unroll 1
                for (int t = warp - 12, sl = na == 9 ? t : 2 - 2 * t; t < na; t += 2, sl = sl ? sl - 1 : 2) {
                    const uint32_t rdA = rd0 + sl * 8192;
                    const int a = (t * NCTA + g) ^ CFG_REV, f = (a & 60) * 4 + (a >> 6);
                    uint4* const d = g_s8 + (f * 4 + (a & 3)) * 128 + lane;
                    uint4 o[4];
                    mbar_wait(bars + (B_RAWA + 3 + t) * 8);
                    if (lane == 0) TLJ(128 + t);
#pragma unroll
                    for (int i = 0; i < 4; i++) {
                        uint4 v0 = lds128(rdA + i * 2048), v1 = lds128((rdA ^ 16) + i * 2048);
                        uint4 v2 = lds128((rdA ^ 32) + i * 2048), v3 = lds128((rdA ^ 48) + i * 2048);
                        o[i].x = pack4(v0.x, v0.y, v0.z, v0.w); o[i].y = pack4(v1.x, v1.y, v1.z, v1.w);
                        o[i].z = pack4(v2.x, v2.y, v2.z, v2.w); o[i].w = pack4(v3.x, v3.y, v3.z, v3.w);
                    }
#pragma unroll
                    for (int i = 0; i < 4; i++) stg128(d + i * 32, o[i]);
                    unsigned rb;
                    if (CFG_WF) asm volatile("fence.proxy.async.global;" ::: "memory");
                    __syncwarp();
                    READ_BACK
                    if (t < 2) asm volatile("barrier.cluster.wait.aligned;" ::: "memory");
                    if (elect_one()) mbar_arrive(bars + ((t < na - 3 ? B_RAWA : B_AFREE + 13) + sl) * 8);
                    if (lane == 0) TLJ(160 + t);
                    if (__shfl_sync(~0u, rb ^ o[0].x, CFG_RB16 ? 6 : 0)) asm volatile("fence.acq_rel.gpu;" ::: "memory");
                    if (elect_one()) asm volatile("red.relaxed.gpu.global.add.u32 [%0], 1;" :: "l"(g_flag + (a & 60) * 8 + (a >> 6)) : "memory");
                    if (lane == 0) TLJ(192 + t);
                }
                cw = warp - 12;
            }
            {
                const uint32_t rd0 = sb + (lane >> 3) * 2048 + (lane & 7) * 16;
                const BJob mb = decode_b((lane & 15) * 16 + r);
                const int myG = mb.G | mb.u << 8;
#pragma unroll 1
                for (int t = k2 ? warp - 12 : warp < 14 ? CFG_TB + warp - 10 : warp - 14; t < NBJ; t += (!k2 && t < CFG_TB) ? 2 : 4) {
                    const uint32_t rdB = rd0 + stage_w<k2>(t);
                    uint4* const d = g_s8 + (1024 + c * 256 + t * 16 + r) * 128 + lane;
                    uint4 o[4];
                    mbar_wait(bars + (B_RAWB + 3 + t) * 8);
                    if (lane == 0) TLJ(138 + t);
                    CV_B(0, x) CV_B(1, y) CV_B(2, z) CV_B(3, w)
#pragma unroll
                    for (int i = 0; i < 4; i++) stg128(d + i * 32, o[i]);
                    if (t < (k2 ? 4 : 2)) asm volatile("barrier.cluster.wait.aligned;" ::: "memory");
                    if (elect_one()) mbar_arrive(bars + ((k2 || t >= NBJ - 3) ? B_FREE + t - (NBJ - 3) : B_RAWB + t % 3) * 8);
                    asm volatile("fence.proxy.async.global;" ::: "memory");
                    __syncwarp();
                    unsigned rb = 0, ep = 0;
                    if (k2) {
                        READ_BACK
                        ep = ld_flag(g_epoch + b);
                    } else if (elect_one()) mbar_arrive(bars + (B_GO + t) * 8);
                    if (lane == 0) TLREC((TL2 ? 234 : 170) + t);
                    int cs[4];
#pragma unroll
                    for (int i = 0; i < 4; i++)
                        cs[i] = __dp4a((int)o[i].x, 0x01010101, __dp4a((int)o[i].y, 0x01010101,
                                __dp4a((int)o[i].z, 0x01010101, __dp4a((int)o[i].w, 0x01010101, 0))));
                    const bool h = lane & 16, odd = lane & 8;
                    int x = (h ? cs[2] : cs[0]) + __shfl_xor_sync(~0u, h ? cs[0] : cs[2], 16);
                    int y = (h ? cs[3] : cs[1]) + __shfl_xor_sync(~0u, h ? cs[1] : cs[3], 16);
                    const int v = (odd ? y : x) + __shfl_xor_sync(~0u, odd ? x : y, 8);
                    const int gu = __shfl_sync(~0u, myG, t), G = gu & 255;
                    if (k2) {
                        if (__shfl_sync(~0u, rb ^ o[0].x, CFG_RB16 ? 6 : 0)) asm volatile("fence.acq_rel.gpu;" ::: "memory");
                        if (elect_one()) asm volatile("red.relaxed.gpu.global.add.u32 [%0], 1;" :: "l"(g_flag + 512 + (gu >> 8)) : "memory");
                        if (lane == 0) TLJ(202 + t);
                        const int old = atomicAdd(g_cs[ep & 1] + col_of(G) + (lane & 7) * 4 + (lane >> 3), v);
                        if (old == 0x7FFFFFFF) g_sink = old;
                        __syncwarp();
                        if (elect_one()) asm volatile("red.relaxed.gpu.global.add.u32 [%0], 1;" :: "l"(g_flag + 576 + (t >= 10)) : "memory");
                    } else if (G != r) {
                        asm volatile("red.async.relaxed.cluster.shared::cluster.mbarrier::complete_tx::bytes.add.s32 [%0], %1, [%2];"
                                     :: "r"(mapa(sb + SM_CS + lane * 4, G)), "r"(v), "r"(mapa(bars + B_CS * 8, G)) : "memory");
                    } else {
                        asm volatile("red.shared.add.s32 [%0], %1;" :: "r"(sb + SM_CS + lane * 4), "r"(v) : "memory");
                        __syncwarp();
                        if (elect_one()) mbar_arrive(bars + B_CS * 8);
                    }
                    if (lane == 0 && !k2) TLJ(202 + t);
                }
            }
        } else {
            asm volatile("setmaxnreg.dec.sync.aligned.u32 " STR(CFG_RO) ";");
            if (warp == 11) {
            if (elect_one()) {
#pragma unroll
                for (int i = 0; i < (k2 ? NU / 2 : NBJ); i++) mbar_init(bars + (B_GO + i) * 8, k2 ? (i * 2 + (r & 1) >= NSLOT ? 9 : 1) : i * 16 + r >= NSLOT * 5 ? 1 + 4 * CS : 1);
#pragma unroll
                for (int i = 0; i < 3; i++) mbar_init(bars + (B_FILL + i) * 8, 4);
            }
            const int u2 = lane * 2 + (r & 1), q = k2 ? (u2 < 32 ? 5 * u2 : 4 * u2 + 32) : (lane & 15) * 16 + r;
            const BJob bj = decode_b(q);
            const int nself = __popc(__ballot_sync(~0u, lane < NBJ && bj.G == r));
            sts32(sb + SM_CS + lane * 4, 0);
            if (lane == 0) {
                mbar_init(bars + B_CS * 8, 1 + nself);
                mbar_expect_tx(bars + B_CS * 8, (16 - nself) * 128);
            }

            asm volatile("fence.mbarrier_init.release.cluster;" ::: "memory");
            asm volatile("barrier.cluster.arrive.relaxed.aligned;" :: "r"(lds32(sb + SM_CS + lane * 4)) : "memory");
            const char* src = (const char*)g_s8 + (1024 + c * 256 + q) * 2048;
            const uint32_t dst = sb + SM_RING + ((CFG_R8 && !k2 && q >= 160) ? ((q + 20) & 31) * 2048 : (bj.u % NSLOT) * SLOT + bj.pos * 2048);
            const uint32_t fb = bars + (B_FULLB + fb_of(bj.u)) * 8;
            asm volatile("barrier.cluster.wait.aligned;" ::: "memory");
            {
                const uint32_t sx2 = (uint32_t)__ldg((const unsigned short*)scale_x) * 0x10001u;
#pragma unroll
                for (int i = lane; i < TN / 4; i += 32) {
                    const bool hi = i >= TN / 8;
                    uint4 v = __ldg((const uint4*)((hi ? bias : scale_w) + c * TN) + (hi ? i - TN / 8 : i));
                    if (CFG_EPI == 2 && !hi) {
                        asm("mul.rn.bf16x2 %0, %0, %1;" : "+r"(v.x) : "r"(sx2)); asm("mul.rn.bf16x2 %0, %0, %1;" : "+r"(v.y) : "r"(sx2));
                        asm("mul.rn.bf16x2 %0, %0, %1;" : "+r"(v.z) : "r"(sx2)); asm("mul.rn.bf16x2 %0, %0, %1;" : "+r"(v.w) : "r"(sx2));
                    }
                    sts128(sb + SM_PAR + TN * 2 + i * 16, v);
                }
                __syncwarp();
                if (elect_one()) mbar_arrive(bars + B_SW * 8);
            }
#pragma unroll 1
            for (int i = 0; i < (k2 ? NU / 2 : NBJ); i++) {
                mbar_wait(bars + (B_GO + i) * 8);
                if (lane == i) {
                    asm volatile("cp.async.bulk.shared::cluster.global.mbarrier::complete_tx::bytes.multicast::cluster [%0], [%1], %2, [%3], %4;"
                                 :: "r"(dst), "l"(src), "r"(k2 ? (u2 < 32 ? SLOT : 8192) : 2048), "r"(fb), "h"((uint16_t)(k2 ? 3 : 0xFFFF)) : "memory");
                    TLREC(64 + i);
                }
                __syncwarp();
            }
            } else if (warp == 10) {
            const unsigned ep = (*(volatile unsigned*)&g_epoch[b] + 1) * 4;
            const unsigned* f = g_flag + (CFG_FL == 1 ? 1024 + b * 32 + (lane & 15) : CFG_FL == 3 ? 1024 + (r * 16 + (lane & 15)) * 32 : r * 32 + (lane & 15));
            bool dn = lane >= 16;
            const bool fr = lane < (k2 ? 7 : 13);
            asm volatile("barrier.cluster.wait.aligned;" ::: "memory");
            if (lane == 0) TLREC(15);
#define CHECK(v)                                                                                                        \
                if (!dn && (int)(v - ep) >= 0 && (fr || mbar_test(bars + (B_AFREE + lane) * 8))) {                 \
                    dn = true;                                                                                          \
                    if (!CFG_WF) asm volatile("fence.proxy.async.global;" ::: "memory");                                \
                    asm volatile("cp.async.bulk.shared::cluster.global.mbarrier::complete_tx::bytes [%0], [%1], %2, [%3];" \
                                 :: "r"(sb + SM_A + lane * 8192), "l"((const char*)g_s8 + (r * 16 + lane) * 8192),      \
                                    "r"(8192), "r"(bars + (B_FULLA + lane) * 8) : "memory");                            \
                    TLREC(112 + lane);                                                                                  \
                }                                                                                                       \
                if (__all_sync(~0u, dn)) break;
            for (int it = 0;; it++) {
                const unsigned v = ld_flag(f);
                if (lane == 0 && (it & 3) == 0 && it < 64) TLREC(88 + (it >> 2));
                CHECK(v)
                if (it > (1 << 22)) __trap();
            }
            } else {
                const bool isw = warp == 9;
                const uint32_t rb = bars + (isw ? B_RAWB : B_RAWA) * 8;
                if (elect_one()) {
#pragma unroll
                    for (int i = 0; i < 13; i++) if (i < 3 || i >= (k2 ? 7 : 5)) mbar_init(rb + i * 8, 1);
                    if (isw) {
                        if (!CFG_ETM) asm volatile("prefetch.tensormap [%0];" :: "l"(maps.m + 1) : "memory");
#pragma unroll
                        for (int i = 13; i < 17; i++) mbar_init(rb + i * 8, 1);
                    }
                }
                __syncwarp();
                const int nj = isw ? NBJ : na, j0 = k2 ? 4 : 2;
                if (lane >= j0 && lane < nj) mbar_expect_tx(rb + (3 + lane) * 8, 8192);
                asm volatile("fence.mbarrier_init.release.cluster;" ::: "memory");
                asm volatile("barrier.cluster.arrive.relaxed.aligned;" ::: "memory");
                const int k = lane / 3, x = lane * 16 + r;
                int sl = lane - k * 3, y, z, T;
                if (isw) {
                    const BJob bj = decode_b(x & 255);
                    y = bj.slab * 64; z = (c * TN + col_of(bj.G)) >> 5; T = time_w(x);
                    if (CFG_BURST && T < NAJ / NCL + x) {
                        const int ph = ((((T - L0) * 16 / RA + L0) * 7) + 32) & 63;
                        T += ((32 - ph) * 16 * CFG_BURST) / (16 * 7 * 4);
                    }
                } else {
                    const int a0 = lane * NCTA + g, a = a0 ^ CFG_REV;
                    y = (a >> 6) * 2; z = (a & 63) * 32; T = time_x(x);
                    if (CFG_BURST && x >= L0 + 9) T += ((32 - (a0 & 63)) * (RA - 16) * CFG_BURST) / (16 * 7 * 4);
                    if (na == 10) sl = sl ? sl - 1 : 2;
                }
                const unsigned te = t0 + (k2 ? sched2(x) : sched(T));
                const uint32_t sd = sb + (isw ? stage_w<k2>(lane) : SM_A + (13 + sl) * 8192);
#pragma unroll 1
                for (int t = j0; t < nj; t++) {
                    if (lane == t) {
                        if (t >= 3 && !k2) mbar_wait(rb + sl * 8, (k & 1) ^ 1);
                        while ((int)(te - clk()) > 0) ;
                        raw_load(maps.m + isw, y, z, sd, rb + (3 + t) * 8);
                        TLJ(224 + isw * 10 + t);
                    }
                    __syncwarp();
                }
                asm volatile("barrier.cluster.wait.aligned;" ::: "memory");
                if (!k2 && !isw) {
#pragma unroll 1
                    for (int t = CFG_PFB; t < NBJ; t++) {
                        const int q = t * 16 + r - 160;
                        const char* p = qw + (((q >> 1) & 15) * 64 + lane) * (N_ * 4) + (c * TN + 320 + (q >> 5) * 64 + (q & 1) * 32) * 4;
                        const unsigned tp = t0 + sched(NAJ / NCL + 160 + q + CFG_PFO);
                        while ((int)(tp - clk()) > 0) ;
                        asm volatile("prefetch.global.L2 [%0];" :: "l"(p));
                        asm volatile("prefetch.global.L2 [%0];" :: "l"(p + 32 * N_ * 4));
                    }
                }
                if (!isw) cw = 2;
                if (k2) {
                    const unsigned e0 = *(volatile unsigned*)&g_epoch[b];
                    if (!isw) {
                        if (lane < TN / 16) g_cs[(e0 & 1) ^ 1][r * (TN / 16) + lane] = 0;
                        const int u = lane * 2 + (r & 1);
                        const unsigned tg = (e0 + 1) * (u < 32 ? 5 : 4);
                        bool dn = u >= NU;
                        for (int it = 0;; it++) {
                            if (!dn && (int)(ld_flag(g_flag + 512 + u) - tg) >= 0) {
                                dn = true;
                                mbar_arrive(bars + (B_GO + lane) * 8);
                            }
                            if (__all_sync(~0u, dn)) break;
                            if (it > (1 << 22)) __trap();
                        }
                    } else {
                        const float zxf = __bfloat162float(__float2bfloat16_rn((float)__ldg(zero_x)));
#pragma unroll 1
                        for (int h = 0; h < 2; h++) {
                            for (int it = 0; (int)(ld_flag(g_flag + 576 + h) - (e0 + 1) * (h ? 32 : 160)) < 0; it++) if (it > (1 << 22)) __trap();
                            int2 v[5];
#pragma unroll
                            for (int j = 0; j < 5; j++) v[j] = __ldcg((const int2*)g_cs[e0 & 1] + min(h * 160 + j * 32 + lane, TN / 2 - 1));
#pragma unroll
                            for (int j = 0; j < 5; j++) {
                                const int i = h * 160 + j * 32 + lane;
                                const float lo = __bfloat162float(__float2bfloat16_rn((float)v[j].x)) * zxf;
                                const float hi = __bfloat162float(__float2bfloat16_rn((float)v[j].y)) * zxf;
                                uint32_t z;
                                asm("cvt.rn.bf16x2.f32 %0, %1, %2;" : "=r"(z) : "f"(hi), "f"(lo));
                                if (i < TN / 2 - 32)
                                    asm volatile("st.async.weak.shared::cluster.mbarrier::complete_tx::bytes.b32 [%0], %1, [%2];"
                                                 :: "r"(sb + SM_PAR + i * 4), "r"(z), "r"(bars + (B_PAR + (i < 128 ? i >> 6 : i < 160 ? (i >> 4) & 1 : (i >> 5) - 3)) * 8) : "memory");
                            }
                            if (lane == 0) TLREC(8 + h);
                        }
                    }
                }
            }
            if (!k2 && r < NBJ && warp == (r < 10 ? 8 : 10)) {
            const float zxf = __bfloat162float(__float2bfloat16_rn((float)__ldg(zero_x)));
            mbar_wait(bars + B_CS * 8);
            const int w = lane & 15;
            const uint32_t ca = sb + SM_CS + ((w >> 1) + (w & 1) * 16) * 4;
            const float lo = __bfloat162float(__float2bfloat16_rn((float)(int)lds32(ca))) * zxf;
            const float hi = __bfloat162float(__float2bfloat16_rn((float)(int)lds32(ca + 32))) * zxf;
            uint32_t z;
            asm("cvt.rn.bf16x2.f32 %0, %1, %2;" : "=r"(z) : "f"(hi), "f"(lo));
            const int piece = r < 10 ? (r >= 5) : (r - 6) >> 1;
#pragma unroll 1
            for (int i = lane >> 4; i < CS; i += 2)
                asm volatile("st.async.weak.shared::cluster.mbarrier::complete_tx::bytes.b32 [%0], %1, [%2];"
                             :: "r"(mapa(sb + SM_PAR + col_of(r) * 2 + w * 4, i)), "r"(z), "r"(mapa(bars + (B_PAR + piece) * 8, i)) : "memory");
            if (lane == 0) TLREC(8);
            }
        }
#pragma unroll 1
            for (int n = cw, k = 0; n < NF; n += 3, k ^= 1) {
                const int gm = (int)(ford_table() >> (4 * n)), g = (gm >> 3) & 1, m = gm & 7;
                const int x = n >= 10 ? (n >> 1) * 64 : m == 4 ? 256 + g * 32 : g * 128 + (m & 1) * 64;
                const int y = n >= 10 ? (n & 1) * 64 : (m & 2) * 32;
                mbar_wait(bars + (B_FILL + cw) * 8, k);
                asm volatile("fence.proxy.async.shared::cta;" ::: "memory");
                if (!(DBG & 2) && elect_one())
                    asm volatile("cp.async.bulk.tensor.2d.global.shared::cta.tile.bulk_group [%0, {%1, %2}], [%3];"
                                 :: "l"(maps.m + (n < 10 && m == 4 ? 3 : 2)), "r"(c * TN + x), "r"(r * 128 + y), "r"(sb + SM_STG + ((cw + NBJ) % 3) * 8192) : "memory");
                asm volatile("cp.async.bulk.commit_group;" ::: "memory");
                if (lane == 0) TLREC(32 + n);
                asm volatile("cp.async.bulk.wait_group.read 0;" ::: "memory");
                __syncwarp();
                if (n < NF - 3 && elect_one()) mbar_arrive(bars + (B_FREE + 3 + n) * 8);
                if (lane == 0) TLREC(48 + n);
            }
        if (cw < 3 && lane == 0) TLE_REC(b, 1 + cw);
        TLEND();
    }
}

}

typedef CUresult (*EncodeFn)(CUtensorMap*, CUtensorMapDataType, cuuint32_t, void*, const cuuint64_t*, const cuuint64_t*,
                             const cuuint32_t*, const cuuint32_t*, CUtensorMapInterleave, CUtensorMapSwizzle,
                             CUtensorMapL2promotion, CUtensorMapFloatOOBfill);

extern "C" void kernel_launch(void* const* d_in, const int* in_sizes, int n_in, void* d_out, int out_size) {
    using namespace w8;
    static EncodeFn encode = nullptr;
    static cudaStream_t side;
    static cudaEvent_t started, joined;
    if (!encode) {
        void* fn = nullptr;
        cudaDriverEntryPointQueryResult qr;
        cudaGetDriverEntryPoint("cuTensorMapEncodeTiled", &fn, cudaEnableDefault, &qr);
        encode = (EncodeFn)fn;
        cudaStreamCreateWithFlags(&side, cudaStreamNonBlocking);
        cudaEventCreateWithFlags(&started, cudaEventDisableTiming);
        cudaEventCreateWithFlags(&joined, cudaEventDisableTiming);
        cudaFuncSetAttribute(w8a8_kernel<false>, cudaFuncAttributeMaxDynamicSharedMemorySize, SM_ALLOC);
        cudaFuncSetAttribute(w8a8_kernel<true>, cudaFuncAttributeMaxDynamicSharedMemorySize, SM_ALLOC);
        cudaFuncSetAttribute(w8a8_kernel<false>, cudaFuncAttributeNonPortableClusterSizeAllowed, 1);
    }
    Maps maps;
    {
        const cuuint64_t dim[3] = {32, K_ / 32, M_}, str[2] = {128, K_ * 4};
        const cuuint32_t box[3] = {32, 2, 32}, es[3] = {1, 1, 1};
        encode(&maps.m[0], CU_TENSOR_MAP_DATA_TYPE_INT32, 3, d_in[0], dim, str, box, es, CU_TENSOR_MAP_INTERLEAVE_NONE,
               CU_TENSOR_MAP_SWIZZLE_128B, CU_TENSOR_MAP_L2_PROMOTION_NONE, CU_TENSOR_MAP_FLOAT_OOB_FILL_NONE);
    }
    {
        const cuuint64_t dim[3] = {32, K_, N_ / 32}, str[2] = {N_ * 4, 128};
        const cuuint32_t box[3] = {32, 64, 1}, es[3] = {1, 1, 1};
        encode(&maps.m[1], CU_TENSOR_MAP_DATA_TYPE_INT32, 3, d_in[1], dim, str, box, es, CU_TENSOR_MAP_INTERLEAVE_NONE,
               CU_TENSOR_MAP_SWIZZLE_NONE, (CUtensorMapL2promotion)CFG_PROMO, CU_TENSOR_MAP_FLOAT_OOB_FILL_NONE);
    }
    {
        const cuuint64_t dim[2] = {N_, M_}, str[1] = {N_ * 2};
        const cuuint32_t box[2] = {WB, 64}, es[2] = {1, 1};
        encode(&maps.m[2], CU_TENSOR_MAP_DATA_TYPE_BFLOAT16, 2, d_out, dim, str, box, es, CU_TENSOR_MAP_INTERLEAVE_NONE,
               CU_TENSOR_MAP_SWIZZLE_128B, CU_TENSOR_MAP_L2_PROMOTION_NONE, CU_TENSOR_MAP_FLOAT_OOB_FILL_NONE);
    }
    {
        const cuuint64_t dim[2] = {N_, M_}, str[1] = {N_ * 2};
        const cuuint32_t box[2] = {32, 128}, es[2] = {1, 1};
        encode(&maps.m[3], CU_TENSOR_MAP_DATA_TYPE_BFLOAT16, 2, d_out, dim, str, box, es, CU_TENSOR_MAP_INTERLEAVE_NONE,
               CU_TENSOR_MAP_SWIZZLE_NONE, CU_TENSOR_MAP_L2_PROMOTION_NONE, CU_TENSOR_MAP_FLOAT_OOB_FILL_NONE);
    }
    for (int k = 0; k < ((DBG & 32) ? 1 : 2); k++) {
        cudaLaunchConfig_t cfg = {};
        cfg.gridDim = dim3(k ? 20 : NCTA); cfg.blockDim = dim3(512); cfg.dynamicSmemBytes = SM_ALLOC; cfg.stream = cudaStreamPerThread;
        cudaLaunchAttribute at[2];
        at[0].id = cudaLaunchAttributeClusterDimension; at[0].val.clusterDim.x = k ? 2 : CS; at[0].val.clusterDim.y = 1; at[0].val.clusterDim.z = 1;
        at[1].id = cudaLaunchAttributeProgrammaticStreamSerialization; at[1].val.programmaticStreamSerializationAllowed = 1;
        cfg.attrs = at; cfg.numAttrs = 1 + k;
        at[1].id = cudaLaunchAttributeLaunchCompletionEvent; at[1].val.launchCompletionEvent.event = started; at[1].val.launchCompletionEvent.flags = 0;
        cfg.numAttrs = 2 - k;
        if (k) { cudaStreamWaitEvent(side, started, 0); cfg.stream = side; }
        if (k && CFG_DOM) { at[1].id = cudaLaunchAttributeMemSyncDomain; at[1].val.memSyncDomain = cudaLaunchMemSyncDomainRemote; cfg.numAttrs = 2; }
        cudaLaunchKernelEx(&cfg, k ? w8a8_kernel<true> : w8a8_kernel<false>,
                           (const char*)d_in[0], (const char*)d_in[1], (const __nv_bfloat16*)d_in[2], (const int*)d_in[3], (const __nv_bfloat16*)d_in[4], (const __nv_bfloat16*)d_in[5]
                           , maps
                           );
        if (k) { cudaEventRecord(joined, side); cudaStreamWaitEvent(cudaStreamPerThread, joined, 0); }
    }
}
```

```cpp
#include <cuda_runtime.h>
#include <cuda.h>
#include <cuda_bf16.h>
#include <stdint.h>

#define CFG_X1 13
#define CFG_P1 46
#define CFG_P2 38
#define CFG_PT 100
#define CFG_L0 32
#define CFG_T0 -300
#define CFG_ACQ 0
#define CFG_MODE 1
#define CFG_PF 0
#define CFG_MC 16
#define CFG_NP 2
#define CFG_D 0
#define CFG_NL 2
#define CFG_R4 2
#define CFG_TD 30
#define CFG_TD0 1200
#define CFG_TDS 600
#define CFG_EPI 2
#define CFG_SLEEP 0
#define CFG_POLL2 0
#define CFG_PF2 0
#define CFG_PREG 56
#define CFG_CREG 200
#define STR2(x) #x
#define STR(x) STR2(x)
#define CFG_WF 1
#define CFG_FL 2
#define CFG_TB 8
#define CFG_Q2 63
#define CFG_PF7 18
#define CFG_Q0 14
#define CFG_NS 1
#define CFG_TS 8
#define CFG_Q3 30
#define CFG_RA 34
#define CFG_SH 0
#define CFG_WIN 2
#define CFG_HOLD 14
#define CFG_HS CFG_X1
#define CFG_PRE 1
#define CFG_P3 CFG_P2
#define CFG_PT3 210
#define CFG_LC 1
#define CFG_T3 1000
#define CFG_K3L 1
#define CFG_H2 1
#define CFG_D3 2
#define CFG_PROMO 0
#define CFG_RC 80
#define CFG_RO 32
#define CFG_PFIRST 1
#define CFG_CD 1
#define CLUSTER_ATTR __cluster_dims__(k2 ? 2 : 16, 1, 1)
#define CFG_ETM 1
#define CFG_EF 0
#define CFG_RB16 1
#define CFG_R8 1
#define CFG_RDY 1
#define CFG_QD 1
#define CFG_XA 96
#define CFG_RA2 CFG_RA
#define CFG_EARLY 0
#define CFG_REV 60
#define CFG_BURST 0
#define CFG_NA0 3
#define CFG_DOM 0
#define CFG_P3L 1
#define CFG_PFB 14
#define CFG_PFO 0
#define CFG_FAST0 1
#define CFG_PA0 0
#define CFG_ST3 1
#define CFG_KA 8
#define CFG_KB 9
#define DBG 0

namespace w8 {

constexpr int M_ = 2048, K_ = 1024, N_ = 3584;
constexpr int CS = 16, NCL = 7, NCTA = CS * NCL;
constexpr int WA = 160, WB = 64;
constexpr int NP = CFG_NP, TN = 2 * WA + NP * WB;
constexpr int DA = CFG_D, NL = CFG_NL, R4 = CFG_R4;
constexpr int NAJ = 1024;
constexpr int X1 = CFG_X1;
constexpr int NSLOT = 7, SLOT = WA * 64;
constexpr int NU1 = 48;
constexpr int NCONV = 4;
constexpr int L0 = CFG_L0, NS = CFG_NS;

constexpr int SM_A = 0;
constexpr int SM_RING = 131072;
constexpr int SM_STG = SM_RING + NSLOT * SLOT;
constexpr int SM_PAR = SM_STG + 3 * 8192;
constexpr int SM_CS = SM_PAR + 3 * TN * 2;
constexpr int SM_BAR = SM_CS + 128;
constexpr int B_FULLB = 0, B_FULLA = 56, B_PAR = 72, B_SW = 77, B_AFREE = 79 - 5  , B_FREE = 90, B_NINIT = 104,
              B_GO = 104, B_FILL = 128, B_CS = 131, B_RAWA = 132, B_RAWB = 145, B_RAWS = 162, B_END = 163;
constexpr int SM_TOTAL = SM_BAR + B_END * 8;
static_assert(SM_TOTAL <= 232448, "");

__device__ uint4 g_s8[(1024 + 8 * 256) * 128];
__device__ unsigned g_flag[1024 + 8192];
__device__ int g_cs[2][TN];
__device__ int g_sink;
__device__ unsigned g_epoch[132];
#define TLE_REC(b, i) do {} while (0)
#define TLREC(i) do {} while (0)
#define TLCLK(i) do {} while (0)
#define TLEND() do {} while (0)
constexpr int SM_ALLOC = SM_TOTAL;

#define TL2 0
#define TLJ(i) TLREC(i)
#define TLW(i) do {} while (0)
#define TLVAL(i, v) do {} while (0)
__device__ __forceinline__ void mbar_init(uint32_t bar, uint32_t cnt) {
    asm volatile("mbarrier.init.shared::cta.b64 [%0], %1;" :: "r"(bar), "r"(cnt) : "memory");
}
__device__ __forceinline__ void mbar_expect_tx(uint32_t bar, uint32_t bytes) {
    asm volatile("mbarrier.arrive.expect_tx.shared::cta.b64 _, [%0], %1;" :: "r"(bar), "r"(bytes) : "memory");
}
__device__ __forceinline__ void mbar_arrive(uint32_t bar) {
    asm volatile("mbarrier.arrive.shared::cta.b64 _, [%0];" :: "r"(bar) : "memory");
}
__device__ __forceinline__ void mbar_arrive_cluster(uint32_t bar) {
    asm volatile("mbarrier.arrive.shared::cluster.b64 _, [%0];" :: "r"(bar) : "memory");
}
__device__ __forceinline__ void mbar_wait(uint32_t bar, uint32_t parity = 0) {
    asm volatile("{\n.reg .pred p;\n.reg .u32 c;\n"
                 "mbarrier.try_wait.parity.shared::cta.b64 p, [%0], %1;\n"
                 "@p bra WAIT_DONE;\n"
                 "mov.u32 c, 0;\n"
                 "WAIT_LOOP:\n"
                 "mbarrier.try_wait.parity.shared::cta.b64 p, [%0], %1;\n"
                 "@p bra WAIT_DONE;\n"
                 "add.u32 c, c, 1;\nsetp.lt.u32 p, c, 0x100000;\n"
                 "@p bra WAIT_LOOP;\n"
                 "trap;\n"
                 "WAIT_DONE:\n}" :: "r"(bar), "r"(parity) : "memory");
}
__device__ __forceinline__ void mbar_wait2(uint32_t bar0, uint32_t bar1) {
    asm volatile("{\n.reg .pred p, q;\n.reg .u32 c;\nmov.u32 c, 0;\n"
                 "WAIT_LOOP:\n"
                 "mbarrier.try_wait.parity.shared::cta.b64 p, [%0], 0;\n"
                 "mbarrier.try_wait.parity.shared::cta.b64 q, [%1], 0;\n"
                 "and.pred p, p, q;\n"
                 "@p bra WAIT_DONE;\n"
                 "add.u32 c, c, 1;\nsetp.lt.u32 p, c, 0x100000;\n"
                 "@p bra WAIT_LOOP;\n"
                 "trap;\n"
                 "WAIT_DONE:\n}" :: "r"(bar0), "r"(bar1) : "memory");
}
__device__ __forceinline__ bool mbar_test(uint32_t bar) {
    uint32_t ok;
    asm volatile("{\n.reg .pred p;\nmbarrier.test_wait.parity.shared::cta.b64 p, [%1], 0;\nselp.u32 %0, 1, 0, p;\n}" : "=r"(ok) : "r"(bar) : "memory");
    return ok;
}
__device__ __forceinline__ bool mbar_test2(uint32_t bar0, uint32_t bar1) {
    uint32_t ok;
    asm volatile("{\n.reg .pred p, q;\nmbarrier.test_wait.parity.shared::cta.b64 p, [%1], 0;\n"
                 "mbarrier.test_wait.parity.shared::cta.b64 q, [%2], 0;\nand.pred p, p, q;\nselp.u32 %0, 1, 0, p;\n}"
                 : "=r"(ok) : "r"(bar0), "r"(bar1) : "memory");
    return ok;
}
__device__ __forceinline__ bool elect_one() {
    uint32_t ok;
    asm volatile("{\n.reg .pred p;\nelect.sync _|p, 0xffffffff;\nselp.u32 %0, 1, 0, p;\n}" : "=r"(ok));
    return ok;
}
__device__ __forceinline__ unsigned ld_acquire(const unsigned* p) {
    unsigned v;
    asm volatile("ld.acquire.gpu.global.u32 %0, [%1];" : "=r"(v) : "l"(p) : "memory");
    return v;
}
__device__ __forceinline__ unsigned ld_flag(const unsigned* p) {
    unsigned v;
    asm volatile("ld.relaxed.gpu.global.u32 %0, [%1];" : "=r"(v) : "l"(p) : "memory");
    return v;
}
__device__ __forceinline__ uint4 lds128(uint32_t a) {
    uint4 v;
    asm volatile("ld.shared.v4.b32 {%0,%1,%2,%3}, [%4];" : "=r"(v.x), "=r"(v.y), "=r"(v.z), "=r"(v.w) : "r"(a) : "memory");
    return v;
}
__device__ __forceinline__ void sts128(uint32_t a, uint4 v) {
    asm volatile("st.shared.v4.b32 [%0], {%1,%2,%3,%4};" :: "r"(a), "r"(v.x), "r"(v.y), "r"(v.z), "r"(v.w) : "memory");
}
__device__ __forceinline__ uint32_t lds32(uint32_t a) {
    uint32_t v;
    asm volatile("ld.shared.b32 %0, [%1];" : "=r"(v) : "r"(a) : "memory");
    return v;
}
__device__ __forceinline__ void sts32(uint32_t a, uint32_t v) {
    asm volatile("st.shared.b32 [%0], %1;" :: "r"(a), "r"(v) : "memory");
}
__device__ __forceinline__ void stg128(void* p, uint4 v) {
    asm volatile("st.global.v4.b32 [%0], {%1,%2,%3,%4};" :: "l"(p), "r"(v.x), "r"(v.y), "r"(v.z), "r"(v.w) : "memory");
}
__device__ __forceinline__ unsigned pack4(unsigned a, unsigned b, unsigned c, unsigned d) {
    unsigned lo, r;
    asm("cvt.pack.sat.s8.s32.b32 %0, %1, %2, 0;" : "=r"(lo) : "r"(d), "r"(c));
    asm("cvt.pack.sat.s8.s32.b32 %0, %1, %2, %3;" : "=r"(r) : "r"(b), "r"(a), "r"(lo));
    return r;
}

constexpr uint32_t DESC_A_HI = 0x80000000u | (512 >> 4);
constexpr uint32_t DESC_B_HI = 512 >> 4;
template <int NR> __device__ __forceinline__ void wgmma_n160(int (&d)[NR], uint32_t alo, uint32_t blo, int scale_d) {
    asm volatile("{\n.reg .pred p;\n.reg .b64 da, db;\nsetp.ne.b32 p, %82, 0;\n"
        "mov.b64 da, {%80, %83};\nmov.b64 db, {%81, %84};\n"
        "wgmma.mma_async.sync.aligned.m64n160k32.s32.s8.s8 "
        "{%0, %1, %2, %3, %4, %5, %6, %7, %8, %9, %10, %11, %12, %13, %14, %15, "
        "%16, %17, %18, %19, %20, %21, %22, %23, %24, %25, %26, %27, %28, %29, %30, %31, "
        "%32, %33, %34, %35, %36, %37, %38, %39, %40, %41, %42, %43, %44, %45, %46, %47, "
        "%48, %49, %50, %51, %52, %53, %54, %55, %56, %57, %58, %59, %60, %61, %62, %63, "
        "%64, %65, %66, %67, %68, %69, %70, %71, %72, %73, %74, %75, %76, %77, %78, %79}, "
        "da, db, p;\n}\n"
        : "+r"(d[0]), "+r"(d[1]), "+r"(d[2]), "+r"(d[3]), "+r"(d[4]), "+r"(d[5]), "+r"(d[6]), "+r"(d[7]),
          "+r"(d[8]), "+r"(d[9]), "+r"(d[10]), "+r"(d[11]), "+r"(d[12]), "+r"(d[13]), "+r"(d[14]), "+r"(d[15]),
          "+r"(d[16]), "+r"(d[17]), "+r"(d[18]), "+r"(d[19]), "+r"(d[20]), "+r"(d[21]), "+r"(d[22]), "+r"(d[23]),
          "+r"(d[24]), "+r"(d[25]), "+r"(d[26]), "+r"(d[27]), "+r"(d[28]), "+r"(d[29]), "+r"(d[30]), "+r"(d[31]),
          "+r"(d[32]), "+r"(d[33]), "+r"(d[34]), "+r"(d[35]), "+r"(d[36]), "+r"(d[37]), "+r"(d[38]), "+r"(d[39]),
          "+r"(d[40]), "+r"(d[41]), "+r"(d[42]), "+r"(d[43]), "+r"(d[44]), "+r"(d[45]), "+r"(d[46]), "+r"(d[47]),
          "+r"(d[48]), "+r"(d[49]), "+r"(d[50]), "+r"(d[51]), "+r"(d[52]), "+r"(d[53]), "+r"(d[54]), "+r"(d[55]),
          "+r"(d[56]), "+r"(d[57]), "+r"(d[58]), "+r"(d[59]), "+r"(d[60]), "+r"(d[61]), "+r"(d[62]), "+r"(d[63]),
          "+r"(d[64]), "+r"(d[65]), "+r"(d[66]), "+r"(d[67]), "+r"(d[68]), "+r"(d[69]), "+r"(d[70]), "+r"(d[71]),
          "+r"(d[72]), "+r"(d[73]), "+r"(d[74]), "+r"(d[75]), "+r"(d[76]), "+r"(d[77]), "+r"(d[78]), "+r"(d[79])
        : "r"(alo), "r"(blo), "r"(scale_d), "r"(DESC_A_HI), "r"(DESC_B_HI));
}
template <int NR> __device__ __forceinline__ void wgmma_t128(int (&d)[NR], uint32_t alo, uint32_t blo, int scale_d) {
    asm volatile("{\n.reg .pred p;\n.reg .b64 da, db;\nsetp.ne.b32 p, %66, 0;\n"
        "mov.b64 da, {%64, %67};\nmov.b64 db, {%65, %68};\n"
        "wgmma.mma_async.sync.aligned.m64n128k32.s32.s8.s8 "
        "{%0, %1, %2, %3, %4, %5, %6, %7, %8, %9, %10, %11, %12, %13, %14, %15, "
        "%16, %17, %18, %19, %20, %21, %22, %23, %24, %25, %26, %27, %28, %29, %30, %31, "
        "%32, %33, %34, %35, %36, %37, %38, %39, %40, %41, %42, %43, %44, %45, %46, %47, "
        "%48, %49, %50, %51, %52, %53, %54, %55, %56, %57, %58, %59, %60, %61, %62, %63}, "
        "da, db, p;\n}\n"
        : "+r"(d[0]), "+r"(d[1]), "+r"(d[2]), "+r"(d[3]), "+r"(d[4]), "+r"(d[5]), "+r"(d[6]), "+r"(d[7]),
          "+r"(d[8]), "+r"(d[9]), "+r"(d[10]), "+r"(d[11]), "+r"(d[12]), "+r"(d[13]), "+r"(d[14]), "+r"(d[15]),
          "+r"(d[16]), "+r"(d[17]), "+r"(d[18]), "+r"(d[19]), "+r"(d[20]), "+r"(d[21]), "+r"(d[22]), "+r"(d[23]),
          "+r"(d[24]), "+r"(d[25]), "+r"(d[26]), "+r"(d[27]), "+r"(d[28]), "+r"(d[29]), "+r"(d[30]), "+r"(d[31]),
          "+r"(d[32]), "+r"(d[33]), "+r"(d[34]), "+r"(d[35]), "+r"(d[36]), "+r"(d[37]), "+r"(d[38]), "+r"(d[39]),
          "+r"(d[40]), "+r"(d[41]), "+r"(d[42]), "+r"(d[43]), "+r"(d[44]), "+r"(d[45]), "+r"(d[46]), "+r"(d[47]),
          "+r"(d[48]), "+r"(d[49]), "+r"(d[50]), "+r"(d[51]), "+r"(d[52]), "+r"(d[53]), "+r"(d[54]), "+r"(d[55]),
          "+r"(d[56]), "+r"(d[57]), "+r"(d[58]), "+r"(d[59]), "+r"(d[60]), "+r"(d[61]), "+r"(d[62]), "+r"(d[63])
        : "r"(alo), "r"(blo), "r"(scale_d), "r"(DESC_B_HI), "r"(DESC_A_HI));
}

__device__ __forceinline__ void wg_fence() { asm volatile("wgmma.fence.sync.aligned;" ::: "memory"); }
__device__ __forceinline__ void wg_commit() { asm volatile("wgmma.commit_group.sync.aligned;" ::: "memory"); }
template <int N> __device__ __forceinline__ void wg_wait() { asm volatile("wgmma.wait_group.sync.aligned %0;" :: "n"(N) : "memory"); }

__device__ __forceinline__ uint32_t mapa(uint32_t a, uint32_t r) {
    uint32_t o;
    asm("mapa.shared::cluster.u32 %0, %1, %2;" : "=r"(o) : "r"(a), "r"(r));
    return o;
}
__device__ __forceinline__ unsigned clk() {
    unsigned t;
    asm volatile("mov.u32 %0, %clock;" : "=r"(t));
    return t;
}
__host__ __device__ constexpr int unit_of(int piece, int slab) {
    return piece < 2 ? (slab < X1 ? 2 * slab + piece : (piece ? 16 : X1) + slab) : 32 + (piece - 2) * 8 + (slab >> 1);
}
__host__ __device__ constexpr int col_of(int G) { return G == 4 ? 256 : (G > 4 && G < 9) ? 32 * G - 32 : 32 * G; }
struct BJob { int u, slab, G, pos; };
__host__ __device__ constexpr BJob decode_b(int q) {
    BJob j = {};
    if (q < 160) {
        j.u = q / 5; j.pos = q - j.u * 5;
        const int piece = j.u < 2 * X1 ? (j.u & 1) : (j.u >= X1 + 16);
        j.slab = j.u < 2 * X1 ? (j.u >> 1) : j.u - (piece ? 16 : X1);
        j.G = piece * 5 + j.pos;
    } else {
        q -= 160;
        j.u = 32 + (q >> 2); j.pos = q & 3;
        j.slab = (q >> 1) & 15;
        j.G = 10 + (q >> 5) * 2 + (q & 1);
    }
    return j;
}
__host__ __device__ constexpr int fb_of(int u) {
    return u < 2 * X1 ? (u & 1) * 32 + (u >> 1) : u < X1 + 16 ? u - X1 : u < 32 ? 16 + u : u < 40 ? u - 16 : u < 48 ? u + 8 : u - 24;
}
template <bool k2> __device__ __forceinline__ int stage_w(int t) { return (k2 && t < 9) ? SM_A + (7 + t) * 8192 : SM_STG + (t % 3) * 8192; }
constexpr int RA = CFG_RA, RB64 = 64 * RA / (RA - 16);
constexpr int RA2 = CFG_RA2, RB642 = 64 * RA2 / (RA2 - 16), XA = CFG_XA, QA = (XA - L0) * (RA - 16) / 16;
__device__ __forceinline__ int time_x(int x) { return max(x, L0 + (((x - L0) * RA + max(x - XA, 0) * (RA2 - RA)) >> 4)); }
__device__ __forceinline__ int time_w(int q) { return min(L0 + ((q * RB64 + max(q - QA, 0) * (RB642 - RB64)) >> 6), NAJ / NCL + q); }
__device__ __forceinline__ int sched2(int x) { return (min(x, 160) - CFG_Q0) * CFG_Q2 + max(x - 160, 0) * CFG_Q3; }
__device__ __forceinline__ unsigned sched(int T) { return T * CFG_P2 + min(T, CFG_PT) * (CFG_P1 - CFG_P2) + max(T - CFG_PT3, 0) * (CFG_P3 - CFG_P2); }
__device__ __forceinline__ void raw_load(const void* map, int y, int z, uint32_t dst, uint32_t bar) {
    asm volatile("cp.async.bulk.tensor.3d.shared::cluster.global.tile.mbarrier::complete_tx::bytes [%0], [%1, {0, %2, %3}], [%4];"
                 :: "r"(dst), "l"(map), "r"(y), "r"(z), "r"(bar) : "memory");
}
__host__ __device__ constexpr uint64_t slot_table(int piece) {
    uint64_t t = 0;
    if (piece < 2) for (int s = 0; s < 16; s++) t |= (uint64_t)(unit_of(piece, s) % NSLOT) << (4 * s);
    else for (int s = 0; s < 8; s++) t |= (uint64_t)(unit_of(piece, 2 * s) % NSLOT) << (4 * s);
    return t;
}
constexpr int NA0 = CFG_NA0;
__host__ __device__ constexpr int ford(int g, int m) {
    return g ? (m < NA0 - 1 ? 2 + 2 * m : NA0 + m) : (m < 2 ? m : m < NA0 ? 2 * m - 1 : 5 + m);
}
__host__ __device__ constexpr uint64_t ford_table() {
    uint64_t t = 0;
    for (int g = 0; g < 2; g++) for (int m = 0; m < 5; m++) t |= (uint64_t)(g * 8 + m) << (4 * ford(g, m));
    return t;
}
struct Maps { CUtensorMap m[4]; };

__device__ __forceinline__ uint32_t bf2_op_epi(int a, int b, uint32_t zc, uint32_t sx, uint32_t sw, uint32_t bi) {
    uint32_t v;
    if (DBG & 1) return a ^ b ^ zc;
    float fa = __int2float_rn(a), fb = __int2float_rn(b);
    asm("cvt.rn.bf16x2.f32 %0, %1, %2;" : "=r"(v) : "f"(fb), "f"(fa));
    asm("sub.rn.bf16x2 %0, %0, %1;" : "+r"(v) : "r"(zc));
    if (CFG_EPI < 2) asm("mul.rn.bf16x2 %0, %0, %1;" : "+r"(v) : "r"(sx));
    if (CFG_EPI == 0) {
        asm("mul.rn.bf16x2 %0, %0, %1;" : "+r"(v) : "r"(sw));
        asm("add.rn.bf16x2 %0, %0, %1;" : "+r"(v) : "r"(bi));
    } else {
        asm("fma.rn.bf16x2 %0, %0, %1, %2;" : "+r"(v) : "r"(sw), "r"(bi));
    }
    return v;
}
struct Par { uint4 zc, sw, bi; };
__device__ __forceinline__ Par ld_par(uint32_t p) { return {lds128(p), lds128(p + TN * 2), lds128(p + TN * 4)}; }
__device__ __forceinline__ uint4 epi_row(const int (&a)[WA / 2], int o, const Par& p, uint32_t sx2) {
    uint4 r;
    r.x = bf2_op_epi(a[o + 0], a[o + 4], p.zc.x, sx2, p.sw.x, p.bi.x);
    r.y = bf2_op_epi(a[o + 8], a[o + 12], p.zc.y, sx2, p.sw.y, p.bi.y);
    r.z = bf2_op_epi(a[o + 1], a[o + 5], p.zc.z, sx2, p.sw.z, p.bi.z);
    r.w = bf2_op_epi(a[o + 9], a[o + 13], p.zc.w, sx2, p.sw.w, p.bi.w);
    return r;
}
__device__ __forceinline__ void release(uint32_t go, int u, int lane, bool k2) {
    const int v = u + NSLOT;
    if (CFG_R8 && !k2) {
        const int q = 5 * v - (v > 34 ? 3 : 0) + lane;
        if (lane < (v > 38 ? 0 : v == 34 ? 2 : 5)) mbar_arrive_cluster(mapa(go + (q >> 4) * 8, q & 15));
        return;
    }
    const int n = k2 ? 1 : v < 32 ? 5 : 4, sh = k2 ? 1 : 4;
    const int q = n * v + (n == 4 ? 32 : 0) + lane;
    if (lane < (v < NU1 ? n : 0)) mbar_arrive_cluster(mapa(go + (q >> sh) * 8, q & ((1 << sh) - 1)));
}

#define READ_BACK asm volatile("ld.relaxed.gpu.global.u32 %0, [%1];" : "=r"(rb) : "l"(d - lane + ((lane + 10) & 15) * 8 + 6) : "memory");
#define CV_B(m, f)                                                                                    \
                    {                                                                                 \
                        uint4 v0 = lds128(rdB + m * 512), v1 = lds128(rdB + m * 512 + 128);           \
                        uint4 v2 = lds128(rdB + m * 512 + 256), v3 = lds128(rdB + m * 512 + 384);     \
                        o[0].f = pack4(v0.x, v1.x, v2.x, v3.x); o[1].f = pack4(v0.y, v1.y, v2.y, v3.y); \
                        o[2].f = pack4(v0.z, v1.z, v2.z, v3.z); o[3].f = pack4(v0.w, v1.w, v2.w, v3.w); \
                    }

__device__ __forceinline__ void last_columns(const Maps& maps, const __nv_bfloat16* scale_x, const int* zero_x, const __nv_bfloat16* scale_w,
                                             const __nv_bfloat16* bias, uint32_t sb, int warp, int lane, unsigned t0) {
    constexpr int C_FULL = 0, C_EMPTY = 32, C_RAW = 64, C_GO = 80, C_PEER = 81;
    const uint32_t bars = sb + SM_BAR;
    const int j = (blockIdx.x & 1) + ((blockIdx.x >> 1) == CFG_KB ? 2 : 0);
    if (CFG_T3) while ((int)(t0 + CFG_T3 - clk()) > 0) ;
    const int s0 = (j & 1) * 8 + (warp >> 1) * 2;
    if (warp < 8) {
        if (elect_one()) {
#pragma unroll
            for (int i = 0; i < 2; i++) {
                const uint32_t bar = bars + (C_RAW + warp * 2 + i) * 8;
                mbar_init(bar, 1); mbar_expect_tx(bar, 8192);
                raw_load(maps.m + 1, (s0 + (i ^ (j >> 1))) * 64, N_ / 32 - 2 + (warp & 1), sb + SM_A + (warp * 2 + i) * 8192, bar);
            }
#pragma unroll
            for (int i = 0; i < 4; i++) { mbar_init(bars + (C_FULL + warp * 4 + i) * 8, 1); mbar_expect_tx(bars + (C_FULL + warp * 4 + i) * 8, 16384); }
#pragma unroll
            for (int i = 0; i < 4; i++) mbar_init(bars + (C_EMPTY + warp * 4 + i) * 8, 4);
            if (warp == 0) {
                mbar_init(bars + C_GO * 8, 8);
                mbar_init(bars + C_PEER * 8, 1); mbar_expect_tx(bars + C_PEER * 8, 32768 + 4096);
            }
        }
        if (warp < 2) sts32(sb + SM_PAR + threadIdx.x * 4, 0);
        asm volatile("fence.mbarrier_init.release.cluster;" ::: "memory");
    }
    __syncthreads();
    asm volatile("barrier.cluster.arrive.relaxed.aligned;" ::: "memory");
    asm volatile("barrier.cluster.wait.aligned;" ::: "memory");
    if (warp >= 8) {
        asm volatile("setmaxnreg.dec.sync.aligned.u32 40;");
        if (warp < 12) {
            const unsigned ep = (*(volatile unsigned*)&g_epoch[128 + j] + 1) * 4;
            const int mb = j * 4 + warp - 8, wg = (warp >> 1) & 1;
            unsigned rdy = 0;
            mbar_wait(bars + C_GO * 8);
            if (CFG_ST3 && wg) mbar_wait(bars + (C_EMPTY + (CFG_ST3 - 1) * 2) * 8);
#pragma unroll 1
            for (int s = 0; s < 16; s++) {
                for (int it = 0; !((rdy >> s) & 1); it++) {
                    rdy = __ballot_sync(~0u, (int)(ld_flag(g_flag + mb * 32 + (lane & 15)) - ep) >= 0);
                    if (it > (1 << 22)) __trap();
                }
                if (s >= CFG_D3) mbar_wait(bars + (C_EMPTY + (s - CFG_D3) * 2 + wg) * 8);
                if (elect_one())
                    asm volatile("cp.async.bulk.shared::cluster.global.mbarrier::complete_tx::bytes [%0], [%1], %2, [%3];"
                                 :: "r"(sb + SM_A + ((s & 3) * 4 + warp - 8) * 8192), "l"((const char*)g_s8 + (mb * 16 + s) * 8192),
                                    "r"(8192), "r"(bars + (C_FULL + s * 2 + wg) * 8) : "memory");
            }
        }
    } else {
        asm volatile("setmaxnreg.inc.sync.aligned.u32 200;");
        const int wg = warp >> 2, w = warp & 3;
        const int c0 = (w >> 1) * 32 + (lane >> 2) * 4 + (w & 1) * 2, r0 = (lane & 3) * 2;
        const uint32_t sx2 = (uint32_t)__ldg((const unsigned short*)scale_x) * 0x10001u;
        uint32_t sw = __ldg((const unsigned*)(scale_w + N_ - WB + c0));
        const uint32_t bi = __ldg((const unsigned*)(bias + N_ - WB + c0));
        const float zxf = __bfloat162float(__float2bfloat16_rn((float)__ldg(zero_x)));
        int cs[4] = {0, 0, 0, 0};
        const uint32_t peer = mapa(sb, (j & 1) ^ 1);
#pragma unroll 1
        for (int i = 0; i < 2; i++) {
            const uint32_t rdB = sb + SM_A + (warp * 2 + i) * 8192 + (lane >> 3) * 2048 + (lane & 7) * 16;
            const uint32_t wr = SM_RING + (s0 + (i ^ (j >> 1))) * 4096 + (warp & 1) * 2048 + lane * 16;
            mbar_wait(bars + (C_RAW + warp * 2 + i) * 8);
            uint4 o[4];
            CV_B(0, x) CV_B(1, y) CV_B(2, z) CV_B(3, w)
#pragma unroll
            for (int k = 0; k < 4; k++) {
                sts128(sb + wr + k * 512, o[k]);
                asm volatile("st.async.weak.shared::cluster.mbarrier::complete_tx::bytes.v4.b32 [%0], {%1,%2,%3,%4}, [%5];"
                             :: "r"(peer + wr + k * 512), "r"(o[k].x), "r"(o[k].y), "r"(o[k].z), "r"(o[k].w), "r"(peer + SM_BAR + C_PEER * 8) : "memory");
                cs[k] = __dp4a((int)o[k].x, 0x01010101, __dp4a((int)o[k].y, 0x01010101,
                        __dp4a((int)o[k].z, 0x01010101, __dp4a((int)o[k].w, 0x01010101, cs[k]))));
            }
        }
        __syncwarp();
        if (elect_one()) mbar_arrive(bars + C_GO * 8);
#pragma unroll
        for (int k = 0; k < 4; k++) {
            const uint32_t ca = SM_PAR + ((warp & 1) * 32 + (lane & 7) * 4 + k) * 4;
            asm volatile("red.shared.add.s32 [%0], %1;" :: "r"(sb + ca), "r"(cs[k]) : "memory");
            asm volatile("red.async.relaxed.cluster.shared::cluster.mbarrier::complete_tx::bytes.add.s32 [%0], %1, [%2];"
                         :: "r"(peer + ca), "r"(cs[k]), "r"(peer + SM_BAR + C_PEER * 8) : "memory");
        }
        mbar_wait(bars + C_PEER * 8);
        asm volatile("fence.proxy.async.shared::cta;" ::: "memory");
        asm volatile("bar.sync 1, 256;" ::: "memory");
        if (CFG_EPI == 2) asm("mul.rn.bf16x2 %0, %0, %1;" : "+r"(sw) : "r"(sx2));
        if (threadIdx.x == 0) TLE_REC(128 + j, 4);
        uint32_t zc;
        asm("cvt.rn.bf16x2.f32 %0, %1, %2;" : "=r"(zc) : "f"(__bfloat162float(__float2bfloat16_rn((float)(int)lds32(sb + SM_PAR + c0 * 4 + 4))) * zxf),
                                                         "f"(__bfloat162float(__float2bfloat16_rn((float)(int)lds32(sb + SM_PAR + c0 * 4))) * zxf));
        const uint32_t sd = (sb & 0x3FFFF) >> 4;
        int t[2][64];
        wg_fence();
#pragma unroll 1
        for (int s = 0; s < 16; s++) {
            const uint32_t db = ((sd + (SM_RING >> 4)) | (8 << 16)) + s * 256, da = ((sd + (SM_A >> 4)) | (1 << 16)) + ((s & 3) * 4 + wg * 2) * 512;
            mbar_wait(bars + (C_FULL + s * 2 + wg) * 8);
            wgmma_t128(t[0], db, da, s);
            wgmma_t128(t[1], db, da + 512, s);
            wgmma_t128(t[0], db + 16, da + 2, 1);
            wgmma_t128(t[1], db + 16, da + 514, 1);
            wg_commit();
            wg_wait<0>();
            if (elect_one()) mbar_arrive(bars + (C_EMPTY + s * 2 + wg) * 8);
        }
        asm volatile("bar.sync %0, 128;" :: "r"(3 + wg) : "memory");
        if (threadIdx.x == 0) TLE_REC(128 + j, 5);
        const uint32_t st0 = sb + SM_A + wg * 16384 + r0 * 128 + (((c0 >> 3) ^ r0) << 4) + (c0 & 7) * 2;
#pragma unroll
        for (int h = 0; h < 4; h++) {
            const uint32_t off = (h >> 1) * 32768 + (h & 1) * 8192;
#pragma unroll
            for (int q = 0; q < 8; q++) {
                const int o = (h & 1) * 32 + q * 4;
                sts32(st0 + off + q * 1024, bf2_op_epi(t[h >> 1][o], t[h >> 1][o + 2], zc, sx2, sw, bi));
                sts32((st0 ^ (5 * 128 + 5 * 16)) + off + q * 1024, bf2_op_epi(t[h >> 1][o + 1], t[h >> 1][o + 3], zc, sx2, sw, bi));
            }
            asm volatile("fence.proxy.async.shared::cta;" ::: "memory");
            asm volatile("bar.sync %0, 128;" :: "r"(3 + wg) : "memory");
            if (w == 0 && elect_one())
                asm volatile("cp.async.bulk.tensor.2d.global.shared::cta.tile.bulk_group [%0, {%1, %2}], [%3];"
                             :: "l"(maps.m + 2), "r"(N_ - WB), "r"(j * 512 + wg * 256 + h * 64), "r"(sb + SM_A + wg * 16384 + off) : "memory");
        }
        if (w == 0) {
            asm volatile("cp.async.bulk.commit_group;" ::: "memory");
            asm volatile("cp.async.bulk.wait_group.read 0;" ::: "memory");
        }
        asm volatile("bar.sync 1, 256;" ::: "memory");
        if (threadIdx.x == 0) asm volatile("red.relaxed.gpu.global.add.u32 [%0], 1;" :: "l"(g_epoch + 128 + j) : "memory");
        if (threadIdx.x == 0) TLE_REC(128 + j, 1);
    }
}

template <bool k2>
__global__ void CLUSTER_ATTR __launch_bounds__(512, 1)
w8a8_kernel(
            const char* __restrict__ qx, const char* __restrict__ qw, const __nv_bfloat16* __restrict__ scale_x, const int* __restrict__ zero_x,
            const __nv_bfloat16* __restrict__ scale_w, const __nv_bfloat16* __restrict__ bias
            , const __grid_constant__ Maps maps
            ) {
    extern __shared__ __align__(1024) unsigned char smem_raw[];
    if (!k2 && !CFG_LC) asm volatile("griddepcontrol.launch_dependents;");
    constexpr int NBJ = k2 ? 12 : 14, NF = NBJ, NU = k2 ? 40 : NU1;
    const int b = blockIdx.x + (k2 ? NCTA - ((blockIdx.x >> 1) > CFG_KA ? 2 : 0) - ((blockIdx.x >> 1) > CFG_KB ? 2 : 0) : 0), r = b & 15, c = k2 ? NCL : b >> 4;
    const unsigned tc = clk();
    if (threadIdx.x < CFG_PF * 64 && !k2) {
        const int a = (threadIdx.x >> 6) * NCTA + r * NCL + c;
        asm volatile("prefetch.global.L2 [%0];" :: "l"(qx + ((a & 63) * 32 + ((threadIdx.x >> 1) & 31)) * (K_ * 4) + (a >> 6) * 256 + (threadIdx.x & 1) * 128));
    }
    const uint32_t sb = (uint32_t)__cvta_generic_to_shared(smem_raw);
    const uint32_t bars = sb + SM_BAR;
    const unsigned tw = __shfl_sync(~0u, (tc & ~15u) | threadIdx.x >> 5, 0), t0 = tw + (k2 ? 0 : CFG_T0);
    const int warp = tw & 15, lane = threadIdx.x & 31;

    if (CFG_FAST0 && !k2 && warp == 12) {
        const int a = r * NCL + c;
        if (elect_one()) {
            mbar_init(bars + (B_RAWA + 3) * 8, 1);
            mbar_expect_tx(bars + (B_RAWA + 3) * 8, 8192);
            if (CFG_PA0) while ((int)(t0 + r * CFG_PA0 - clk()) > 0) ;
            raw_load(maps.m, (a >> 6) * 2, ((a ^ CFG_REV) & 63) * 32, sb + SM_A + (a < NAJ % NCTA ? 15 : 13) * 8192, bars + (B_RAWA + 3) * 8);
        }
        __syncwarp();
    }
    if (CFG_ETM && warp >= 8 + (CFG_FAST0 && CFG_PA0 == 0) && warp < 10 && elect_one()) asm volatile("prefetch.tensormap [%0];" :: "l"(maps.m + (warp & 1)) : "memory");
    if (k2 && ((blockIdx.x >> 1) == CFG_KA || (blockIdx.x >> 1) == CFG_KB)) {
        if (!(DBG & 64)) last_columns(maps, scale_x, zero_x, scale_w, bias, sb, warp, lane, t0);
        return;
    }
    if (warp >= 12) {
        asm volatile("barrier.cluster.arrive.relaxed.aligned;" ::: "memory");
        if (warp == 12 && lane == 0) TLREC(0);
        const int t = k2 ? warp - 12 : warp & 1, isw = k2 || warp >= 14;
        const int x = t * 16 + r, a = (x * NCL + c) ^ CFG_REV, sx = (x * 26) >> 8;
        static_assert(X1 >= 7, "");
        const uint32_t bar = bars + ((isw ? B_RAWB : B_RAWA) + 3 + t) * 8;
        if (!(CFG_FAST0 && !k2 && warp == 12) && elect_one()) {
            mbar_init(bar, 1);
            mbar_expect_tx(bar, 8192);
            const unsigned te = t0 + (k2 ? sched2(x) : (isw ? time_w(x) : time_x(x)) * CFG_P1);
            while ((int)(te - clk()) > 0) ;
            raw_load(maps.m + isw, isw ? sx * 64 : (a >> 6) * 2,
                     isw ? c * (TN / 32) + (int)((0x9765483210ull >> ((x - sx * 10) * 4)) & 15) : (a & 63) * 32,
                     sb + (k2 ? SM_A + 7 * 8192 : isw ? SM_STG : SM_A + 13 * 8192) + ((isw || r * NCL + c >= NAJ % NCTA) ? t : 2 - 2 * t) * 8192, bar);
            TLJ(224 + isw * 10 + t);
        }
        __syncwarp();
    }
    if (warp < 8) {
        const uint32_t p = bars + warp * 104;
        if (elect_one()) {
#pragma unroll
            for (int i = 0; i < 13; i++) mbar_init(p + i * 8, 1);
        }
        __syncwarp();
        const int i = warp * 13 + lane;
        if (lane < 13 && i < B_SW) mbar_expect_tx(p + lane * 8, i >= B_PAR ? (i < B_PAR + 2 ? WA * 2 : WB * 2) : (i & 16) || i >= 48 ? 8192 : WA * 64);
        asm volatile("fence.mbarrier_init.release.cluster;" ::: "memory");
    }
    if (warp < 8 || warp == 10) asm volatile("barrier.cluster.arrive.relaxed.aligned;" ::: "memory");
    if (CFG_PF7 && !k2 && warp == 10 && lane < CFG_PF7) {
        const int n = b * CFG_PF7 + lane, row = n / 10;
        asm volatile("prefetch.global.L2 [%0];" :: "l"(qw + row * (N_ * 4) + NCL * TN * 4 + (n - row * 10) * 128));
    }

    if (warp < 8) {
        if (warp < 2 && elect_one()) asm volatile("prefetch.tensormap [%0];" :: "l"(maps.m + 2 + warp) : "memory");
        asm volatile("setmaxnreg.inc.sync.aligned.u32 " STR(CFG_CREG) ";");
        const int wg = warp >> 2;
        const uint32_t sd = (sb & 0x3FFFF) >> 4;
        const unsigned short sxr = __ldg((const unsigned short*)scale_x);
        const uint32_t sx2 = (uint32_t)sxr * 0x10001u;
        const uint32_t par = sb + SM_PAR + (lane & 3) * 16 + wg * 256;
        const uint32_t go = bars + B_GO * 8;
        const int w = warp & 3, pq = (lane >> 2) ^ (lane & 4);
        uint32_t so = (w * 16 + pq) * 128 + (((lane & 3) ^ pq) << 4);
        const int c0 = (w >> 1) * 32 + (lane >> 2) * 4 + (w & 1) * 2, r0 = (lane & 3) * 2;
        uint32_t pp = sb + SM_PAR + (2 * WA + wg * WB + c0) * 2, st0 = r0 * 128 + (((c0 >> 3) ^ r0) << 4) + (c0 & 7) * 2;
        int rq = lane < (k2 ? 1 : 4) ? (k2 ? 1 : 4) * (32 + wg * 8 + ((CFG_R8 && !k2) ? 8 : NSLOT)) + (k2 ? 0 : 32) + lane : 1000;
        asm volatile("" : "+r"(so), "+r"(pp), "+r"(st0), "+r"(rq));
        asm volatile("barrier.cluster.wait.aligned;" ::: "memory");
        if (threadIdx.x == 0) { TLREC(250); TLCLK(251); }
        int a0[WA / 2], a1[WA / 2];
        uint32_t barB = bars + (B_FULLB + wg * 32) * 8;
        wg_fence();
        {
            uint64_t tbl = wg ? slot_table(1) : slot_table(0);
            uint32_t da = (sd + (SM_A >> 4)) | (1 << 16);
            int up = 99;
            bool rdy = false;
#pragma unroll 1
            for (int s = 0; s < 16; s++) {
                const uint32_t db = ((sd + (SM_RING >> 4)) | (8 << 16)) + ((uint32_t)tbl & 15) * (SLOT >> 4);
                const bool hold = CFG_HOLD && (CFG_H2 || !k2) && wg && s == CFG_HS;
                if (hold || (!rdy && !mbar_test2(bars + (B_FULLA + s) * 8, barB))) {
                    wg_wait<0>();
                    release(go, up, lane, k2); up = 99;
                    mbar_wait2(bars + (B_FULLA + s) * 8, barB);
                    if (threadIdx.x % 128 == 0) TLW(160 + wg * 16 + s);
                    if (hold) asm volatile("bar.sync 7, 256;" ::: "memory");
                }
                wgmma_n160(a0, da, db, s);
                wgmma_n160(a1, da + 256, db, s);
                wg_commit();
                if (CFG_HOLD && (CFG_H2 || !k2) && !wg && s == CFG_HOLD) asm volatile("bar.arrive 7, 256;" ::: "memory");
                wg_wait<1>();
                release(go, up, lane, k2);
                wgmma_n160(a0, da + 2, db + 16, 1);
                wgmma_n160(a1, da + 258, db + 16, 1);
                wg_commit();
                if (threadIdx.x % 128 == 0) TLREC(256 + wg * 32 + s);
                up = s < X1 ? 2 * s + wg : (wg ? 16 : X1) + s;
                tbl >>= 4; da += 512; barB += 8;
                if (CFG_RDY) rdy = mbar_test2(bars + (B_FULLA + s + 1) * 8, barB);
                if (s < 15) wg_wait<1>();
            }
        }
        mbar_wait2(bars + (B_PAR + wg) * 8, bars + B_SW * 8);
        Par P = ld_par(par);
        wg_wait<0>();
        release(go, wg ? 31 : X1 + 15, lane, k2);
        if (threadIdx.x % 128 == 0) { TLREC(1 + wg); TLE_REC(b, 4 + wg); }
        bool ready = mbar_test(barB);
#define FILL_BEGIN(n0, n1) mbar_wait(bars + (B_FREE + (wg ? n1 : n0)) * 8);                                              \
                           const uint32_t buf = sb + SM_STG + (wg ? (n1 + NBJ) % 3 : (n0 + NBJ) % 3) * 8192;
#define FILL_END(n0, n1) __syncwarp(); if (elect_one()) mbar_arrive(bars + (B_FILL + (wg ? n1 % 3 : n0 % 3)) * 8);        \
                         if (threadIdx.x % 128 == 0) TLREC(16 + (wg ? n1 : n0));
#define FILL_PAIR(a, J, PN, n0, n1)                                                                                     \
        {                                                                                                               \
            const uint4 v0 = epi_row(a, J * 16, P, sx2);                                                                \
            const Par Q = ld_par(par + J * 64 + 64);                                                                    \
            const uint4 v1 = epi_row(a, J * 16 + 2, P, sx2);                                                            \
            if (CFG_EARLY == 2 && (n0) == ford(0, NA0)) { wg_wait<0>(); if (wg == 0) RELEASE_N() }                      \
            FILL_BEGIN(n0, n1)                                                                                          \
            sts128(buf + so, v0); sts128(buf + so + 1024, v1);                                                          \
            if ((PN) >= 0) P = ld_par(par + (PN));                                                                      \
            sts128(buf + (so ^ 64), epi_row(a, J * 16 + 16, Q, sx2));                                                   \
            sts128(buf + (so ^ 64) + 1024, epi_row(a, J * 16 + 18, Q, sx2));                                            \
            FILL_END(n0, n1)                                                                                            \
        }
        constexpr int rn = k2 ? 1 : 4;
#define RELEASE_N() { if (rq < (k2 ? NU : NBJ * 16)) mbar_arrive_cluster(mapa(go + (rq >> rn) * 8, rq & ((1 << rn) - 1))); rq += rn; nrel++; }
#define NARROW(p)                                                                                                       \
        {                                                                                                               \
            uint32_t tbl = (uint32_t)slot_table(p), da = (sd + (SM_A >> 4)) | (1 << 16);                                \
            wg_fence();                                                                                                 \
            _Pragma("unroll 1") for (int i = 0; i < 8; i++) {                                                           \
                const uint32_t db = ((sd + (SM_RING >> 4)) | (8 << 16)) + ((CFG_R8 && !k2) ? ((i + 5) & 7) * 512 : (tbl & 15) * (SLOT >> 4)); \
                if (!ready && !mbar_test(barB)) {                                                                       \
                    wg_wait<0>();                                                                                       \
                    if (p == 2 || !CFG_R8) { _Pragma("unroll 1") while (nrel < i) RELEASE_N() }                         \
                    mbar_wait(barB);                                                                                    \
                }                                                                                                       \
                _Pragma("unroll") for (int kk = 0; kk < 4; kk++)                                                        \
                    wgmma_t128(t, db + (kk >> 1) * 256 + (kk & 1) * 16, da + (kk >> 1) * 512 + (kk & 1) * 2, kk ? 1 : i); \
                wg_commit();                                                                                            \
                if (threadIdx.x % 128 == 0) TLREC(256 + (p == 2 ? 16 : 48) + i);                                        \
                barB += 8;                                                                                              \
                ready = mbar_test(barB);                                                                                \
                if ((p == 2 || !CFG_R8) && nrel < i - CFG_QD) RELEASE_N()                                               \
                tbl >>= 4; da += 1024;                                                                                  \
                wg_wait<CFG_QD>();                                                                                      \
            }                                                                                                           \
            if (p == 2) { if (nrel < 8 - CFG_QD) RELEASE_N() if (NA0 < 5) P = ld_par(par + pn); }                       \
            else { zc = lds32(pp); sw = lds32(pp + TN * 2); bi = lds32(pp + TN * 4); }                                  \
            if (p == 3 || !CFG_EARLY) wg_wait<0>();                                                                     \
            if (p == 2 && !CFG_EARLY) RELEASE_N()                                                                       \
            if (threadIdx.x % 128 == 0) TLREC(3 + p);                                                                   \
        }
#define FO(m) ford(0, m), ford(1, m)
#define FILL_PAIR2(...) FILL_PAIR(__VA_ARGS__)
#define NARROW_AT(k, PN) if (NA0 == k) { pn = PN; if (wg == 0) NARROW(2) else if (k < 5) P = ld_par(par + pn); }   \
                         if (CFG_EARLY == 1 && NA0 == k - 1) { wg_wait<0>(); if (wg == 0) RELEASE_N() }
        int nrel = 0, pn = 0;
        static_assert(CFG_EARLY != 2 || NA0 < 4, "");
        FILL_PAIR2(a0, 0, 128, FO(0)) FILL_PAIR2(a0, 2, NA0 == 2 ? -1 : 0, FO(1))
        int t[64];
        uint32_t zc, sw, bi;
        NARROW_AT(2, 0)
        FILL_PAIR2(a1, 0, NA0 == 3 ? -1 : 128, FO(2))
        NARROW_AT(3, 128)
        FILL_PAIR2(a1, 2, NA0 == 4 ? -1 : 512 - wg * 192, FO(3))
        NARROW_AT(4, 512 - wg * 192)
        {
            const uint4 v0 = epi_row(a0, 64, P, sx2), v1 = epi_row(a0, 66, P, sx2);
            if (!(k2 && wg) && NA0 < 5) mbar_wait(bars + (B_PAR + 2 + wg) * 8);
            FILL_BEGIN(ford(0, 4), ford(1, 4))
            const uint32_t s4 = buf + ((so >> 1) & ~63u) + (lane & 3) * 16;
            sts128(s4, v0); sts128(s4 + 512, v1);
            sts128(s4 + 4096, epi_row(a1, 64, P, sx2)); sts128(s4 + 4608, epi_row(a1, 66, P, sx2));
            FILL_END(ford(0, 4), ford(1, 4))
        }
        NARROW_AT(5, 0)
        if (!(k2 && wg) && NA0 == 5) mbar_wait(bars + (B_PAR + 2 + wg) * 8);
        NARROW_AT(6, 0)
        if (!(k2 && wg)) {
        if (!k2 && wg == 1) NARROW(3) else { zc = lds32(pp); sw = lds32(pp + TN * 2); bi = lds32(pp + TN * 4); }
#define FILL_T(h)                                                                                                       \
        {                                                                                                               \
            FILL_BEGIN((10 + h), (12 + h))                                                                              \
            _Pragma("unroll") for (int j = 0; j < 8; j++) {                                                             \
                const int o = h * 32 + j * 4;                                                                           \
                sts32(buf + st0 + j * 1024, bf2_op_epi(t[o], t[o + 2], zc, sx2, sw, bi));                               \
                sts32(buf + (st0 ^ (5 * 128 + 5 * 16)) + j * 1024, bf2_op_epi(t[o + 1], t[o + 3], zc, sx2, sw, bi));    \
            }                                                                                                           \
            FILL_END((10 + h), (12 + h))                                                                                \
        }
        FILL_T(0) FILL_T(1)
        }
        if (DBG & 4) for (int i = 0; i < 56; i++) mbar_wait(bars + i * 8);
        if (threadIdx.x == 0) { TLREC(252); TLCLK(253); }
        TLEND();
        if (threadIdx.x == 128) asm volatile("red.relaxed.gpu.global.add.u32 [%0], 1;" :: "l"(g_epoch + b) : "memory");
    } else {
        const int g = r * NCL + c, na = k2 ? 0 : NAJ / NCTA + (g < NAJ % NCTA);
        int cw = NF;
        if (warp >= 12) {
            asm volatile("setmaxnreg.dec.sync.aligned.u32 " STR(CFG_RC) ";");
            if (warp < 14) {
                const int c4 = (lane ^ (lane >> 3)) & 3, ln = ((lane >> 2) ^ (lane & 4)) * 2 + (c4 >> 1);
                const uint32_t rd0 = sb + SM_A + 13 * 8192 + ln * 128 + ((((c4 & 1) << 2) ^ (ln & 7)) << 4);
#pragma unroll 1
                for (int t = warp - 12, sl = na == 9 ? t : 2 - 2 * t; t < na; t += 2, sl = sl ? sl - 1 : 2) {
                    const uint32_t rdA = rd0 + sl * 8192;
                    const int a = (t * NCTA + g) ^ CFG_REV, f = (a & 60) * 4 + (a >> 6);
                    uint4* const d = g_s8 + (f * 4 + (a & 3)) * 128 + lane;
                    uint4 o[4];
                    mbar_wait(bars + (B_RAWA + 3 + t) * 8);
                    if (lane == 0) TLJ(128 + t);
#pragma unroll
                    for (int i = 0; i < 4; i++) {
                        uint4 v0 = lds128(rdA + i * 2048), v1 = lds128((rdA ^ 16) + i * 2048);
                        uint4 v2 = lds128((rdA ^ 32) + i * 2048), v3 = lds128((rdA ^ 48) + i * 2048);
                        o[i].x = pack4(v0.x, v0.y, v0.z, v0.w); o[i].y = pack4(v1.x, v1.y, v1.z, v1.w);
                        o[i].z = pack4(v2.x, v2.y, v2.z, v2.w); o[i].w = pack4(v3.x, v3.y, v3.z, v3.w);
                    }
#pragma unroll
                    for (int i = 0; i < 4; i++) stg128(d + i * 32, o[i]);
                    unsigned rb;
                    if (CFG_WF) asm volatile("fence.proxy.async.global;" ::: "memory");
                    __syncwarp();
                    READ_BACK
                    if (t < 2) asm volatile("barrier.cluster.wait.aligned;" ::: "memory");
                    if (elect_one()) mbar_arrive(bars + ((t < na - 3 ? B_RAWA : B_AFREE + 13) + sl) * 8);
                    if (lane == 0) TLJ(160 + t);
                    if (__shfl_sync(~0u, rb ^ o[0].x, CFG_RB16 ? 6 : 0)) asm volatile("fence.acq_rel.gpu;" ::: "memory");
                    if (elect_one()) asm volatile("red.relaxed.gpu.global.add.u32 [%0], 1;" :: "l"(g_flag + (a & 60) * 8 + (a >> 6)) : "memory");
                    if (lane == 0) TLJ(192 + t);
                }
                cw = warp - 12;
            }
            {
                const uint32_t rd0 = sb + (lane >> 3) * 2048 + (lane & 7) * 16;
                const BJob mb = decode_b((lane & 15) * 16 + r);
                const int myG = mb.G | mb.u << 8;
#pragma unroll 1
                for (int t = k2 ? warp - 12 : warp < 14 ? CFG_TB + warp - 10 : warp - 14; t < NBJ; t += (!k2 && t < CFG_TB) ? 2 : 4) {
                    const uint32_t rdB = rd0 + stage_w<k2>(t);
                    uint4* const d = g_s8 + (1024 + c * 256 + t * 16 + r) * 128 + lane;
                    uint4 o[4];
                    mbar_wait(bars + (B_RAWB + 3 + t) * 8);
                    if (lane == 0) TLJ(138 + t);
                    CV_B(0, x) CV_B(1, y) CV_B(2, z) CV_B(3, w)
#pragma unroll
                    for (int i = 0; i < 4; i++) stg128(d + i * 32, o[i]);
                    if (t < (k2 ? 4 : 2)) asm volatile("barrier.cluster.wait.aligned;" ::: "memory");
                    if (elect_one()) mbar_arrive(bars + ((k2 || t >= NBJ - 3) ? B_FREE + t - (NBJ - 3) : B_RAWB + t % 3) * 8);
                    asm volatile("fence.proxy.async.global;" ::: "memory");
                    __syncwarp();
                    unsigned rb = 0, ep = 0;
                    if (k2) {
                        READ_BACK
                        ep = ld_flag(g_epoch + b);
                    } else if (elect_one()) mbar_arrive(bars + (B_GO + t) * 8);
                    if (lane == 0) TLREC((TL2 ? 234 : 170) + t);
                    int cs[4];
#pragma unroll
                    for (int i = 0; i < 4; i++)
                        cs[i] = __dp4a((int)o[i].x, 0x01010101, __dp4a((int)o[i].y, 0x01010101,
                                __dp4a((int)o[i].z, 0x01010101, __dp4a((int)o[i].w, 0x01010101, 0))));
                    const bool h = lane & 16, odd = lane & 8;
                    int x = (h ? cs[2] : cs[0]) + __shfl_xor_sync(~0u, h ? cs[0] : cs[2], 16);
                    int y = (h ? cs[3] : cs[1]) + __shfl_xor_sync(~0u, h ? cs[1] : cs[3], 16);
                    const int v = (odd ? y : x) + __shfl_xor_sync(~0u, odd ? x : y, 8);
                    const int gu = __shfl_sync(~0u, myG, t), G = gu & 255;
                    if (k2) {
                        if (__shfl_sync(~0u, rb ^ o[0].x, CFG_RB16 ? 6 : 0)) asm volatile("fence.acq_rel.gpu;" ::: "memory");
                        if (elect_one()) asm volatile("red.relaxed.gpu.global.add.u32 [%0], 1;" :: "l"(g_flag + 512 + (gu >> 8)) : "memory");
                        if (lane == 0) TLJ(202 + t);
                        const int old = atomicAdd(g_cs[ep & 1] + col_of(G) + (lane & 7) * 4 + (lane >> 3), v);
                        if (old == 0x7FFFFFFF) g_sink = old;
                        __syncwarp();
                        if (elect_one()) asm volatile("red.relaxed.gpu.global.add.u32 [%0], 1;" :: "l"(g_flag + 576 + (t >= 10)) : "memory");
                    } else if (G != r) {
                        asm volatile("red.async.relaxed.cluster.shared::cluster.mbarrier::complete_tx::bytes.add.s32 [%0], %1, [%2];"
                                     :: "r"(mapa(sb + SM_CS + lane * 4, G)), "r"(v), "r"(mapa(bars + B_CS * 8, G)) : "memory");
                    } else {
                        asm volatile("red.shared.add.s32 [%0], %1;" :: "r"(sb + SM_CS + lane * 4), "r"(v) : "memory");
                        __syncwarp();
                        if (elect_one()) mbar_arrive(bars + B_CS * 8);
                    }
                    if (lane == 0 && !k2) TLJ(202 + t);
                }
            }
        } else {
            asm volatile("setmaxnreg.dec.sync.aligned.u32 " STR(CFG_RO) ";");
            if (warp == 11) {
            if (elect_one()) {
#pragma unroll
                for (int i = 0; i < (k2 ? NU / 2 : NBJ); i++) mbar_init(bars + (B_GO + i) * 8, k2 ? (i * 2 + (r & 1) >= NSLOT ? 9 : 1) : i * 16 + r >= NSLOT * 5 ? 1 + 4 * CS : 1);
#pragma unroll
                for (int i = 0; i < 3; i++) mbar_init(bars + (B_FILL + i) * 8, 4);
            }
            const int u2 = lane * 2 + (r & 1), q = k2 ? (u2 < 32 ? 5 * u2 : 4 * u2 + 32) : (lane & 15) * 16 + r;
            const BJob bj = decode_b(q);
            const int nself = __popc(__ballot_sync(~0u, lane < NBJ && bj.G == r));
            sts32(sb + SM_CS + lane * 4, 0);
            if (lane == 0) {
                mbar_init(bars + B_CS * 8, 1 + nself);
                mbar_expect_tx(bars + B_CS * 8, (16 - nself) * 128);
            }

            asm volatile("fence.mbarrier_init.release.cluster;" ::: "memory");
            asm volatile("barrier.cluster.arrive.relaxed.aligned;" :: "r"(lds32(sb + SM_CS + lane * 4)) : "memory");
            const char* src = (const char*)g_s8 + (1024 + c * 256 + q) * 2048;
            const uint32_t dst = sb + SM_RING + ((CFG_R8 && !k2 && q >= 160) ? ((q + 20) & 31) * 2048 : (bj.u % NSLOT) * SLOT + bj.pos * 2048);
            const uint32_t fb = bars + (B_FULLB + fb_of(bj.u)) * 8;
            asm volatile("barrier.cluster.wait.aligned;" ::: "memory");
            {
                const uint32_t sx2 = (uint32_t)__ldg((const unsigned short*)scale_x) * 0x10001u;
#pragma unroll
                for (int i = lane; i < TN / 4; i += 32) {
                    const bool hi = i >= TN / 8;
                    uint4 v = __ldg((const uint4*)((hi ? bias : scale_w) + c * TN) + (hi ? i - TN / 8 : i));
                    if (CFG_EPI == 2 && !hi) {
                        asm("mul.rn.bf16x2 %0, %0, %1;" : "+r"(v.x) : "r"(sx2)); asm("mul.rn.bf16x2 %0, %0, %1;" : "+r"(v.y) : "r"(sx2));
                        asm("mul.rn.bf16x2 %0, %0, %1;" : "+r"(v.z) : "r"(sx2)); asm("mul.rn.bf16x2 %0, %0, %1;" : "+r"(v.w) : "r"(sx2));
                    }
                    sts128(sb + SM_PAR + TN * 2 + i * 16, v);
                }
                __syncwarp();
                if (elect_one()) mbar_arrive(bars + B_SW * 8);
            }
#pragma unroll 1
            for (int i = 0; i < (k2 ? NU / 2 : NBJ); i++) {
                mbar_wait(bars + (B_GO + i) * 8);
                if (lane == i) {
                    asm volatile("cp.async.bulk.shared::cluster.global.mbarrier::complete_tx::bytes.multicast::cluster [%0], [%1], %2, [%3], %4;"
                                 :: "r"(dst), "l"(src), "r"(k2 ? (u2 < 32 ? SLOT : 8192) : 2048), "r"(fb), "h"((uint16_t)(k2 ? 3 : 0xFFFF)) : "memory");
                    TLREC(64 + i);
                }
                __syncwarp();
            }
            } else if (warp == 10) {
            const unsigned ep = (*(volatile unsigned*)&g_epoch[b] + 1) * 4;
            const unsigned* f = g_flag + (CFG_FL == 1 ? 1024 + b * 32 + (lane & 15) : CFG_FL == 3 ? 1024 + (r * 16 + (lane & 15)) * 32 : r * 32 + (lane & 15));
            bool dn = lane >= 16;
            const bool fr = lane < (k2 ? 7 : 13);
            asm volatile("barrier.cluster.wait.aligned;" ::: "memory");
            if (lane == 0) TLREC(15);
#define CHECK(v)                                                                                                        \
                if (!dn && (int)(v - ep) >= 0 && (fr || mbar_test(bars + (B_AFREE + lane) * 8))) {                 \
                    dn = true;                                                                                          \
                    if (!CFG_WF) asm volatile("fence.proxy.async.global;" ::: "memory");                                \
                    asm volatile("cp.async.bulk.shared::cluster.global.mbarrier::complete_tx::bytes [%0], [%1], %2, [%3];" \
                                 :: "r"(sb + SM_A + lane * 8192), "l"((const char*)g_s8 + (r * 16 + lane) * 8192),      \
                                    "r"(8192), "r"(bars + (B_FULLA + lane) * 8) : "memory");                            \
                    TLREC(112 + lane);                                                                                  \
                }                                                                                                       \
                if (__all_sync(~0u, dn)) break;
            for (int it = 0;; it++) {
                const unsigned v = ld_flag(f);
                if (lane == 0 && (it & 3) == 0 && it < 64) TLREC(88 + (it >> 2));
                CHECK(v)
                if (it > (1 << 22)) __trap();
            }
            } else {
                const bool isw = warp == 9;
                const uint32_t rb = bars + (isw ? B_RAWB : B_RAWA) * 8;
                if (elect_one()) {
#pragma unroll
                    for (int i = 0; i < 13; i++) if (i < 3 || i >= (k2 ? 7 : 5)) mbar_init(rb + i * 8, 1);
                    if (isw) {
                        if (!CFG_ETM) asm volatile("prefetch.tensormap [%0];" :: "l"(maps.m + 1) : "memory");
#pragma unroll
                        for (int i = 13; i < 17; i++) mbar_init(rb + i * 8, 1);
                    }
                }
                __syncwarp();
                const int nj = isw ? NBJ : na, j0 = k2 ? 4 : 2;
                if (lane >= j0 && lane < nj) mbar_expect_tx(rb + (3 + lane) * 8, 8192);
                asm volatile("fence.mbarrier_init.release.cluster;" ::: "memory");
                asm volatile("barrier.cluster.arrive.relaxed.aligned;" ::: "memory");
                const int k = lane / 3, x = lane * 16 + r;
                int sl = lane - k * 3, y, z, T;
                if (isw) {
                    const BJob bj = decode_b(x & 255);
                    y = bj.slab * 64; z = (c * TN + col_of(bj.G)) >> 5; T = time_w(x);
                    if (CFG_BURST && T < NAJ / NCL + x) {
                        const int ph = ((((T - L0) * 16 / RA + L0) * 7) + 32) & 63;
                        T += ((32 - ph) * 16 * CFG_BURST) / (16 * 7 * 4);
                    }
                } else {
                    const int a0 = lane * NCTA + g, a = a0 ^ CFG_REV;
                    y = (a >> 6) * 2; z = (a & 63) * 32; T = time_x(x);
                    if (CFG_BURST && x >= L0 + 9) T += ((32 - (a0 & 63)) * (RA - 16) * CFG_BURST) / (16 * 7 * 4);
                    if (na == 10) sl = sl ? sl - 1 : 2;
                }
                const unsigned te = t0 + (k2 ? sched2(x) : sched(T));
                const uint32_t sd = sb + (isw ? stage_w<k2>(lane) : SM_A + (13 + sl) * 8192);
#pragma unroll 1
                for (int t = j0; t < nj; t++) {
                    if (lane == t) {
                        if (t >= 3 && !k2) mbar_wait(rb + sl * 8, (k & 1) ^ 1);
                        while ((int)(te - clk()) > 0) ;
                        raw_load(maps.m + isw, y, z, sd, rb + (3 + t) * 8);
                        TLJ(224 + isw * 10 + t);
                    }
                    __syncwarp();
                }
                asm volatile("barrier.cluster.wait.aligned;" ::: "memory");
                if (!k2 && !isw) {
#pragma unroll 1
                    for (int t = CFG_PFB; t < NBJ; t++) {
                        const int q = t * 16 + r - 160;
                        const char* p = qw + (((q >> 1) & 15) * 64 + lane) * (N_ * 4) + (c * TN + 320 + (q >> 5) * 64 + (q & 1) * 32) * 4;
                        const unsigned tp = t0 + sched(NAJ / NCL + 160 + q + CFG_PFO);
                        while ((int)(tp - clk()) > 0) ;
                        asm volatile("prefetch.global.L2 [%0];" :: "l"(p));
                        asm volatile("prefetch.global.L2 [%0];" :: "l"(p + 32 * N_ * 4));
                    }
                }
                if (!isw) cw = 2;
                if (k2) {
                    const unsigned e0 = *(volatile unsigned*)&g_epoch[b];
                    if (!isw) {
                        if (lane < TN / 16) g_cs[(e0 & 1) ^ 1][r * (TN / 16) + lane] = 0;
                        const int u = lane * 2 + (r & 1);
                        const unsigned tg = (e0 + 1) * (u < 32 ? 5 : 4);
                        bool dn = u >= NU;
                        for (int it = 0;; it++) {
                            if (!dn && (int)(ld_flag(g_flag + 512 + u) - tg) >= 0) {
                                dn = true;
                                mbar_arrive(bars + (B_GO + lane) * 8);
                            }
                            if (__all_sync(~0u, dn)) break;
                            if (it > (1 << 22)) __trap();
                        }
                    } else {
                        const float zxf = __bfloat162float(__float2bfloat16_rn((float)__ldg(zero_x)));
#pragma unroll 1
                        for (int h = 0; h < 2; h++) {
                            for (int it = 0; (int)(ld_flag(g_flag + 576 + h) - (e0 + 1) * (h ? 32 : 160)) < 0; it++) if (it > (1 << 22)) __trap();
                            int2 v[5];
#pragma unroll
                            for (int j = 0; j < 5; j++) v[j] = __ldcg((const int2*)g_cs[e0 & 1] + min(h * 160 + j * 32 + lane, TN / 2 - 1));
#pragma unroll
                            for (int j = 0; j < 5; j++) {
                                const int i = h * 160 + j * 32 + lane;
                                const float lo = __bfloat162float(__float2bfloat16_rn((float)v[j].x)) * zxf;
                                const float hi = __bfloat162float(__float2bfloat16_rn((float)v[j].y)) * zxf;
                                uint32_t z;
                                asm("cvt.rn.bf16x2.f32 %0, %1, %2;" : "=r"(z) : "f"(hi), "f"(lo));
                                if (i < TN / 2 - 32)
                                    asm volatile("st.async.weak.shared::cluster.mbarrier::complete_tx::bytes.b32 [%0], %1, [%2];"
                                                 :: "r"(sb + SM_PAR + i * 4), "r"(z), "r"(bars + (B_PAR + (i < 128 ? i >> 6 : i < 160 ? (i >> 4) & 1 : (i >> 5) - 3)) * 8) : "memory");
                            }
                            if (lane == 0) TLREC(8 + h);
                        }
                    }
                }
            }
            if (!k2 && r < NBJ && warp == (r < 10 ? 8 : 10)) {
            const float zxf = __bfloat162float(__float2bfloat16_rn((float)__ldg(zero_x)));
            mbar_wait(bars + B_CS * 8);
            const int w = lane & 15;
            const uint32_t ca = sb + SM_CS + ((w >> 1) + (w & 1) * 16) * 4;
            const float lo = __bfloat162float(__float2bfloat16_rn((float)(int)lds32(ca))) * zxf;
            const float hi = __bfloat162float(__float2bfloat16_rn((float)(int)lds32(ca + 32))) * zxf;
            uint32_t z;
            asm("cvt.rn.bf16x2.f32 %0, %1, %2;" : "=r"(z) : "f"(hi), "f"(lo));
            const int piece = r < 10 ? (r >= 5) : (r - 6) >> 1;
#pragma unroll 1
            for (int i = lane >> 4; i < CS; i += 2)
                asm volatile("st.async.weak.shared::cluster.mbarrier::complete_tx::bytes.b32 [%0], %1, [%2];"
                             :: "r"(mapa(sb + SM_PAR + col_of(r) * 2 + w * 4, i)), "r"(z), "r"(mapa(bars + (B_PAR + piece) * 8, i)) : "memory");
            if (lane == 0) TLREC(8);
            }
        }
#pragma unroll 1
            for (int n = cw, k = 0; n < NF; n += 3, k ^= 1) {
                const int gm = (int)(ford_table() >> (4 * n)), g = (gm >> 3) & 1, m = gm & 7;
                const int x = n >= 10 ? (n >> 1) * 64 : m == 4 ? 256 + g * 32 : g * 128 + (m & 1) * 64;
                const int y = n >= 10 ? (n & 1) * 64 : (m & 2) * 32;
                mbar_wait(bars + (B_FILL + cw) * 8, k);
                asm volatile("fence.proxy.async.shared::cta;" ::: "memory");
                if (!(DBG & 2) && elect_one())
                    asm volatile("cp.async.bulk.tensor.2d.global.shared::cta.tile.bulk_group [%0, {%1, %2}], [%3];"
                                 :: "l"(maps.m + (n < 10 && m == 4 ? 3 : 2)), "r"(c * TN + x), "r"(r * 128 + y), "r"(sb + SM_STG + ((cw + NBJ) % 3) * 8192) : "memory");
                asm volatile("cp.async.bulk.commit_group;" ::: "memory");
                if (lane == 0) TLREC(32 + n);
                asm volatile("cp.async.bulk.wait_group.read 0;" ::: "memory");
                __syncwarp();
                if (n < NF - 3 && elect_one()) mbar_arrive(bars + (B_FREE + 3 + n) * 8);
                if (lane == 0) TLREC(48 + n);
            }
        if (cw < 3 && lane == 0) TLE_REC(b, 1 + cw);
        TLEND();
    }
}

}

typedef CUresult (*EncodeFn)(CUtensorMap*, CUtensorMapDataType, cuuint32_t, void*, const cuuint64_t*, const cuuint64_t*,
                             const cuuint32_t*, const cuuint32_t*, CUtensorMapInterleave, CUtensorMapSwizzle,
                             CUtensorMapL2promotion, CUtensorMapFloatOOBfill);

extern "C" void kernel_launch(void* const* d_in, const int* in_sizes, int n_in, void* d_out, int out_size) {
    using namespace w8;
    static EncodeFn encode = nullptr;
    static cudaStream_t side;
    static cudaEvent_t started, joined;
    if (!encode) {
        void* fn = nullptr;
        cudaDriverEntryPointQueryResult qr;
        cudaGetDriverEntryPoint("cuTensorMapEncodeTiled", &fn, cudaEnableDefault, &qr);
        encode = (EncodeFn)fn;
        cudaStreamCreateWithFlags(&side, cudaStreamNonBlocking);
        cudaEventCreateWithFlags(&started, cudaEventDisableTiming);
        cudaEventCreateWithFlags(&joined, cudaEventDisableTiming);
        cudaFuncSetAttribute(w8a8_kernel<false>, cudaFuncAttributeMaxDynamicSharedMemorySize, SM_ALLOC);
        cudaFuncSetAttribute(w8a8_kernel<true>, cudaFuncAttributeMaxDynamicSharedMemorySize, SM_ALLOC);
        cudaFuncSetAttribute(w8a8_kernel<false>, cudaFuncAttributeNonPortableClusterSizeAllowed, 1);
    }
    Maps maps;
    {
        const cuuint64_t dim[3] = {32, K_ / 32, M_}, str[2] = {128, K_ * 4};
        const cuuint32_t box[3] = {32, 2, 32}, es[3] = {1, 1, 1};
        encode(&maps.m[0], CU_TENSOR_MAP_DATA_TYPE_INT32, 3, d_in[0], dim, str, box, es, CU_TENSOR_MAP_INTERLEAVE_NONE,
               CU_TENSOR_MAP_SWIZZLE_128B, CU_TENSOR_MAP_L2_PROMOTION_NONE, CU_TENSOR_MAP_FLOAT_OOB_FILL_NONE);
    }
    {
        const cuuint64_t dim[3] = {32, K_, N_ / 32}, str[2] = {N_ * 4, 128};
        const cuuint32_t box[3] = {32, 64, 1}, es[3] = {1, 1, 1};
        encode(&maps.m[1], CU_TENSOR_MAP_DATA_TYPE_INT32, 3, d_in[1], dim, str, box, es, CU_TENSOR_MAP_INTERLEAVE_NONE,
               CU_TENSOR_MAP_SWIZZLE_NONE, (CUtensorMapL2promotion)CFG_PROMO, CU_TENSOR_MAP_FLOAT_OOB_FILL_NONE);
    }
    {
        const cuuint64_t dim[2] = {N_, M_}, str[1] = {N_ * 2};
        const cuuint32_t box[2] = {WB, 64}, es[2] = {1, 1};
        encode(&maps.m[2], CU_TENSOR_MAP_DATA_TYPE_BFLOAT16, 2, d_out, dim, str, box, es, CU_TENSOR_MAP_INTERLEAVE_NONE,
               CU_TENSOR_MAP_SWIZZLE_128B, CU_TENSOR_MAP_L2_PROMOTION_NONE, CU_TENSOR_MAP_FLOAT_OOB_FILL_NONE);
    }
    {
        const cuuint64_t dim[2] = {N_, M_}, str[1] = {N_ * 2};
        const cuuint32_t box[2] = {32, 128}, es[2] = {1, 1};
        encode(&maps.m[3], CU_TENSOR_MAP_DATA_TYPE_BFLOAT16, 2, d_out, dim, str, box, es, CU_TENSOR_MAP_INTERLEAVE_NONE,
               CU_TENSOR_MAP_SWIZZLE_NONE, CU_TENSOR_MAP_L2_PROMOTION_NONE, CU_TENSOR_MAP_FLOAT_OOB_FILL_NONE);
    }
    for (int k = 0; k < ((DBG & 32) ? 1 : 2); k++) {
        cudaLaunchConfig_t cfg = {};
        cfg.gridDim = dim3(k ? 20 : NCTA); cfg.blockDim = dim3(512); cfg.dynamicSmemBytes = SM_ALLOC; cfg.stream = cudaStreamPerThread;
        cudaLaunchAttribute at[2];
        at[0].id = cudaLaunchAttributeClusterDimension; at[0].val.clusterDim.x = k ? 2 : CS; at[0].val.clusterDim.y = 1; at[0].val.clusterDim.z = 1;
        at[1].id = cudaLaunchAttributeProgrammaticStreamSerialization; at[1].val.programmaticStreamSerializationAllowed = 1;
        cfg.attrs = at; cfg.numAttrs = 1 + k;
        at[1].id = cudaLaunchAttributeLaunchCompletionEvent; at[1].val.launchCompletionEvent.event = started; at[1].val.launchCompletionEvent.flags = 0;
        cfg.numAttrs = 2 - k;
        if (k) { cudaStreamWaitEvent(side, started, 0); cfg.stream = side; }
        if (k && CFG_DOM) { at[1].id = cudaLaunchAttributeMemSyncDomain; at[1].val.memSyncDomain = cudaLaunchMemSyncDomainRemote; cfg.numAttrs = 2; }
        cudaLaunchKernelEx(&cfg, k ? w8a8_kernel<true> : w8a8_kernel<false>,
                           (const char*)d_in[0], (const char*)d_in[1], (const __nv_bfloat16*)d_in[2], (const int*)d_in[3], (const __nv_bfloat16*)d_in[4], (const __nv_bfloat16*)d_in[5]
                           , maps
                           );
        if (k) { cudaEventRecord(joined, side); cudaStreamWaitEvent(cudaStreamPerThread, joined, 0); }
    }
}
```

```cpp
#include <cuda_runtime.h>
#include <cuda.h>
#include <cuda_bf16.h>
#include <stdint.h>

#define CFG_X1 13
#define CFG_P1 46
#define CFG_P2 40
#define CFG_PT 100
#define CFG_L0 34
#define CFG_T0 -300
#define CFG_ACQ 0
#define CFG_MODE 1
#define CFG_PF 0
#define CFG_MC 16
#define CFG_NP 2
#define CFG_D 0
#define CFG_NL 2
#define CFG_R4 2
#define CFG_TD 30
#define CFG_TD0 1200
#define CFG_TDS 600
#define CFG_EPI 2
#define CFG_SLEEP 0
#define CFG_POLL2 0
#define CFG_PF2 0
#define CFG_PREG 56
#define CFG_CREG 200
#define STR2(x) #x
#define STR(x) STR2(x)
#define CFG_WF 1
#define CFG_FL 2
#define CFG_TB 10
#define CFG_Q2 63
#define CFG_PF7 18
#define CFG_Q0 14
#define CFG_NS 1
#define CFG_TS 8
#define CFG_Q3 30
#define CFG_RA 33
#define CFG_SH 0
#define CFG_WIN 2
#define CFG_HOLD 14
#define CFG_HS CFG_X1
#define CFG_PRE 1
#define CFG_P3 CFG_P2
#define CFG_PT3 210
#define CFG_LC 1
#define CFG_T3 1000
#define CFG_K3L 1
#define CFG_H2 1
#define CFG_D3 2
#define CFG_PROMO 0
#define CFG_RC 80
#define CFG_RO 32
#define CFG_PFIRST 1
#define CFG_CD 1
#define CLUSTER_ATTR __cluster_dims__(k2 ? 2 : 16, 1, 1)
#define CFG_ETM 1
#define CFG_EF 0
#define CFG_RB16 1
#define CFG_R8 1
#define CFG_RDY 1
#define CFG_QD 1
#define CFG_XA 96
#define CFG_RA2 CFG_RA
#define CFG_EARLY 0
#define CFG_REV 60
#define CFG_BURST 0
#define CFG_NA0 3
#define CFG_DOM 0
#define CFG_P3L 1
#define CFG_PFB 14
#define CFG_PFO 0
#define CFG_FAST0 1
#define CFG_PA0 0
#define CFG_ST3 1
#define CFG_KA 8
#define CFG_KB 9
#define CFG_H3 0
#define CFG_TAIL 0
#define CFG_NOFENCE 0
#define CFG_COB 1
#define CFG_TA 10
#define CFG_AG 0
#define CFG_ORD 0
#define DBG 0

namespace w8 {

constexpr int M_ = 2048, K_ = 1024, N_ = 3584;
constexpr int CS = 16, NCL = 7, NCTA = CS * NCL;
constexpr int WA = 160, WB = 64;
constexpr int NP = CFG_NP, TN = 2 * WA + NP * WB;
constexpr int DA = CFG_D, NL = CFG_NL, R4 = CFG_R4;
constexpr int NAJ = 1024;
constexpr int X1 = CFG_X1;
constexpr int NSLOT = 7, SLOT = WA * 64;
constexpr int NU1 = 48;
constexpr int NCONV = 4;
constexpr int L0 = CFG_L0, NS = CFG_NS;

constexpr int SM_A = 0;
constexpr int SM_RING = 131072;
constexpr int SM_STG = SM_RING + NSLOT * SLOT;
constexpr int SM_PAR = SM_STG + 3 * 8192;
constexpr int SM_CS = SM_PAR + 3 * TN * 2;
constexpr int SM_BAR = SM_CS + 128;
constexpr int B_FULLB = 0, B_FULLA = 56, B_PAR = 72, B_SW = 77, B_AFREE = 79 - 5  , B_FREE = 90, B_NINIT = 104,
              B_GO = 104, B_FILL = 128, B_CS = 131, B_RAWA = 132, B_RAWB = 145, B_RAWS = 162, B_END = 163;
constexpr int SM_TOTAL = SM_BAR + B_END * 8;
static_assert(SM_TOTAL <= 232448, "");

__device__ uint4 g_s8[(1024 + 8 * 256) * 128];
__device__ unsigned g_flag[1024 + 8192];
__device__ int g_cs[2][TN];
__device__ int g_sink;
__device__ unsigned g_epoch[132];
#define TLE_REC(b, i) do {} while (0)
#define TLREC(i) do {} while (0)
#define TLCLK(i) do {} while (0)
#define TLEND() do {} while (0)
constexpr int SM_ALLOC = SM_TOTAL;

#define TL2 0
#define TLJ(i) TLREC(i)
#define TLW(i) do {} while (0)
#define TLVAL(i, v) do {} while (0)
__device__ __forceinline__ void mbar_init(uint32_t bar, uint32_t cnt) {
    asm volatile("mbarrier.init.shared::cta.b64 [%0], %1;" :: "r"(bar), "r"(cnt) : "memory");
}
__device__ __forceinline__ void mbar_expect_tx(uint32_t bar, uint32_t bytes) {
    asm volatile("mbarrier.arrive.expect_tx.shared::cta.b64 _, [%0], %1;" :: "r"(bar), "r"(bytes) : "memory");
}
__device__ __forceinline__ void mbar_arrive(uint32_t bar) {
    asm volatile("mbarrier.arrive.shared::cta.b64 _, [%0];" :: "r"(bar) : "memory");
}
__device__ __forceinline__ void mbar_arrive_cluster(uint32_t bar) {
    asm volatile("mbarrier.arrive.shared::cluster.b64 _, [%0];" :: "r"(bar) : "memory");
}
__device__ __forceinline__ void mbar_wait(uint32_t bar, uint32_t parity = 0) {
    asm volatile("{\n.reg .pred p;\n.reg .u32 c;\n"
                 "mbarrier.try_wait.parity.shared::cta.b64 p, [%0], %1;\n"
                 "@p bra WAIT_DONE;\n"
                 "mov.u32 c, 0;\n"
                 "WAIT_LOOP:\n"
                 "mbarrier.try_wait.parity.shared::cta.b64 p, [%0], %1;\n"
                 "@p bra WAIT_DONE;\n"
                 "add.u32 c, c, 1;\nsetp.lt.u32 p, c, 0x100000;\n"
                 "@p bra WAIT_LOOP;\n"
                 "trap;\n"
                 "WAIT_DONE:\n}" :: "r"(bar), "r"(parity) : "memory");
}
__device__ __forceinline__ void mbar_wait2(uint32_t bar0, uint32_t bar1) {
    asm volatile("{\n.reg .pred p, q;\n.reg .u32 c;\nmov.u32 c, 0;\n"
                 "WAIT_LOOP:\n"
                 "mbarrier.try_wait.parity.shared::cta.b64 p, [%0], 0;\n"
                 "mbarrier.try_wait.parity.shared::cta.b64 q, [%1], 0;\n"
                 "and.pred p, p, q;\n"
                 "@p bra WAIT_DONE;\n"
                 "add.u32 c, c, 1;\nsetp.lt.u32 p, c, 0x100000;\n"
                 "@p bra WAIT_LOOP;\n"
                 "trap;\n"
                 "WAIT_DONE:\n}" :: "r"(bar0), "r"(bar1) : "memory");
}
__device__ __forceinline__ bool mbar_test(uint32_t bar) {
    uint32_t ok;
    asm volatile("{\n.reg .pred p;\nmbarrier.test_wait.parity.shared::cta.b64 p, [%1], 0;\nselp.u32 %0, 1, 0, p;\n}" : "=r"(ok) : "r"(bar) : "memory");
    return ok;
}
__device__ __forceinline__ bool mbar_test2(uint32_t bar0, uint32_t bar1) {
    uint32_t ok;
    asm volatile("{\n.reg .pred p, q;\nmbarrier.test_wait.parity.shared::cta.b64 p, [%1], 0;\n"
                 "mbarrier.test_wait.parity.shared::cta.b64 q, [%2], 0;\nand.pred p, p, q;\nselp.u32 %0, 1, 0, p;\n}"
                 : "=r"(ok) : "r"(bar0), "r"(bar1) : "memory");
    return ok;
}
__device__ __forceinline__ bool elect_one() {
    uint32_t ok;
    asm volatile("{\n.reg .pred p;\nelect.sync _|p, 0xffffffff;\nselp.u32 %0, 1, 0, p;\n}" : "=r"(ok));
    return ok;
}
__device__ __forceinline__ unsigned ld_acquire(const unsigned* p) {
    unsigned v;
    asm volatile("ld.acquire.gpu.global.u32 %0, [%1];" : "=r"(v) : "l"(p) : "memory");
    return v;
}
__device__ __forceinline__ unsigned ld_flag(const unsigned* p) {
    unsigned v;
    asm volatile("ld.relaxed.gpu.global.u32 %0, [%1];" : "=r"(v) : "l"(p) : "memory");
    return v;
}
__device__ __forceinline__ uint4 lds128(uint32_t a) {
    uint4 v;
    asm volatile("ld.shared.v4.b32 {%0,%1,%2,%3}, [%4];" : "=r"(v.x), "=r"(v.y), "=r"(v.z), "=r"(v.w) : "r"(a) : "memory");
    return v;
}
__device__ __forceinline__ void sts128(uint32_t a, uint4 v) {
    asm volatile("st.shared.v4.b32 [%0], {%1,%2,%3,%4};" :: "r"(a), "r"(v.x), "r"(v.y), "r"(v.z), "r"(v.w) : "memory");
}
__device__ __forceinline__ uint32_t lds32(uint32_t a) {
    uint32_t v;
    asm volatile("ld.shared.b32 %0, [%1];" : "=r"(v) : "r"(a) : "memory");
    return v;
}
__device__ __forceinline__ void sts32(uint32_t a, uint32_t v) {
    asm volatile("st.shared.b32 [%0], %1;" :: "r"(a), "r"(v) : "memory");
}
__device__ __forceinline__ void stg128(void* p, uint4 v) {
    asm volatile("st.global.v4.b32 [%0], {%1,%2,%3,%4};" :: "l"(p), "r"(v.x), "r"(v.y), "r"(v.z), "r"(v.w) : "memory");
}
__device__ __forceinline__ unsigned pack4(unsigned a, unsigned b, unsigned c, unsigned d) {
    unsigned lo, r;
    asm("cvt.pack.sat.s8.s32.b32 %0, %1, %2, 0;" : "=r"(lo) : "r"(d), "r"(c));
    asm("cvt.pack.sat.s8.s32.b32 %0, %1, %2, %3;" : "=r"(r) : "r"(b), "r"(a), "r"(lo));
    return r;
}

constexpr uint32_t DESC_A_HI = 0x80000000u | (512 >> 4);
constexpr uint32_t DESC_B_HI = 512 >> 4;
template <int NR> __device__ __forceinline__ void wgmma_n160(int (&d)[NR], uint32_t alo, uint32_t blo, int scale_d) {
    asm volatile("{\n.reg .pred p;\n.reg .b64 da, db;\nsetp.ne.b32 p, %82, 0;\n"
        "mov.b64 da, {%80, %83};\nmov.b64 db, {%81, %84};\n"
        "wgmma.mma_async.sync.aligned.m64n160k32.s32.s8.s8 "
        "{%0, %1, %2, %3, %4, %5, %6, %7, %8, %9, %10, %11, %12, %13, %14, %15, "
        "%16, %17, %18, %19, %20, %21, %22, %23, %24, %25, %26, %27, %28, %29, %30, %31, "
        "%32, %33, %34, %35, %36, %37, %38, %39, %40, %41, %42, %43, %44, %45, %46, %47, "
        "%48, %49, %50, %51, %52, %53, %54, %55, %56, %57, %58, %59, %60, %61, %62, %63, "
        "%64, %65, %66, %67, %68, %69, %70, %71, %72, %73, %74, %75, %76, %77, %78, %79}, "
        "da, db, p;\n}\n"
        : "+r"(d[0]), "+r"(d[1]), "+r"(d[2]), "+r"(d[3]), "+r"(d[4]), "+r"(d[5]), "+r"(d[6]), "+r"(d[7]),
          "+r"(d[8]), "+r"(d[9]), "+r"(d[10]), "+r"(d[11]), "+r"(d[12]), "+r"(d[13]), "+r"(d[14]), "+r"(d[15]),
          "+r"(d[16]), "+r"(d[17]), "+r"(d[18]), "+r"(d[19]), "+r"(d[20]), "+r"(d[21]), "+r"(d[22]), "+r"(d[23]),
          "+r"(d[24]), "+r"(d[25]), "+r"(d[26]), "+r"(d[27]), "+r"(d[28]), "+r"(d[29]), "+r"(d[30]), "+r"(d[31]),
          "+r"(d[32]), "+r"(d[33]), "+r"(d[34]), "+r"(d[35]), "+r"(d[36]), "+r"(d[37]), "+r"(d[38]), "+r"(d[39]),
          "+r"(d[40]), "+r"(d[41]), "+r"(d[42]), "+r"(d[43]), "+r"(d[44]), "+r"(d[45]), "+r"(d[46]), "+r"(d[47]),
          "+r"(d[48]), "+r"(d[49]), "+r"(d[50]), "+r"(d[51]), "+r"(d[52]), "+r"(d[53]), "+r"(d[54]), "+r"(d[55]),
          "+r"(d[56]), "+r"(d[57]), "+r"(d[58]), "+r"(d[59]), "+r"(d[60]), "+r"(d[61]), "+r"(d[62]), "+r"(d[63]),
          "+r"(d[64]), "+r"(d[65]), "+r"(d[66]), "+r"(d[67]), "+r"(d[68]), "+r"(d[69]), "+r"(d[70]), "+r"(d[71]),
          "+r"(d[72]), "+r"(d[73]), "+r"(d[74]), "+r"(d[75]), "+r"(d[76]), "+r"(d[77]), "+r"(d[78]), "+r"(d[79])
        : "r"(alo), "r"(blo), "r"(scale_d), "r"(DESC_A_HI), "r"(DESC_B_HI));
}
template <int NR> __device__ __forceinline__ void wgmma_t128(int (&d)[NR], uint32_t alo, uint32_t blo, int scale_d) {
    asm volatile("{\n.reg .pred p;\n.reg .b64 da, db;\nsetp.ne.b32 p, %66, 0;\n"
        "mov.b64 da, {%64, %67};\nmov.b64 db, {%65, %68};\n"
        "wgmma.mma_async.sync.aligned.m64n128k32.s32.s8.s8 "
        "{%0, %1, %2, %3, %4, %5, %6, %7, %8, %9, %10, %11, %12, %13, %14, %15, "
        "%16, %17, %18, %19, %20, %21, %22, %23, %24, %25, %26, %27, %28, %29, %30, %31, "
        "%32, %33, %34, %35, %36, %37, %38, %39, %40, %41, %42, %43, %44, %45, %46, %47, "
        "%48, %49, %50, %51, %52, %53, %54, %55, %56, %57, %58, %59, %60, %61, %62, %63}, "
        "da, db, p;\n}\n"
        : "+r"(d[0]), "+r"(d[1]), "+r"(d[2]), "+r"(d[3]), "+r"(d[4]), "+r"(d[5]), "+r"(d[6]), "+r"(d[7]),
          "+r"(d[8]), "+r"(d[9]), "+r"(d[10]), "+r"(d[11]), "+r"(d[12]), "+r"(d[13]), "+r"(d[14]), "+r"(d[15]),
          "+r"(d[16]), "+r"(d[17]), "+r"(d[18]), "+r"(d[19]), "+r"(d[20]), "+r"(d[21]), "+r"(d[22]), "+r"(d[23]),
          "+r"(d[24]), "+r"(d[25]), "+r"(d[26]), "+r"(d[27]), "+r"(d[28]), "+r"(d[29]), "+r"(d[30]), "+r"(d[31]),
          "+r"(d[32]), "+r"(d[33]), "+r"(d[34]), "+r"(d[35]), "+r"(d[36]), "+r"(d[37]), "+r"(d[38]), "+r"(d[39]),
          "+r"(d[40]), "+r"(d[41]), "+r"(d[42]), "+r"(d[43]), "+r"(d[44]), "+r"(d[45]), "+r"(d[46]), "+r"(d[47]),
          "+r"(d[48]), "+r"(d[49]), "+r"(d[50]), "+r"(d[51]), "+r"(d[52]), "+r"(d[53]), "+r"(d[54]), "+r"(d[55]),
          "+r"(d[56]), "+r"(d[57]), "+r"(d[58]), "+r"(d[59]), "+r"(d[60]), "+r"(d[61]), "+r"(d[62]), "+r"(d[63])
        : "r"(alo), "r"(blo), "r"(scale_d), "r"(DESC_B_HI), "r"(DESC_A_HI));
}

__device__ __forceinline__ void wg_fence() { asm volatile("wgmma.fence.sync.aligned;" ::: "memory"); }
__device__ __forceinline__ void wg_commit() { asm volatile("wgmma.commit_group.sync.aligned;" ::: "memory"); }
template <int N> __device__ __forceinline__ void wg_wait() { asm volatile("wgmma.wait_group.sync.aligned %0;" :: "n"(N) : "memory"); }

__device__ __forceinline__ uint32_t mapa(uint32_t a, uint32_t r) {
    uint32_t o;
    asm("mapa.shared::cluster.u32 %0, %1, %2;" : "=r"(o) : "r"(a), "r"(r));
    return o;
}
__device__ __forceinline__ unsigned clk() {
    unsigned t;
    asm volatile("mov.u32 %0, %clock;" : "=r"(t));
    return t;
}
__host__ __device__ constexpr int unit_of(int piece, int slab) {
    return piece < 2 ? (slab < X1 ? 2 * slab + piece : (piece ? 16 : X1) + slab) : 32 + (piece - 2) * 8 + (slab >> 1);
}
__host__ __device__ constexpr int col_of(int G) { return G == 4 ? 256 : (G > 4 && G < 9) ? 32 * G - 32 : 32 * G; }
struct BJob { int u, slab, G, pos; };
__host__ __device__ constexpr BJob decode_b(int q) {
    BJob j = {};
    if (q < 160) {
        j.u = q / 5; j.pos = q - j.u * 5;
        const int piece = j.u < 2 * X1 ? (j.u & 1) : (j.u >= X1 + 16);
        j.slab = j.u < 2 * X1 ? (j.u >> 1) : j.u - (piece ? 16 : X1);
        j.G = piece * 5 + j.pos;
    } else {
        q -= 160;
        j.u = 32 + (q >> 2); j.pos = q & 3;
        j.slab = (q >> 1) & 15;
        j.G = 10 + (q >> 5) * 2 + (q & 1);
    }
    return j;
}
__host__ __device__ constexpr int fb_of(int u) {
    return u < 2 * X1 ? (u & 1) * 32 + (u >> 1) : u < X1 + 16 ? u - X1 : u < 32 ? 16 + u : u < 40 ? u - 16 : u < 48 ? u + 8 : u - 24;
}
template <bool k2> __device__ __forceinline__ int stage_w(int t) { return (k2 && t < 9) ? SM_A + (7 + t) * 8192 : SM_STG + (t % 3) * 8192; }
constexpr int RA = CFG_RA, RB64 = 64 * RA / (RA - 16);
constexpr int RA2 = CFG_RA2, RB642 = 64 * RA2 / (RA2 - 16), XA = CFG_XA, QA = (XA - L0) * (RA - 16) / 16;
__device__ __forceinline__ int time_x(int x) { return max(x, L0 + (((x - L0) * RA + max(x - XA, 0) * (RA2 - RA)) >> 4)); }
__device__ __forceinline__ int time_w(int q) { return min(L0 + ((q * RB64 + max(q - QA, 0) * (RB642 - RB64)) >> 6), NAJ / NCL + q); }
__device__ __forceinline__ int sched2(int x) { return (min(x, 160) - CFG_Q0) * CFG_Q2 + max(x - 160, 0) * CFG_Q3; }
__device__ __forceinline__ unsigned sched(int T) { return T * CFG_P2 + min(T, CFG_PT) * (CFG_P1 - CFG_P2) + max(T - CFG_PT3, 0) * (CFG_P3 - CFG_P2); }
__device__ __forceinline__ void raw_load(const void* map, int y, int z, uint32_t dst, uint32_t bar) {
    asm volatile("cp.async.bulk.tensor.3d.shared::cluster.global.tile.mbarrier::complete_tx::bytes [%0], [%1, {0, %2, %3}], [%4];"
                 :: "r"(dst), "l"(map), "r"(y), "r"(z), "r"(bar) : "memory");
}
__host__ __device__ constexpr uint64_t slot_table(int piece) {
    uint64_t t = 0;
    if (piece < 2) for (int s = 0; s < 16; s++) t |= (uint64_t)(unit_of(piece, s) % NSLOT) << (4 * s);
    else for (int s = 0; s < 8; s++) t |= (uint64_t)(unit_of(piece, 2 * s) % NSLOT) << (4 * s);
    return t;
}
constexpr int NA0 = CFG_NA0;
__host__ __device__ constexpr int ford(int g, int m) {
    if (CFG_ORD) return g ? NA0 + m : m < NA0 ? m : 5 + m;
    return g ? (m < NA0 - 1 ? 2 + 2 * m : NA0 + m) : (m < 2 ? m : m < NA0 ? 2 * m - 1 : 5 + m);
}
__host__ __device__ constexpr uint64_t ford_table() {
    uint64_t t = 0;
    for (int g = 0; g < 2; g++) for (int m = 0; m < 5; m++) t |= (uint64_t)(g * 8 + m) << (4 * ford(g, m));
    return t;
}
struct Maps { CUtensorMap m[4]; };

__device__ __forceinline__ uint32_t bf2_op_epi(int a, int b, uint32_t zc, uint32_t sx, uint32_t sw, uint32_t bi) {
    uint32_t v;
    if (DBG & 1) return a ^ b ^ zc;
    float fa = __int2float_rn(a), fb = __int2float_rn(b);
    asm("cvt.rn.bf16x2.f32 %0, %1, %2;" : "=r"(v) : "f"(fb), "f"(fa));
    asm("sub.rn.bf16x2 %0, %0, %1;" : "+r"(v) : "r"(zc));
    if (CFG_EPI < 2) asm("mul.rn.bf16x2 %0, %0, %1;" : "+r"(v) : "r"(sx));
    if (CFG_EPI == 0) {
        asm("mul.rn.bf16x2 %0, %0, %1;" : "+r"(v) : "r"(sw));
        asm("add.rn.bf16x2 %0, %0, %1;" : "+r"(v) : "r"(bi));
    } else {
        asm("fma.rn.bf16x2 %0, %0, %1, %2;" : "+r"(v) : "r"(sw), "r"(bi));
    }
    return v;
}
struct Par { uint4 zc, sw, bi; };
__device__ __forceinline__ Par ld_par(uint32_t p) { return {lds128(p), lds128(p + TN * 2), lds128(p + TN * 4)}; }
__device__ __forceinline__ uint4 epi_row(const int (&a)[WA / 2], int o, const Par& p, uint32_t sx2) {
    uint4 r;
    r.x = bf2_op_epi(a[o + 0], a[o + 4], p.zc.x, sx2, p.sw.x, p.bi.x);
    r.y = bf2_op_epi(a[o + 8], a[o + 12], p.zc.y, sx2, p.sw.y, p.bi.y);
    r.z = bf2_op_epi(a[o + 1], a[o + 5], p.zc.z, sx2, p.sw.z, p.bi.z);
    r.w = bf2_op_epi(a[o + 9], a[o + 13], p.zc.w, sx2, p.sw.w, p.bi.w);
    return r;
}
__device__ __forceinline__ void release(uint32_t go, int u, int lane, bool k2) {
    const int v = u + NSLOT;
    if (CFG_R8 && !k2) {
        const int q = 5 * v - (v > 34 ? 3 : 0) + lane;
        if (lane < (v > 38 ? 0 : v == 34 ? 2 : 5)) mbar_arrive_cluster(mapa(go + (q >> 4) * 8, q & 15));
        return;
    }
    const int n = k2 ? 1 : v < 32 ? 5 : 4, sh = k2 ? 1 : 4;
    const int q = n * v + (n == 4 ? 32 : 0) + lane;
    if (lane < (v < NU1 ? n : 0)) mbar_arrive_cluster(mapa(go + (q >> sh) * 8, q & ((1 << sh) - 1)));
}

#define READ_BACK asm volatile("ld.relaxed.gpu.global.u32 %0, [%1];" : "=r"(rb) : "l"(d - lane + ((lane + 10) & 15) * 8 + 6) : "memory");
#define CV_B(m, f)                                                                                    \
                    {                                                                                 \
                        uint4 v0 = lds128(rdB + m * 512), v1 = lds128(rdB + m * 512 + 128);           \
                        uint4 v2 = lds128(rdB + m * 512 + 256), v3 = lds128(rdB + m * 512 + 384);     \
                        o[0].f = pack4(v0.x, v1.x, v2.x, v3.x); o[1].f = pack4(v0.y, v1.y, v2.y, v3.y); \
                        o[2].f = pack4(v0.z, v1.z, v2.z, v3.z); o[3].f = pack4(v0.w, v1.w, v2.w, v3.w); \
                    }

__device__ __forceinline__ void last_columns(const Maps& maps, const __nv_bfloat16* scale_x, const int* zero_x, const __nv_bfloat16* scale_w,
                                             const __nv_bfloat16* bias, uint32_t sb, int warp, int lane, unsigned t0) {
    constexpr int C_FULL = 0, C_EMPTY = 32, C_RAW = 64, C_GO = 80, C_PEER = 81;
    const uint32_t bars = sb + SM_BAR;
    const int j = (blockIdx.x & 1) + ((blockIdx.x >> 1) == CFG_KB ? 2 : 0);
    if (CFG_T3) while ((int)(t0 + CFG_T3 - clk()) > 0) ;
    const int s0 = (j & 1) * 8 + (warp >> 1) * 2;
    if (warp < 8) {
        if (elect_one()) {
#pragma unroll
            for (int i = 0; i < 2; i++) {
                const uint32_t bar = bars + (C_RAW + warp * 2 + i) * 8;
                mbar_init(bar, 1); mbar_expect_tx(bar, 8192);
                raw_load(maps.m + 1, (s0 + (i ^ (j >> 1))) * 64, N_ / 32 - 2 + (warp & 1), sb + SM_A + (warp * 2 + i) * 8192, bar);
            }
#pragma unroll
            for (int i = 0; i < 4; i++) { mbar_init(bars + (C_FULL + warp * 4 + i) * 8, 1); mbar_expect_tx(bars + (C_FULL + warp * 4 + i) * 8, 16384); }
#pragma unroll
            for (int i = 0; i < 4; i++) mbar_init(bars + (C_EMPTY + warp * 4 + i) * 8, 4);
            if (warp == 0) {
                mbar_init(bars + C_GO * 8, 8);
                mbar_init(bars + C_PEER * 8, 1); mbar_expect_tx(bars + C_PEER * 8, 32768 + 4096);
            }
        }
        if (warp < 2) sts32(sb + SM_PAR + threadIdx.x * 4, 0);
        asm volatile("fence.mbarrier_init.release.cluster;" ::: "memory");
    }
    __syncthreads();
    asm volatile("barrier.cluster.arrive.relaxed.aligned;" ::: "memory");
    asm volatile("barrier.cluster.wait.aligned;" ::: "memory");
    if (warp >= 8) {
        asm volatile("setmaxnreg.dec.sync.aligned.u32 40;");
        if (warp < 12) {
            const unsigned ep = (*(volatile unsigned*)&g_epoch[128 + j] + 1) * 4;
            const int mb = j * 4 + warp - 8, wg = (warp >> 1) & 1;
            unsigned rdy = 0;
            mbar_wait(bars + C_GO * 8);
            if (CFG_ST3 && wg) mbar_wait(bars + (C_EMPTY + (CFG_ST3 - 1) * 2) * 8);
#pragma unroll 1
            for (int s = 0; s < 16; s++) {
                for (int it = 0; !((rdy >> s) & 1); it++) {
                    rdy = __ballot_sync(~0u, (int)(ld_flag(g_flag + mb * 32 + (lane & 15)) - ep) >= 0);
                    if (it > (1 << 22)) __trap();
                }
                if (s >= CFG_D3) mbar_wait(bars + (C_EMPTY + (s - CFG_D3) * 2 + wg) * 8);
                if (elect_one())
                    asm volatile("cp.async.bulk.shared::cluster.global.mbarrier::complete_tx::bytes [%0], [%1], %2, [%3];"
                                 :: "r"(sb + SM_A + ((s & 3) * 4 + warp - 8) * 8192), "l"((const char*)g_s8 + (mb * 16 + s) * 8192),
                                    "r"(8192), "r"(bars + (C_FULL + s * 2 + wg) * 8) : "memory");
            }
        }
    } else {
        asm volatile("setmaxnreg.inc.sync.aligned.u32 200;");
        const int wg = warp >> 2, w = warp & 3;
        const int c0 = (w >> 1) * 32 + (lane >> 2) * 4 + (w & 1) * 2, r0 = (lane & 3) * 2;
        const uint32_t sx2 = (uint32_t)__ldg((const unsigned short*)scale_x) * 0x10001u;
        uint32_t sw = __ldg((const unsigned*)(scale_w + N_ - WB + c0));
        const uint32_t bi = __ldg((const unsigned*)(bias + N_ - WB + c0));
        const float zxf = __bfloat162float(__float2bfloat16_rn((float)__ldg(zero_x)));
        int cs[4] = {0, 0, 0, 0};
        const uint32_t peer = mapa(sb, (j & 1) ^ 1);
#pragma unroll 1
        for (int i = 0; i < 2; i++) {
            const uint32_t rdB = sb + SM_A + (warp * 2 + i) * 8192 + (lane >> 3) * 2048 + (lane & 7) * 16;
            const uint32_t wr = SM_RING + (s0 + (i ^ (j >> 1))) * 4096 + (warp & 1) * 2048 + lane * 16;
            mbar_wait(bars + (C_RAW + warp * 2 + i) * 8);
            uint4 o[4];
            CV_B(0, x) CV_B(1, y) CV_B(2, z) CV_B(3, w)
#pragma unroll
            for (int k = 0; k < 4; k++) {
                sts128(sb + wr + k * 512, o[k]);
                asm volatile("st.async.weak.shared::cluster.mbarrier::complete_tx::bytes.v4.b32 [%0], {%1,%2,%3,%4}, [%5];"
                             :: "r"(peer + wr + k * 512), "r"(o[k].x), "r"(o[k].y), "r"(o[k].z), "r"(o[k].w), "r"(peer + SM_BAR + C_PEER * 8) : "memory");
                cs[k] = __dp4a((int)o[k].x, 0x01010101, __dp4a((int)o[k].y, 0x01010101,
                        __dp4a((int)o[k].z, 0x01010101, __dp4a((int)o[k].w, 0x01010101, cs[k]))));
            }
        }
        __syncwarp();
        if (elect_one()) mbar_arrive(bars + C_GO * 8);
#pragma unroll
        for (int k = 0; k < 4; k++) {
            const uint32_t ca = SM_PAR + ((warp & 1) * 32 + (lane & 7) * 4 + k) * 4;
            asm volatile("red.shared.add.s32 [%0], %1;" :: "r"(sb + ca), "r"(cs[k]) : "memory");
            asm volatile("red.async.relaxed.cluster.shared::cluster.mbarrier::complete_tx::bytes.add.s32 [%0], %1, [%2];"
                         :: "r"(peer + ca), "r"(cs[k]), "r"(peer + SM_BAR + C_PEER * 8) : "memory");
        }
        mbar_wait(bars + C_PEER * 8);
        asm volatile("fence.proxy.async.shared::cta;" ::: "memory");
        asm volatile("bar.sync 1, 256;" ::: "memory");
        if (CFG_EPI == 2) asm("mul.rn.bf16x2 %0, %0, %1;" : "+r"(sw) : "r"(sx2));
        if (threadIdx.x == 0) TLE_REC(128 + j, 4);
        uint32_t zc;
        asm("cvt.rn.bf16x2.f32 %0, %1, %2;" : "=r"(zc) : "f"(__bfloat162float(__float2bfloat16_rn((float)(int)lds32(sb + SM_PAR + c0 * 4 + 4))) * zxf),
                                                         "f"(__bfloat162float(__float2bfloat16_rn((float)(int)lds32(sb + SM_PAR + c0 * 4))) * zxf));
        const uint32_t sd = (sb & 0x3FFFF) >> 4;
        int t[2][64];
        wg_fence();
#pragma unroll 1
        for (int s = 0; s < 16; s++) {
            const uint32_t db = ((sd + (SM_RING >> 4)) | (8 << 16)) + s * 256, da = ((sd + (SM_A >> 4)) | (1 << 16)) + ((s & 3) * 4 + wg * 2) * 512;
            mbar_wait(bars + (C_FULL + s * 2 + wg) * 8);
            wgmma_t128(t[0], db, da, s);
            wgmma_t128(t[1], db, da + 512, s);
            wgmma_t128(t[0], db + 16, da + 2, 1);
            wgmma_t128(t[1], db + 16, da + 514, 1);
            wg_commit();
            wg_wait<0>();
            if (elect_one()) mbar_arrive(bars + (C_EMPTY + s * 2 + wg) * 8);
        }
        asm volatile("bar.sync %0, 128;" :: "r"(3 + wg) : "memory");
        if (threadIdx.x == 0) TLE_REC(128 + j, 5);
        const uint32_t st0 = sb + SM_A + wg * 16384 + r0 * 128 + (((c0 >> 3) ^ r0) << 4) + (c0 & 7) * 2;
#pragma unroll
        for (int h = 0; h < 4; h++) {
            const uint32_t off = (h >> 1) * 32768 + (h & 1) * 8192;
#pragma unroll
            for (int q = 0; q < 8; q++) {
                const int o = (h & 1) * 32 + q * 4;
                sts32(st0 + off + q * 1024, bf2_op_epi(t[h >> 1][o], t[h >> 1][o + 2], zc, sx2, sw, bi));
                sts32((st0 ^ (5 * 128 + 5 * 16)) + off + q * 1024, bf2_op_epi(t[h >> 1][o + 1], t[h >> 1][o + 3], zc, sx2, sw, bi));
            }
            asm volatile("fence.proxy.async.shared::cta;" ::: "memory");
            asm volatile("bar.sync %0, 128;" :: "r"(3 + wg) : "memory");
            if (w == 0 && elect_one())
                asm volatile("cp.async.bulk.tensor.2d.global.shared::cta.tile.bulk_group [%0, {%1, %2}], [%3];"
                             :: "l"(maps.m + 2), "r"(N_ - WB), "r"(j * 512 + wg * 256 + h * 64), "r"(sb + SM_A + wg * 16384 + off) : "memory");
        }
        if (w == 0) {
            asm volatile("cp.async.bulk.commit_group;" ::: "memory");
            asm volatile("cp.async.bulk.wait_group.read 0;" ::: "memory");
        }
        asm volatile("bar.sync 1, 256;" ::: "memory");
        if (threadIdx.x == 0) asm volatile("red.relaxed.gpu.global.add.u32 [%0], 1;" :: "l"(g_epoch + 128 + j) : "memory");
        if (threadIdx.x == 0) TLE_REC(128 + j, 1);
    }
}

template <bool k2>
__global__ void CLUSTER_ATTR __launch_bounds__(512, 1)
w8a8_kernel(
            const char* __restrict__ qx, const char* __restrict__ qw, const __nv_bfloat16* __restrict__ scale_x, const int* __restrict__ zero_x,
            const __nv_bfloat16* __restrict__ scale_w, const __nv_bfloat16* __restrict__ bias
            , const __grid_constant__ Maps maps
            ) {
    extern __shared__ __align__(1024) unsigned char smem_raw[];
    if (!k2 && !CFG_LC) asm volatile("griddepcontrol.launch_dependents;");
    constexpr int NBJ = k2 ? 12 : 14, NF = NBJ, NU = k2 ? 40 : NU1;
    constexpr bool cob = CFG_COB && !k2;
    const int b = blockIdx.x + (k2 ? NCTA - ((blockIdx.x >> 1) > CFG_KA ? 2 : 0) - ((blockIdx.x >> 1) > CFG_KB ? 2 : 0) : 0), r = b & 15, c = k2 ? NCL : b >> 4;
    const unsigned tc = clk();
    if (threadIdx.x < CFG_PF * 64 && !k2) {
        const int a = (threadIdx.x >> 6) * NCTA + r * NCL + c;
        asm volatile("prefetch.global.L2 [%0];" :: "l"(qx + ((a & 63) * 32 + ((threadIdx.x >> 1) & 31)) * (K_ * 4) + (a >> 6) * 256 + (threadIdx.x & 1) * 128));
    }
    const uint32_t sb = (uint32_t)__cvta_generic_to_shared(smem_raw);
    const uint32_t bars = sb + SM_BAR;
    const unsigned tw = __shfl_sync(~0u, (tc & ~15u) | threadIdx.x >> 5, 0), t0 = tw + (k2 ? 0 : CFG_T0);
    const int warp = tw & 15, lane = threadIdx.x & 31;

    if (CFG_FAST0 && !k2 && warp == 12) {
        const int a = r * NCL + c;
        if (elect_one()) {
            mbar_init(bars + (B_RAWA + 3) * 8, 1);
            mbar_expect_tx(bars + (B_RAWA + 3) * 8, 8192);
            if (CFG_PA0) while ((int)(t0 + r * CFG_PA0 - clk()) > 0) ;
            raw_load(maps.m, (a >> 6) * 2, ((a ^ CFG_REV) & 63) * 32, sb + SM_A + (a < NAJ % NCTA ? 15 : 13) * 8192, bars + (B_RAWA + 3) * 8);
        }
        __syncwarp();
    }
    if (CFG_ETM && warp >= 8 + (CFG_FAST0 && CFG_PA0 == 0) && warp < 10 && elect_one()) asm volatile("prefetch.tensormap [%0];" :: "l"(maps.m + (warp & 1)) : "memory");
    if (k2 && ((blockIdx.x >> 1) == CFG_KA || (blockIdx.x >> 1) == CFG_KB)) {
        if (!(DBG & 64)) last_columns(maps, scale_x, zero_x, scale_w, bias, sb, warp, lane, t0);
        return;
    }
    if (warp >= 12) {
        if (cob && warp == 14 && elect_one()) { mbar_init(bars + (B_RAWB + 3) * 8, 1); mbar_expect_tx(bars + (B_RAWB + 3) * 8, 8192); }
        __syncwarp();
        asm volatile("barrier.cluster.arrive.relaxed.aligned;" ::: "memory");
        if (warp == 12 && lane == 0) TLREC(0);
        const int t = k2 ? warp - 12 : warp & 1, isw = k2 || warp >= 14;
        const int x = t * 16 + r, a = (x * NCL + c) ^ CFG_REV, sx = (x * 26) >> 8;
        static_assert(X1 >= 7, "");
        const uint32_t bar = bars + ((isw ? B_RAWB : B_RAWA) + 3 + t) * 8;
        if (cob && warp == 15) asm volatile("barrier.cluster.wait.aligned;" ::: "memory");
        else if (!(CFG_FAST0 && !k2 && warp == 12) && elect_one()) {
            if (!(cob && warp == 14)) { mbar_init(bar, 1); mbar_expect_tx(bar, 8192); }
            const unsigned te = t0 + (k2 ? sched2(x) : (isw ? time_w(x) : time_x(x)) * CFG_P1);
            while ((int)(te - clk()) > 0) ;
            raw_load(maps.m + isw, isw ? sx * 64 : (a >> 6) * 2,
                     isw ? c * (TN / 32) + (int)((0x9765483210ull >> ((x - sx * 10) * 4)) & 15) : (a & 63) * 32,
                     sb + (k2 ? SM_A + 7 * 8192 : isw ? SM_STG : SM_A + 13 * 8192) + ((isw || r * NCL + c >= NAJ % NCTA) ? t : 2 - 2 * t) * 8192, bar);
            TLJ(224 + isw * 10 + t);
        }
        __syncwarp();
    }
    if (warp < 8) {
        const uint32_t p = bars + warp * 104;
        if (elect_one()) {
#pragma unroll
            for (int i = 0; i < 13; i++) mbar_init(p + i * 8, (cob && ((warp == 6 && i == 12) || (warp == 7 && i < 2))) ? 2 : 1);
            static_assert(B_FREE == 90, "");
        }
        __syncwarp();
        const int i = warp * 13 + lane;
        if (lane < 13 && i < B_SW) mbar_expect_tx(p + lane * 8, i >= B_PAR ? (i < B_PAR + 2 ? WA * 2 : WB * 2) : (i & 16) || i >= 48 ? 8192 : WA * 64);
        asm volatile("fence.mbarrier_init.release.cluster;" ::: "memory");
    }
    if (warp < 8 || warp == 10) asm volatile("barrier.cluster.arrive.relaxed.aligned;" ::: "memory");
    if (CFG_PF7 && !k2 && warp == 10 && lane < CFG_PF7) {
        const int n = b * CFG_PF7 + lane, row = n / 10;
        asm volatile("prefetch.global.L2 [%0];" :: "l"(qw + row * (N_ * 4) + NCL * TN * 4 + (n - row * 10) * 128));
    }

    if (warp < 8) {
        if (warp < 2 && elect_one()) asm volatile("prefetch.tensormap [%0];" :: "l"(maps.m + 2 + warp) : "memory");
        asm volatile("setmaxnreg.inc.sync.aligned.u32 " STR(CFG_CREG) ";");
        const int wg = warp >> 2;
        const uint32_t sd = (sb & 0x3FFFF) >> 4;
        const unsigned short sxr = __ldg((const unsigned short*)scale_x);
        const uint32_t sx2 = (uint32_t)sxr * 0x10001u;
        const uint32_t par = sb + SM_PAR + (lane & 3) * 16 + wg * 256;
        const uint32_t go = bars + B_GO * 8;
        const int w = warp & 3, pq = (lane >> 2) ^ (lane & 4);
        uint32_t so = (w * 16 + pq) * 128 + (((lane & 3) ^ pq) << 4);
        const int c0 = (w >> 1) * 32 + (lane >> 2) * 4 + (w & 1) * 2, r0 = (lane & 3) * 2;
        uint32_t pp = sb + SM_PAR + (2 * WA + wg * WB + c0) * 2, st0 = r0 * 128 + (((c0 >> 3) ^ r0) << 4) + (c0 & 7) * 2;
        int rq = lane < (k2 ? 1 : 4) ? (k2 ? 1 : 4) * (32 + wg * 8 + ((CFG_R8 && !k2) ? 8 : NSLOT)) + (k2 ? 0 : 32) + lane : 1000;
        asm volatile("" : "+r"(so), "+r"(pp), "+r"(st0), "+r"(rq));
        asm volatile("barrier.cluster.wait.aligned;" ::: "memory");
        if (threadIdx.x == 0) { TLREC(250); TLCLK(251); }
        int a0[WA / 2], a1[WA / 2];
        uint32_t barB = bars + (B_FULLB + wg * 32) * 8;
        wg_fence();
        {
            uint64_t tbl = wg ? slot_table(1) : slot_table(0);
            uint32_t da = (sd + (SM_A >> 4)) | (1 << 16);
            int up = 99;
            bool rdy = false;
#pragma unroll 1
            for (int s = 0; s < 16; s++) {
                const uint32_t db = ((sd + (SM_RING >> 4)) | (8 << 16)) + ((uint32_t)tbl & 15) * (SLOT >> 4);
                const bool hold = CFG_HOLD && (CFG_H2 || !k2) && wg && s == CFG_HS;
                if (hold || (!rdy && !mbar_test2(bars + (B_FULLA + s) * 8, barB))) {
                    wg_wait<0>();
                    release(go, up, lane, k2); up = 99;
                    mbar_wait2(bars + (B_FULLA + s) * 8, barB);
                    if (threadIdx.x % 128 == 0) TLW(160 + wg * 16 + s);
                    if (hold) asm volatile("bar.sync 7, 256;" ::: "memory");
                }
                wgmma_n160(a0, da, db, s);
                wgmma_n160(a1, da + 256, db, s);
                wg_commit();
                if (CFG_HOLD && (CFG_H2 || !k2) && !wg && s == CFG_HOLD) asm volatile("bar.arrive 7, 256;" ::: "memory");
                wg_wait<1>();
                release(go, up, lane, k2);
                wgmma_n160(a0, da + 2, db + 16, 1);
                wgmma_n160(a1, da + 258, db + 16, 1);
                wg_commit();
                if (threadIdx.x % 128 == 0) TLREC(256 + wg * 32 + s);
                up = s < X1 ? 2 * s + wg : (wg ? 16 : X1) + s;
                tbl >>= 4; da += 512; barB += 8;
                if (CFG_RDY) rdy = mbar_test2(bars + (B_FULLA + s + 1) * 8, barB);
                if (s < 15) wg_wait<1>();
            }
        }
        mbar_wait2(bars + (B_PAR + wg) * 8, bars + B_SW * 8);
        Par P = ld_par(par);
        wg_wait<0>();
        release(go, wg ? 31 : X1 + 15, lane, k2);
        if (threadIdx.x % 128 == 0) { TLREC(1 + wg); TLE_REC(b, 4 + wg); }
        bool ready = mbar_test(barB);
#define FILL_BEGIN(n0, n1) mbar_wait(bars + (B_FREE + (wg ? n1 : n0)) * 8);                                              \
                           const uint32_t buf = sb + SM_STG + (wg ? (n1 + NBJ) % 3 : (n0 + NBJ) % 3) * 8192;
#define FILL_END(n0, n1) __syncwarp(); if (elect_one()) mbar_arrive(bars + (B_FILL + (wg ? n1 % 3 : n0 % 3)) * 8);        \
                         if (threadIdx.x % 128 == 0) TLREC(16 + (wg ? n1 : n0));
#define FILL_PAIR(a, J, PN, n0, n1)                                                                                     \
        {                                                                                                               \
            const uint4 v0 = epi_row(a, J * 16, P, sx2);                                                                \
            const Par Q = ld_par(par + J * 64 + 64);                                                                    \
            const uint4 v1 = epi_row(a, J * 16 + 2, P, sx2);                                                            \
            if (CFG_EARLY == 2 && (n0) == ford(0, NA0)) { wg_wait<0>(); if (wg == 0) RELEASE_N() }                      \
            if (CFG_EARLY == 3 && (n0) == ford(0, NA0)) { wg_wait<1>(); if (wg == 0 && nrel < 7) RELEASE_N() }          \
            FILL_BEGIN(n0, n1)                                                                                          \
            sts128(buf + so, v0); sts128(buf + so + 1024, v1);                                                          \
            if ((PN) >= 0) P = ld_par(par + (PN));                                                                      \
            sts128(buf + (so ^ 64), epi_row(a, J * 16 + 16, Q, sx2));                                                   \
            sts128(buf + (so ^ 64) + 1024, epi_row(a, J * 16 + 18, Q, sx2));                                            \
            FILL_END(n0, n1)                                                                                            \
        }
        constexpr int rn = k2 ? 1 : 4;
#define RELEASE_N() { if (rq < (k2 ? NU : NBJ * 16)) mbar_arrive_cluster(mapa(go + (rq >> rn) * 8, rq & ((1 << rn) - 1))); rq += rn; nrel++; }
#define NARROW(p)                                                                                                       \
        {                                                                                                               \
            uint32_t tbl = (uint32_t)slot_table(p), da = (sd + (SM_A >> 4)) | (1 << 16);                                \
            if (CFG_H3 && p == 3) asm volatile("bar.sync 6, 256;" ::: "memory");                                        \
            wg_fence();                                                                                                 \
            _Pragma("unroll 1") for (int i = 0; i < ((CFG_EARLY == 4 && p == 2 && !k2) ? 6 : 8); i++) {                 \
                const uint32_t db = ((sd + (SM_RING >> 4)) | (8 << 16)) + ((CFG_R8 && !k2) ? ((i + 5) & 7) * 512 : (tbl & 15) * (SLOT >> 4)); \
                if (!ready && !mbar_test(barB)) {                                                                       \
                    wg_wait<0>();                                                                                       \
                    if (p == 2 || !CFG_R8) { _Pragma("unroll 1") while (nrel < i) RELEASE_N() }                         \
                    mbar_wait(barB);                                                                                    \
                }                                                                                                       \
                _Pragma("unroll") for (int kk = 0; kk < 4; kk++)                                                        \
                    wgmma_t128(t, db + (kk >> 1) * 256 + (kk & 1) * 16, da + (kk >> 1) * 512 + (kk & 1) * 2, kk ? 1 : i); \
                wg_commit();                                                                                            \
                if (threadIdx.x % 128 == 0) TLREC(256 + (p == 2 ? 16 : 48) + i);                                        \
                barB += 8;                                                                                              \
                ready = mbar_test(barB);                                                                                \
                if ((p == 2 || !CFG_R8) && nrel < i - CFG_QD) RELEASE_N()                                               \
                tbl >>= 4; da += 1024;                                                                                  \
                if (CFG_H3 && !k2 && p == 2 && i == CFG_H3) asm volatile("bar.arrive 6, 256;" ::: "memory");            \
                if (CFG_TAIL && p == 3 && i == 4) asm volatile("bar.sync 4, 128;" ::: "memory");                        \
                if (CFG_EARLY != 3 || p == 3 || i < 7) wg_wait<CFG_QD>();                                               \
            }                                                                                                           \
            if (CFG_EARLY == 4 && p == 2 && !k2) {            \
                P = ld_par(par + pn);                                                                                   \
                mbar_wait2(barB, barB + 8);                                                                             \
                _Pragma("unroll") for (int kk = 0; kk < 8; kk++)                                                        \
                    wgmma_t128(t, ((sd + (SM_RING >> 4)) | (8 << 16)) + 3 * 512 + (kk >> 1) * 256 + (kk & 1) * 16, da + (kk >> 1) * 512 + (kk & 1) * 2, 1); \
                wg_commit();                                                                                            \
                wg_wait<1>();                                                                                           \
                _Pragma("unroll 1") while (nrel < 6) RELEASE_N()                                                        \
            } else                                                                                                      \
            if (p == 2) { if (CFG_EARLY != 3) { if (nrel < 8 - CFG_QD) RELEASE_N() if (NA0 < 5) P = ld_par(par + pn); } } \
            else { zc = lds32(pp); sw = lds32(pp + TN * 2); bi = lds32(pp + TN * 4); }                                  \
            if (p == 3 || !CFG_EARLY) wg_wait<0>();                                                                     \
            if (p == 2 && !CFG_EARLY) RELEASE_N()                                                                       \
            if (threadIdx.x % 128 == 0) TLREC(3 + p);                                                                   \
        }
#define FO(m) ford(0, m), ford(1, m)
#define FILL_PAIR2(...) FILL_PAIR(__VA_ARGS__)
#define NARROW_AT(k, PN) if (NA0 == k) { pn = PN; if (wg == 0) NARROW(2) else if (k < 5) P = ld_par(par + pn); }   \
                         if ((CFG_EARLY == 1 || CFG_EARLY >= 3) && NA0 == k - 1) { wg_wait<0>(); if (wg == 0) { RELEASE_N() if (CFG_EARLY == 4 && !k2) RELEASE_N() } }
        int nrel = 0, pn = 0;
        static_assert(CFG_EARLY < 2 || NA0 < 4, "");
        FILL_PAIR2(a0, 0, 128, FO(0)) FILL_PAIR2(a0, 2, NA0 == 2 ? -1 : 0, FO(1))
        int t[64];
        uint32_t zc, sw, bi;
        NARROW_AT(2, 0)
        FILL_PAIR2(a1, 0, NA0 == 3 ? -1 : 128, FO(2))
        NARROW_AT(3, 128)
        FILL_PAIR2(a1, 2, NA0 == 4 ? -1 : 512 - wg * 192, FO(3))
        NARROW_AT(4, 512 - wg * 192)
        {
            const uint4 v0 = epi_row(a0, 64, P, sx2), v1 = epi_row(a0, 66, P, sx2);
            if (!(k2 && wg) && NA0 < 5) mbar_wait(bars + (B_PAR + 2 + wg) * 8);
            FILL_BEGIN(ford(0, 4), ford(1, 4))
            const uint32_t s4 = buf + ((so >> 1) & ~63u) + (lane & 3) * 16;
            sts128(s4, v0); sts128(s4 + 512, v1);
            sts128(s4 + 4096, epi_row(a1, 64, P, sx2)); sts128(s4 + 4608, epi_row(a1, 66, P, sx2));
            FILL_END(ford(0, 4), ford(1, 4))
        }
        NARROW_AT(5, 0)
        if (!(k2 && wg) && NA0 == 5) mbar_wait(bars + (B_PAR + 2 + wg) * 8);
        NARROW_AT(6, 0)
        if (!(k2 && wg)) {
        if (!k2 && wg == 1) NARROW(3) else { zc = lds32(pp); sw = lds32(pp + TN * 2); bi = lds32(pp + TN * 4); }
#define FILL_T(h)                                                                                                       \
        {                                                                                                               \
            if (!(CFG_TAIL && wg)) mbar_wait(bars + (B_FREE + (wg ? 12 + h : 10 + h)) * 8);                             \
            const uint32_t buf = sb + ((CFG_TAIL && wg) ? SM_RING + (5 + h) * 8192 : SM_STG + (wg ? (12 + h + NBJ) % 3 : (10 + h + NBJ) % 3) * 8192); \
            _Pragma("unroll") for (int j = 0; j < 8; j++) {                                                             \
                const int o = h * 32 + j * 4;                                                                           \
                sts32(buf + st0 + j * 1024, bf2_op_epi(t[o], t[o + 2], zc, sx2, sw, bi));                               \
                sts32(buf + (st0 ^ (5 * 128 + 5 * 16)) + j * 1024, bf2_op_epi(t[o + 1], t[o + 3], zc, sx2, sw, bi));    \
            }                                                                                                           \
            __syncwarp();                                                                                               \
            if (elect_one()) mbar_arrive(bars + (wg ? (CFG_TAIL ? B_GO + 14 + h : B_FILL + (12 + h) % 3) : B_FILL + (10 + h) % 3) * 8); \
            if (threadIdx.x % 128 == 0) TLREC(16 + (wg ? 12 + h : 10 + h));                                             \
        }
        FILL_T(0) FILL_T(1)
        }
        if (DBG & 4) for (int i = 0; i < 56; i++) mbar_wait(bars + i * 8);
        if (threadIdx.x == 0) { TLREC(252); TLCLK(253); }
        TLEND();
        if (threadIdx.x == 128) asm volatile("red.relaxed.gpu.global.add.u32 [%0], 1;" :: "l"(g_epoch + b) : "memory");
    } else {
        const int g = r * NCL + c, na = k2 ? 0 : NAJ / NCTA + (g < NAJ % NCTA);
        int cw = NF;
        if (warp >= 12) {
            asm volatile("setmaxnreg.dec.sync.aligned.u32 " STR(CFG_RC) ";");
            if (warp < 14) {
                const int c4 = (lane ^ (lane >> 3)) & 3, ln = ((lane >> 2) ^ (lane & 4)) * 2 + (c4 >> 1);
                const uint32_t rd0 = sb + SM_A + 13 * 8192 + ln * 128 + ((((c4 & 1) << 2) ^ (ln & 7)) << 4);
#pragma unroll 1
                for (int t = warp - 12, sl = na == 9 ? t : 2 - 2 * t; t < na; t += 2, sl = sl ? sl - 1 : 2) {
                    const uint32_t rdA = rd0 + sl * 8192;
                    const int a = (t * NCTA + g) ^ CFG_REV, f = (a & 60) * 4 + (a >> 6);
                    uint4* const d = g_s8 + (f * 4 + (a & 3)) * 128 + lane;
                    uint4 o[4];
                    mbar_wait(bars + (B_RAWA + 3 + t) * 8);
                    if (lane == 0) TLJ(128 + t);
#pragma unroll
                    for (int i = 0; i < 4; i++) {
                        uint4 v0 = lds128(rdA + i * 2048), v1 = lds128((rdA ^ 16) + i * 2048);
                        uint4 v2 = lds128((rdA ^ 32) + i * 2048), v3 = lds128((rdA ^ 48) + i * 2048);
                        o[i].x = pack4(v0.x, v0.y, v0.z, v0.w); o[i].y = pack4(v1.x, v1.y, v1.z, v1.w);
                        o[i].z = pack4(v2.x, v2.y, v2.z, v2.w); o[i].w = pack4(v3.x, v3.y, v3.z, v3.w);
                    }
#pragma unroll
                    for (int i = 0; i < 4; i++) stg128(d + i * 32, o[i]);
                    unsigned rb;
                    if (CFG_WF) asm volatile("fence.proxy.async.global;" ::: "memory");
                    __syncwarp();
                    READ_BACK
                    if (t < 2) asm volatile("barrier.cluster.wait.aligned;" ::: "memory");
                    if (elect_one()) mbar_arrive(bars + ((t < na - 3 ? B_RAWA : B_AFREE + 13) + sl) * 8);
                    if (lane == 0) TLJ(160 + t);
                    if (__shfl_sync(~0u, rb ^ o[0].x, CFG_RB16 ? 6 : 0)) asm volatile("fence.acq_rel.gpu;" ::: "memory");
                    if (elect_one()) asm volatile("red.relaxed.gpu.global.add.u32 [%0], 1;" :: "l"(g_flag + (a & 60) * 8 + (a >> 6)) : "memory");
                    if (lane == 0) TLJ(192 + t);
                }
                if (k2 || !CFG_AG) cw = warp - 12;
            }
            if (cob) {
                const int hw = warp & 1;
                const uint32_t rd0 = sb + SM_STG + hw * 4096 + (lane >> 3) * 1024 + (lane & 7) * 16;
                const int myG = decode_b((lane & 15) * 16 + r).G;
#pragma unroll 1
                for (int t = warp < 14 ? CFG_TA : 0; t < NBJ; t += warp < 14 ? NBJ : t == CFG_TA - 1 ? 2 : 1) {
                    const int sl = t % 3;
                    const uint32_t rdB = rd0 + sl * 8192;
                    char* const d = (char*)g_s8 + (1024 + c * 256 + t * 16 + r) * 2048 + hw * 256 + (lane >> 4) * 128 + (lane & 7) * 16 + (lane & 8);
                    uint2 o[4];
                    mbar_wait(bars + (B_RAWB + 3 + t) * 8);
                    if (lane == 0 && !hw) TLJ(138 + t);
                    CV_B(0, x) CV_B(1, y)
#pragma unroll
                    for (int i = 0; i < 4; i++) asm volatile("st.global.v2.b32 [%0], {%1,%2};" :: "l"(d + i * 512), "r"(o[i].x), "r"(o[i].y) : "memory");
                    if (t == 0 && warp == 14) asm volatile("barrier.cluster.wait.aligned;" ::: "memory");
                    if (elect_one()) mbar_arrive(bars + (t >= NBJ - 3 ? B_FREE + t - (NBJ - 3) : B_RAWB + sl) * 8);
                    asm volatile("fence.proxy.async.global;" ::: "memory");
                    __syncwarp();
                    if (elect_one()) mbar_arrive(bars + (B_GO + t) * 8);
                    if (lane == 0 && !hw) TLREC((TL2 ? 234 : 170) + t);
                    int cs[4];
#pragma unroll
                    for (int i = 0; i < 4; i++) cs[i] = __dp4a((int)o[i].x, 0x01010101, __dp4a((int)o[i].y, 0x01010101, 0));
                    const int p01 = cs[0] + cs[1] * 65536, p23 = cs[2] + cs[3] * 65536;
                    const bool h = lane & 16;
                    int x = (h ? p23 : p01) + __shfl_xor_sync(~0u, h ? p01 : p23, 16);
                    x += __shfl_xor_sync(~0u, x, 8);
                    const int lo = (int)(short)x, v = (lane & 8) ? (x - lo) >> 16 : lo;
                    const int G = __shfl_sync(~0u, myG, t);
                    if (G != r) {
                        asm volatile("red.async.relaxed.cluster.shared::cluster.mbarrier::complete_tx::bytes.add.s32 [%0], %1, [%2];"
                                     :: "r"(mapa(sb + SM_CS + lane * 4, G)), "r"(v), "r"(mapa(bars + B_CS * 8, G)) : "memory");
                    } else {
                        asm volatile("red.shared.add.s32 [%0], %1;" :: "r"(sb + SM_CS + lane * 4), "r"(v) : "memory");
                        __syncwarp();
                        if (elect_one()) mbar_arrive(bars + B_CS * 8);
                    }
                    if (lane == 0 && !hw) TLJ(202 + t);
                }
            } else {
                const uint32_t rd0 = sb + (lane >> 3) * 2048 + (lane & 7) * 16;
                const BJob mb = decode_b((lane & 15) * 16 + r);
                const int myG = mb.G | mb.u << 8;
#pragma unroll 1
                for (int t = k2 ? warp - 12 : warp < 14 ? CFG_TB + warp - 10 : warp - 14; t < NBJ; t += (!k2 && t < CFG_TB) ? 2 : 4) {
                    const uint32_t rdB = rd0 + stage_w<k2>(t);
                    uint4* const d = g_s8 + (1024 + c * 256 + t * 16 + r) * 128 + lane;
                    uint4 o[4];
                    mbar_wait(bars + (B_RAWB + 3 + t) * 8);
                    if (lane == 0) TLJ(138 + t);
                    CV_B(0, x) CV_B(1, y) CV_B(2, z) CV_B(3, w)
#pragma unroll
                    for (int i = 0; i < 4; i++) stg128(d + i * 32, o[i]);
                    if (t < (k2 ? 4 : 2)) asm volatile("barrier.cluster.wait.aligned;" ::: "memory");
                    if (elect_one()) mbar_arrive(bars + ((k2 || t >= NBJ - 3) ? B_FREE + t - (NBJ - 3) : B_RAWB + t % 3) * 8);
                    asm volatile("fence.proxy.async.global;" ::: "memory");
                    __syncwarp();
                    unsigned rb = 0, ep = 0;
                    if (k2) {
                        READ_BACK
                        ep = ld_flag(g_epoch + b);
                    } else if (elect_one()) mbar_arrive(bars + (B_GO + t) * 8);
                    if (lane == 0) TLREC((TL2 ? 234 : 170) + t);
                    int cs[4];
#pragma unroll
                    for (int i = 0; i < 4; i++)
                        cs[i] = __dp4a((int)o[i].x, 0x01010101, __dp4a((int)o[i].y, 0x01010101,
                                __dp4a((int)o[i].z, 0x01010101, __dp4a((int)o[i].w, 0x01010101, 0))));
                    const bool h = lane & 16, odd = lane & 8;
                    int x = (h ? cs[2] : cs[0]) + __shfl_xor_sync(~0u, h ? cs[0] : cs[2], 16);
                    int y = (h ? cs[3] : cs[1]) + __shfl_xor_sync(~0u, h ? cs[1] : cs[3], 16);
                    const int v = (odd ? y : x) + __shfl_xor_sync(~0u, odd ? x : y, 8);
                    const int gu = __shfl_sync(~0u, myG, t), G = gu & 255;
                    if (k2) {
                        if (__shfl_sync(~0u, rb ^ o[0].x, CFG_RB16 ? 6 : 0)) asm volatile("fence.acq_rel.gpu;" ::: "memory");
                        if (elect_one()) asm volatile("red.relaxed.gpu.global.add.u32 [%0], 1;" :: "l"(g_flag + 512 + (gu >> 8)) : "memory");
                        if (lane == 0) TLJ(202 + t);
                        const int old = atomicAdd(g_cs[ep & 1] + col_of(G) + (lane & 7) * 4 + (lane >> 3), v);
                        if (old == 0x7FFFFFFF) g_sink = old;
                        __syncwarp();
                        if (elect_one()) asm volatile("red.relaxed.gpu.global.add.u32 [%0], 1;" :: "l"(g_flag + 576 + (t >= 10)) : "memory");
                    } else if (G != r) {
                        asm volatile("red.async.relaxed.cluster.shared::cluster.mbarrier::complete_tx::bytes.add.s32 [%0], %1, [%2];"
                                     :: "r"(mapa(sb + SM_CS + lane * 4, G)), "r"(v), "r"(mapa(bars + B_CS * 8, G)) : "memory");
                    } else {
                        asm volatile("red.shared.add.s32 [%0], %1;" :: "r"(sb + SM_CS + lane * 4), "r"(v) : "memory");
                        __syncwarp();
                        if (elect_one()) mbar_arrive(bars + B_CS * 8);
                    }
                    if (lane == 0 && !k2) TLJ(202 + t);
                }
            }
        } else {
            asm volatile("setmaxnreg.dec.sync.aligned.u32 " STR(CFG_RO) ";");
            if (warp == 11) {
            if (elect_one()) {
#pragma unroll
                for (int i = 0; i < (k2 ? NU / 2 : NBJ); i++) mbar_init(bars + (B_GO + i) * 8, k2 ? (i * 2 + (r & 1) >= NSLOT ? 9 : 1) : (i * 16 + r >= NSLOT * 5 ? 1 + 4 * CS : 1) + cob);
#pragma unroll
                for (int i = 0; i < 3; i++) mbar_init(bars + (B_FILL + i) * 8, 4);
                if (CFG_TAIL && !k2) { mbar_init(bars + (B_GO + 14) * 8, 4); mbar_init(bars + (B_GO + 15) * 8, 4); }
            }
            const int u2 = lane * 2 + (r & 1), q = k2 ? (u2 < 32 ? 5 * u2 : 4 * u2 + 32) : (lane & 15) * 16 + r;
            const BJob bj = decode_b(q);
            const int nself = __popc(__ballot_sync(~0u, lane < NBJ && bj.G == r));
            sts32(sb + SM_CS + lane * 4, 0);
            if (lane == 0) {
                mbar_init(bars + B_CS * 8, 1 + (nself << cob));
                mbar_expect_tx(bars + B_CS * 8, (16 - nself) * (128 << cob));
            }

            asm volatile("fence.mbarrier_init.release.cluster;" ::: "memory");
            asm volatile("barrier.cluster.arrive.relaxed.aligned;" :: "r"(lds32(sb + SM_CS + lane * 4)) : "memory");
            const char* src = (const char*)g_s8 + (1024 + c * 256 + q) * 2048;
            const uint32_t dst = sb + SM_RING + ((CFG_R8 && !k2 && q >= 160) ? ((q + 20) & 31) * 2048 : (bj.u % NSLOT) * SLOT + bj.pos * 2048);
            const uint32_t fb = bars + (B_FULLB + fb_of(bj.u)) * 8;
            asm volatile("barrier.cluster.wait.aligned;" ::: "memory");
            {
                const uint32_t sx2 = (uint32_t)__ldg((const unsigned short*)scale_x) * 0x10001u;
#pragma unroll
                for (int i = lane; i < TN / 4; i += 32) {
                    const bool hi = i >= TN / 8;
                    uint4 v = __ldg((const uint4*)((hi ? bias : scale_w) + c * TN) + (hi ? i - TN / 8 : i));
                    if (CFG_EPI == 2 && !hi) {
                        asm("mul.rn.bf16x2 %0, %0, %1;" : "+r"(v.x) : "r"(sx2)); asm("mul.rn.bf16x2 %0, %0, %1;" : "+r"(v.y) : "r"(sx2));
                        asm("mul.rn.bf16x2 %0, %0, %1;" : "+r"(v.z) : "r"(sx2)); asm("mul.rn.bf16x2 %0, %0, %1;" : "+r"(v.w) : "r"(sx2));
                    }
                    sts128(sb + SM_PAR + TN * 2 + i * 16, v);
                }
                __syncwarp();
                if (elect_one()) mbar_arrive(bars + B_SW * 8);
            }
#pragma unroll 1
            for (int i = 0; i < (k2 ? NU / 2 : NBJ); i++) {
                mbar_wait(bars + (B_GO + i) * 8);
                if (lane == i) {
                    asm volatile("cp.async.bulk.shared::cluster.global.mbarrier::complete_tx::bytes.multicast::cluster [%0], [%1], %2, [%3], %4;"
                                 :: "r"(dst), "l"(src), "r"(k2 ? (u2 < 32 ? SLOT : 8192) : 2048), "r"(fb), "h"((uint16_t)(k2 ? 3 : 0xFFFF)) : "memory");
                    TLREC(64 + i);
                }
                __syncwarp();
            }
            } else if (warp == 10) {
            const unsigned ep = (*(volatile unsigned*)&g_epoch[b] + 1) * 4;
            const unsigned* f = g_flag + (CFG_FL == 1 ? 1024 + b * 32 + (lane & 15) : CFG_FL == 3 ? 1024 + (r * 16 + (lane & 15)) * 32 : r * 32 + (lane & 15));
            bool dn = lane >= 16;
            const bool fr = lane < (k2 ? 7 : 13);
            asm volatile("barrier.cluster.wait.aligned;" ::: "memory");
            if (lane == 0) TLREC(15);
#define CHECK(v)                                                                                                        \
                if (!dn && (int)(v - ep) >= 0 && (fr || mbar_test(bars + (B_AFREE + lane) * 8))) {                 \
                    dn = true;                                                                                          \
                    if (!CFG_WF) asm volatile("fence.proxy.async.global;" ::: "memory");                                \
                    asm volatile("cp.async.bulk.shared::cluster.global.mbarrier::complete_tx::bytes [%0], [%1], %2, [%3];" \
                                 :: "r"(sb + SM_A + lane * 8192), "l"((const char*)g_s8 + (r * 16 + lane) * 8192),      \
                                    "r"(8192), "r"(bars + (B_FULLA + lane) * 8) : "memory");                            \
                    TLREC(112 + lane);                                                                                  \
                }                                                                                                       \
                if (__all_sync(~0u, dn)) break;
            for (int it = 0;; it++) {
                const unsigned v = ld_flag(f);
                if (lane == 0 && (it & 3) == 0 && it < 64) TLREC(88 + (it >> 2));
                CHECK(v)
                if (it > (1 << 22)) __trap();
            }
            } else {
                const bool isw = warp == 9;
                const uint32_t rb = bars + (isw ? B_RAWB : B_RAWA) * 8;
                if (elect_one()) {
#pragma unroll
                    for (int i = 0; i < 13; i++) if (i < 3 || i >= (k2 ? 7 : 5)) mbar_init(rb + i * 8, (i < 3 && isw && cob) ? 2 : 1);
                    if (isw) {
                        if (!CFG_ETM) asm volatile("prefetch.tensormap [%0];" :: "l"(maps.m + 1) : "memory");
#pragma unroll
                        for (int i = 13; i < 17; i++) mbar_init(rb + i * 8, 1);
                        if (cob) mbar_init(rb + 4 * 8, 1);
                    }
                }
                __syncwarp();
                const int nj = isw ? NBJ : na, j0 = k2 ? 4 : (cob && isw) ? 1 : 2;
                if (lane >= j0 && lane < nj) mbar_expect_tx(rb + (3 + lane) * 8, 8192);
                asm volatile("fence.mbarrier_init.release.cluster;" ::: "memory");
                asm volatile("barrier.cluster.arrive.relaxed.aligned;" ::: "memory");
                const int k = lane / 3, x = lane * 16 + r;
                int sl = lane - k * 3, y, z, T;
                if (isw) {
                    const BJob bj = decode_b(x & 255);
                    y = bj.slab * 64; z = (c * TN + col_of(bj.G)) >> 5; T = time_w(x);
                    if (CFG_BURST && T < NAJ / NCL + x) {
                        const int ph = ((((T - L0) * 16 / RA + L0) * 7) + 32) & 63;
                        T += ((32 - ph) * 16 * CFG_BURST) / (16 * 7 * 4);
                    }
                } else {
                    const int a0 = lane * NCTA + g, a = a0 ^ CFG_REV;
                    y = (a >> 6) * 2; z = (a & 63) * 32; T = time_x(x);
                    if (CFG_BURST && x >= L0 + 9) T += ((32 - (a0 & 63)) * (RA - 16) * CFG_BURST) / (16 * 7 * 4);
                    if (na == 10) sl = sl ? sl - 1 : 2;
                }
                const unsigned te = t0 + (k2 ? sched2(x) : sched(T));
                const uint32_t sd = sb + (isw ? stage_w<k2>(lane) : SM_A + (13 + sl) * 8192);
#pragma unroll 1
                for (int t = j0; t < nj; t++) {
                    if (lane == t) {
                        if (t >= 3 && !k2) mbar_wait(rb + sl * 8, (k & 1) ^ 1);
                        while ((int)(te - clk()) > 0) ;
                        raw_load(maps.m + isw, y, z, sd, rb + (3 + t) * 8);
                        TLJ(224 + isw * 10 + t);
                    }
                    __syncwarp();
                }
                asm volatile("barrier.cluster.wait.aligned;" ::: "memory");
                if (!k2 && !isw) {
#pragma unroll 1
                    for (int t = CFG_PFB; t < NBJ; t++) {
                        const int q = t * 16 + r - 160;
                        const char* p = qw + (((q >> 1) & 15) * 64 + lane) * (N_ * 4) + (c * TN + 320 + (q >> 5) * 64 + (q & 1) * 32) * 4;
                        const unsigned tp = t0 + sched(NAJ / NCL + 160 + q + CFG_PFO);
                        while ((int)(tp - clk()) > 0) ;
                        asm volatile("prefetch.global.L2 [%0];" :: "l"(p));
                        asm volatile("prefetch.global.L2 [%0];" :: "l"(p + 32 * N_ * 4));
                    }
                }
                if (!isw) cw = 2; else if (!k2 && CFG_AG) cw = 0;
                if (k2) {
                    const unsigned e0 = *(volatile unsigned*)&g_epoch[b];
                    if (!isw) {
                        if (lane < TN / 16) g_cs[(e0 & 1) ^ 1][r * (TN / 16) + lane] = 0;
                        const int u = lane * 2 + (r & 1);
                        const unsigned tg = (e0 + 1) * (u < 32 ? 5 : 4);
                        bool dn = u >= NU;
                        for (int it = 0;; it++) {
                            if (!dn && (int)(ld_flag(g_flag + 512 + u) - tg) >= 0) {
                                dn = true;
                                mbar_arrive(bars + (B_GO + lane) * 8);
                            }
                            if (__all_sync(~0u, dn)) break;
                            if (it > (1 << 22)) __trap();
                        }
                    } else {
                        const float zxf = __bfloat162float(__float2bfloat16_rn((float)__ldg(zero_x)));
#pragma unroll 1
                        for (int h = 0; h < 2; h++) {
                            for (int it = 0; (int)(ld_flag(g_flag + 576 + h) - (e0 + 1) * (h ? 32 : 160)) < 0; it++) if (it > (1 << 22)) __trap();
                            int2 v[5];
#pragma unroll
                            for (int j = 0; j < 5; j++) v[j] = __ldcg((const int2*)g_cs[e0 & 1] + min(h * 160 + j * 32 + lane, TN / 2 - 1));
#pragma unroll
                            for (int j = 0; j < 5; j++) {
                                const int i = h * 160 + j * 32 + lane;
                                const float lo = __bfloat162float(__float2bfloat16_rn((float)v[j].x)) * zxf;
                                const float hi = __bfloat162float(__float2bfloat16_rn((float)v[j].y)) * zxf;
                                uint32_t z;
                                asm("cvt.rn.bf16x2.f32 %0, %1, %2;" : "=r"(z) : "f"(hi), "f"(lo));
                                if (i < TN / 2 - 32)
                                    asm volatile("st.async.weak.shared::cluster.mbarrier::complete_tx::bytes.b32 [%0], %1, [%2];"
                                                 :: "r"(sb + SM_PAR + i * 4), "r"(z), "r"(bars + (B_PAR + (i < 128 ? i >> 6 : i < 160 ? (i >> 4) & 1 : (i >> 5) - 3)) * 8) : "memory");
                            }
                            if (lane == 0) TLREC(8 + h);
                        }
                    }
                }
            }
            if (!k2 && CFG_AG && warp == 10) cw = 1;
        }
            if (!k2 && r < NBJ && warp == (CFG_AG ? (r < 10 ? 8 : 15) : (r < 10 ? 8 : 10))) {
            const float zxf = __bfloat162float(__float2bfloat16_rn((float)__ldg(zero_x)));
            mbar_wait(bars + B_CS * 8);
            const int w = lane & 15;
            const uint32_t ca = sb + SM_CS + ((w >> 1) + (w & 1) * 16) * 4;
            const float lo = __bfloat162float(__float2bfloat16_rn((float)(int)lds32(ca))) * zxf;
            const float hi = __bfloat162float(__float2bfloat16_rn((float)(int)lds32(ca + 32))) * zxf;
            uint32_t z;
            asm("cvt.rn.bf16x2.f32 %0, %1, %2;" : "=r"(z) : "f"(hi), "f"(lo));
            const int piece = r < 10 ? (r >= 5) : (r - 6) >> 1;
#pragma unroll 1
            for (int i = lane >> 4; i < CS; i += 2)
                asm volatile("st.async.weak.shared::cluster.mbarrier::complete_tx::bytes.b32 [%0], %1, [%2];"
                             :: "r"(mapa(sb + SM_PAR + col_of(r) * 2 + w * 4, i)), "r"(z), "r"(mapa(bars + (B_PAR + piece) * 8, i)) : "memory");
            if (lane == 0) TLREC(8);
            }
#pragma unroll 1
            for (int n = (CFG_TAIL && !k2 && warp >= 14) ? warp - 2 : cw, k = 0; n < ((CFG_TAIL && warp < 14) ? 12 : NF); n += 3, k ^= 1) {
                const int gm = (int)(ford_table() >> (4 * n)), g = (gm >> 3) & 1, m = gm & 7;
                const int x = n >= 10 ? (n >> 1) * 64 : m == 4 ? 256 + g * 32 : g * 128 + (m & 1) * 64;
                const int y = n >= 10 ? (n & 1) * 64 : (m & 2) * 32;
                mbar_wait(bars + ((CFG_TAIL && n >= 12) ? B_GO + 2 + n : B_FILL + cw) * 8, k);
                if (!CFG_NOFENCE) asm volatile("fence.proxy.async.shared::cta;" ::: "memory");
                if (!(DBG & 2) && elect_one())
                    asm volatile("cp.async.bulk.tensor.2d.global.shared::cta.tile.bulk_group [%0, {%1, %2}], [%3];"
                                 :: "l"(maps.m + (n < 10 && m == 4 ? 3 : 2)), "r"(c * TN + x), "r"(r * 128 + y), "r"(sb + ((CFG_TAIL && n >= 12) ? SM_RING + (n - 7) * 8192 : SM_STG + ((cw + NBJ) % 3) * 8192)) : "memory");
                asm volatile("cp.async.bulk.commit_group;" ::: "memory");
                if (lane == 0) TLREC(32 + n);
                asm volatile("cp.async.bulk.wait_group.read 0;" ::: "memory");
                __syncwarp();
                if (n < NF - 3 && elect_one()) mbar_arrive(bars + (B_FREE + 3 + n) * 8);
                if (lane == 0) TLREC(48 + n);
            }
        if (CFG_TAIL && !k2) { if (lane == 0 && (warp >= 14 || cw == 2)) TLE_REC(b, warp >= 14 ? warp - 13 : 3); }
        else if (cw < 3 && lane == 0) TLE_REC(b, 1 + cw);
        TLEND();
    }
}

}

typedef CUresult (*EncodeFn)(CUtensorMap*, CUtensorMapDataType, cuuint32_t, void*, const cuuint64_t*, const cuuint64_t*,
                             const cuuint32_t*, const cuuint32_t*, CUtensorMapInterleave, CUtensorMapSwizzle,
                             CUtensorMapL2promotion, CUtensorMapFloatOOBfill);

extern "C" void kernel_launch(void* const* d_in, const int* in_sizes, int n_in, void* d_out, int out_size) {
    using namespace w8;
    static EncodeFn encode = nullptr;
    static cudaStream_t side;
    static cudaEvent_t started, joined;
    if (!encode) {
        void* fn = nullptr;
        cudaDriverEntryPointQueryResult qr;
        cudaGetDriverEntryPoint("cuTensorMapEncodeTiled", &fn, cudaEnableDefault, &qr);
        encode = (EncodeFn)fn;
        cudaStreamCreateWithFlags(&side, cudaStreamNonBlocking);
        cudaEventCreateWithFlags(&started, cudaEventDisableTiming);
        cudaEventCreateWithFlags(&joined, cudaEventDisableTiming);
        cudaFuncSetAttribute(w8a8_kernel<false>, cudaFuncAttributeMaxDynamicSharedMemorySize, SM_ALLOC);
        cudaFuncSetAttribute(w8a8_kernel<true>, cudaFuncAttributeMaxDynamicSharedMemorySize, SM_ALLOC);
        cudaFuncSetAttribute(w8a8_kernel<false>, cudaFuncAttributeNonPortableClusterSizeAllowed, 1);
    }
    Maps maps;
    {
        const cuuint64_t dim[3] = {32, K_ / 32, M_}, str[2] = {128, K_ * 4};
        const cuuint32_t box[3] = {32, 2, 32}, es[3] = {1, 1, 1};
        encode(&maps.m[0], CU_TENSOR_MAP_DATA_TYPE_INT32, 3, d_in[0], dim, str, box, es, CU_TENSOR_MAP_INTERLEAVE_NONE,
               CU_TENSOR_MAP_SWIZZLE_128B, CU_TENSOR_MAP_L2_PROMOTION_NONE, CU_TENSOR_MAP_FLOAT_OOB_FILL_NONE);
    }
    {
        const cuuint64_t dim[3] = {32, K_, N_ / 32}, str[2] = {N_ * 4, 128};
        const cuuint32_t box[3] = {32, 64, 1}, es[3] = {1, 1, 1};
        encode(&maps.m[1], CU_TENSOR_MAP_DATA_TYPE_INT32, 3, d_in[1], dim, str, box, es, CU_TENSOR_MAP_INTERLEAVE_NONE,
               CU_TENSOR_MAP_SWIZZLE_NONE, (CUtensorMapL2promotion)CFG_PROMO, CU_TENSOR_MAP_FLOAT_OOB_FILL_NONE);
    }
    {
        const cuuint64_t dim[2] = {N_, M_}, str[1] = {N_ * 2};
        const cuuint32_t box[2] = {WB, 64}, es[2] = {1, 1};
        encode(&maps.m[2], CU_TENSOR_MAP_DATA_TYPE_BFLOAT16, 2, d_out, dim, str, box, es, CU_TENSOR_MAP_INTERLEAVE_NONE,
               CU_TENSOR_MAP_SWIZZLE_128B, CU_TENSOR_MAP_L2_PROMOTION_NONE, CU_TENSOR_MAP_FLOAT_OOB_FILL_NONE);
    }
    {
        const cuuint64_t dim[2] = {N_, M_}, str[1] = {N_ * 2};
        const cuuint32_t box[2] = {32, 128}, es[2] = {1, 1};
        encode(&maps.m[3], CU_TENSOR_MAP_DATA_TYPE_BFLOAT16, 2, d_out, dim, str, box, es, CU_TENSOR_MAP_INTERLEAVE_NONE,
               CU_TENSOR_MAP_SWIZZLE_NONE, CU_TENSOR_MAP_L2_PROMOTION_NONE, CU_TENSOR_MAP_FLOAT_OOB_FILL_NONE);
    }
    for (int k = 0; k < ((DBG & 32) ? 1 : 2); k++) {
        cudaLaunchConfig_t cfg = {};
        cfg.gridDim = dim3(k ? 20 : NCTA); cfg.blockDim = dim3(512); cfg.dynamicSmemBytes = SM_ALLOC; cfg.stream = cudaStreamPerThread;
        cudaLaunchAttribute at[2];
        at[0].id = cudaLaunchAttributeClusterDimension; at[0].val.clusterDim.x = k ? 2 : CS; at[0].val.clusterDim.y = 1; at[0].val.clusterDim.z = 1;
        at[1].id = cudaLaunchAttributeProgrammaticStreamSerialization; at[1].val.programmaticStreamSerializationAllowed = 1;
        cfg.attrs = at; cfg.numAttrs = 1 + k;
        at[1].id = cudaLaunchAttributeLaunchCompletionEvent; at[1].val.launchCompletionEvent.event = started; at[1].val.launchCompletionEvent.flags = 0;
        cfg.numAttrs = 2 - k;
        if (k) { cudaStreamWaitEvent(side, started, 0); cfg.stream = side; }
        if (k && CFG_DOM) { at[1].id = cudaLaunchAttributeMemSyncDomain; at[1].val.memSyncDomain = cudaLaunchMemSyncDomainRemote; cfg.numAttrs = 2; }
        cudaLaunchKernelEx(&cfg, k ? w8a8_kernel<true> : w8a8_kernel<false>,
                           (const char*)d_in[0], (const char*)d_in[1], (const __nv_bfloat16*)d_in[2], (const int*)d_in[3], (const __nv_bfloat16*)d_in[4], (const __nv_bfloat16*)d_in[5]
                           , maps
                           );
        if (k) { cudaEventRecord(joined, side); cudaStreamWaitEvent(cudaStreamPerThread, joined, 0); }
    }
}
```

```cpp
#include <cuda_runtime.h>
#include <cuda.h>
#include <cuda_bf16.h>
#include <stdint.h>

#define CFG_X1 13
#define CFG_P1 46
#define CFG_P2 40
#define CFG_PT 100
#define CFG_L0 34
#define CFG_RA 33
#define CFG_T0 -300
#define CFG_Q0 14
#define CFG_Q2 63
#define CFG_Q3 30
#define CFG_T3 1000
#define CFG_D3 2
#define CFG_PF7 18
#define CFG_TA 10
#define CFG_HOLD 14
#define CFG_EPI 2

namespace w8 {

constexpr int M_ = 2048, K_ = 1024, N_ = 3584;
constexpr int CS = 16, NCL = 7, NCTA = CS * NCL;
constexpr int WA = 160, WB = 64, TN = 2 * WA + 2 * WB;
constexpr int X1 = CFG_X1;
constexpr int HOLD = CFG_HOLD;
constexpr int NSLOT = 7, SLOT = WA * 64;
constexpr int NAJ = 1024;
constexpr int REV = 60;
constexpr int TA = CFG_TA;

constexpr int L0 = CFG_L0, RA = CFG_RA, RB64 = 64 * RA / (RA - 16);
constexpr int P1 = CFG_P1, P2 = CFG_P2, PT = CFG_PT, T0 = CFG_T0;
__device__ __forceinline__ int time_x(int x) { return max(x, L0 + (((x - L0) * RA) >> 4)); }
__device__ __forceinline__ int time_w(int q) { return min(L0 + ((q * RB64) >> 6), NAJ / NCL + q); }
__device__ __forceinline__ unsigned sched(int T) { return T * P2 + min(T, PT) * (P1 - P2); }
__device__ __forceinline__ int sched2(int q) { return (min(q, 160) - CFG_Q0) * CFG_Q2 + max(q - 160, 0) * CFG_Q3; }

constexpr int SM_A = 0;
constexpr int SM_RING = 131072;
constexpr int SM_STG = SM_RING + NSLOT * SLOT;
constexpr int SM_PAR = SM_STG + 3 * 8192;
constexpr int SM_CS = SM_PAR + 3 * TN * 2;
constexpr int SM_BAR = SM_CS + 128;
constexpr int B_FULLB = 0, B_FULLA = 56, B_PAR = 72, B_SW = 77, B_AFREE = 74  , B_FREE = 90,
              B_GO = 104, B_FILL = 128, B_CS = 131, B_RAWA = 132, B_RAWB = 145, B_END = 163;
constexpr int SM_TOTAL = SM_BAR + B_END * 8;
static_assert(SM_TOTAL <= 232448, "");

__device__ uint4 g_s8[(1024 + 8 * 256) * 128];
constexpr int F_W = 512, F_CS = 576;
__device__ unsigned g_flag[608];
__device__ unsigned g_epoch[132];
__device__ int g_cs[2][TN];
__device__ int g_sink;

__device__ __forceinline__ void mbar_init(uint32_t bar, uint32_t cnt) {
    asm volatile("mbarrier.init.shared::cta.b64 [%0], %1;" :: "r"(bar), "r"(cnt) : "memory");
}
__device__ __forceinline__ void mbar_expect_tx(uint32_t bar, uint32_t bytes) {
    asm volatile("mbarrier.arrive.expect_tx.shared::cta.b64 _, [%0], %1;" :: "r"(bar), "r"(bytes) : "memory");
}
__device__ __forceinline__ void mbar_arrive(uint32_t bar) {
    asm volatile("mbarrier.arrive.shared::cta.b64 _, [%0];" :: "r"(bar) : "memory");
}
__device__ __forceinline__ void mbar_arrive_cluster(uint32_t bar) {
    asm volatile("mbarrier.arrive.shared::cluster.b64 _, [%0];" :: "r"(bar) : "memory");
}
__device__ __forceinline__ void mbar_wait(uint32_t bar, uint32_t parity = 0) {
    asm volatile("{\n.reg .pred p;\n.reg .u32 c;\n"
                 "mbarrier.try_wait.parity.shared::cta.b64 p, [%0], %1;\n"
                 "@p bra WAIT_DONE;\n"
                 "mov.u32 c, 0;\n"
                 "WAIT_LOOP:\n"
                 "mbarrier.try_wait.parity.shared::cta.b64 p, [%0], %1;\n"
                 "@p bra WAIT_DONE;\n"
                 "add.u32 c, c, 1;\nsetp.lt.u32 p, c, 0x100000;\n"
                 "@p bra WAIT_LOOP;\n"
                 "trap;\n"
                 "WAIT_DONE:\n}" :: "r"(bar), "r"(parity) : "memory");
}
__device__ __forceinline__ void mbar_wait2(uint32_t bar0, uint32_t bar1) {
    asm volatile("{\n.reg .pred p, q;\n.reg .u32 c;\nmov.u32 c, 0;\n"
                 "WAIT_LOOP:\n"
                 "mbarrier.try_wait.parity.shared::cta.b64 p, [%0], 0;\n"
                 "mbarrier.try_wait.parity.shared::cta.b64 q, [%1], 0;\n"
                 "and.pred p, p, q;\n"
                 "@p bra WAIT_DONE;\n"
                 "add.u32 c, c, 1;\nsetp.lt.u32 p, c, 0x100000;\n"
                 "@p bra WAIT_LOOP;\n"
                 "trap;\n"
                 "WAIT_DONE:\n}" :: "r"(bar0), "r"(bar1) : "memory");
}
__device__ __forceinline__ bool mbar_test(uint32_t bar) {
    uint32_t ok;
    asm volatile("{\n.reg .pred p;\nmbarrier.test_wait.parity.shared::cta.b64 p, [%1], 0;\nselp.u32 %0, 1, 0, p;\n}" : "=r"(ok) : "r"(bar) : "memory");
    return ok;
}
__device__ __forceinline__ bool mbar_test2(uint32_t bar0, uint32_t bar1) {
    uint32_t ok;
    asm volatile("{\n.reg .pred p, q;\nmbarrier.test_wait.parity.shared::cta.b64 p, [%1], 0;\n"
                 "mbarrier.test_wait.parity.shared::cta.b64 q, [%2], 0;\nand.pred p, p, q;\nselp.u32 %0, 1, 0, p;\n}"
                 : "=r"(ok) : "r"(bar0), "r"(bar1) : "memory");
    return ok;
}
__device__ __forceinline__ bool elect_one() {
    uint32_t ok;
    asm volatile("{\n.reg .pred p;\nelect.sync _|p, 0xffffffff;\nselp.u32 %0, 1, 0, p;\n}" : "=r"(ok));
    return ok;
}
__device__ __forceinline__ unsigned ld_flag(const unsigned* p) {
    unsigned v;
    asm volatile("ld.relaxed.gpu.global.u32 %0, [%1];" : "=r"(v) : "l"(p) : "memory");
    return v;
}
__device__ __forceinline__ uint4 lds128(uint32_t a) {
    uint4 v;
    asm volatile("ld.shared.v4.b32 {%0,%1,%2,%3}, [%4];" : "=r"(v.x), "=r"(v.y), "=r"(v.z), "=r"(v.w) : "r"(a) : "memory");
    return v;
}
__device__ __forceinline__ void sts128(uint32_t a, uint4 v) {
    asm volatile("st.shared.v4.b32 [%0], {%1,%2,%3,%4};" :: "r"(a), "r"(v.x), "r"(v.y), "r"(v.z), "r"(v.w) : "memory");
}
__device__ __forceinline__ uint32_t lds32(uint32_t a) {
    uint32_t v;
    asm volatile("ld.shared.b32 %0, [%1];" : "=r"(v) : "r"(a) : "memory");
    return v;
}
__device__ __forceinline__ void sts32(uint32_t a, uint32_t v) {
    asm volatile("st.shared.b32 [%0], %1;" :: "r"(a), "r"(v) : "memory");
}
__device__ __forceinline__ void stg128(void* p, uint4 v) {
    asm volatile("st.global.v4.b32 [%0], {%1,%2,%3,%4};" :: "l"(p), "r"(v.x), "r"(v.y), "r"(v.z), "r"(v.w) : "memory");
}
__device__ __forceinline__ unsigned pack4(unsigned a, unsigned b, unsigned c, unsigned d) {
    unsigned lo, r;
    asm("cvt.pack.sat.s8.s32.b32 %0, %1, %2, 0;" : "=r"(lo) : "r"(d), "r"(c));
    asm("cvt.pack.sat.s8.s32.b32 %0, %1, %2, %3;" : "=r"(r) : "r"(b), "r"(a), "r"(lo));
    return r;
}
__device__ __forceinline__ uint32_t mapa(uint32_t a, uint32_t r) {
    uint32_t o;
    asm("mapa.shared::cluster.u32 %0, %1, %2;" : "=r"(o) : "r"(a), "r"(r));
    return o;
}
__device__ __forceinline__ unsigned clk() {
    unsigned t;
    asm volatile("mov.u32 %0, %clock;" : "=r"(t));
    return t;
}
__device__ __forceinline__ void cluster_arrive() { asm volatile("barrier.cluster.arrive.relaxed.aligned;" ::: "memory"); }
__device__ __forceinline__ void cluster_wait() { asm volatile("barrier.cluster.wait.aligned;" ::: "memory"); }
__device__ __forceinline__ void fence_init() { asm volatile("fence.mbarrier_init.release.cluster;" ::: "memory"); }
__device__ __forceinline__ void flag_add(unsigned* p) { asm volatile("red.relaxed.gpu.global.add.u32 [%0], 1;" :: "l"(p) : "memory"); }
__device__ __forceinline__ void raw_load(const void* map, int y, int z, uint32_t dst, uint32_t bar) {
    asm volatile("cp.async.bulk.tensor.3d.shared::cluster.global.tile.mbarrier::complete_tx::bytes [%0], [%1, {0, %2, %3}], [%4];"
                 :: "r"(dst), "l"(map), "r"(y), "r"(z), "r"(bar) : "memory");
}
__device__ __forceinline__ void tile_load(uint32_t dst, int tile, uint32_t bar) {
    asm volatile("cp.async.bulk.shared::cluster.global.mbarrier::complete_tx::bytes [%0], [%1], %2, [%3];"
                 :: "r"(dst), "l"((const char*)g_s8 + tile * 8192), "r"(8192), "r"(bar) : "memory");
}
__device__ __forceinline__ void tile_store(const void* map, int x, int y, uint32_t src) {
    asm volatile("cp.async.bulk.tensor.2d.global.shared::cta.tile.bulk_group [%0, {%1, %2}], [%3];"
                 :: "l"(map), "r"(x), "r"(y), "r"(src) : "memory");
}
__device__ __forceinline__ void st_async(uint32_t a, uint32_t v, uint32_t bar) {
    asm volatile("st.async.weak.shared::cluster.mbarrier::complete_tx::bytes.b32 [%0], %1, [%2];" :: "r"(a), "r"(v), "r"(bar) : "memory");
}
__device__ __forceinline__ void red_async(uint32_t a, int v, uint32_t bar) {
    asm volatile("red.async.relaxed.cluster.shared::cluster.mbarrier::complete_tx::bytes.add.s32 [%0], %1, [%2];" :: "r"(a), "r"(v), "r"(bar) : "memory");
}
__device__ __forceinline__ void red_shared(uint32_t a, int v) { asm volatile("red.shared.add.s32 [%0], %1;" :: "r"(a), "r"(v) : "memory"); }
__device__ __forceinline__ int sum4(unsigned v, int c) { return __dp4a((int)v, 0x01010101, c); }

constexpr uint32_t DESC_A_HI = 0x80000000u | (512 >> 4);
constexpr uint32_t DESC_B_HI = 512 >> 4;
template <int NR> __device__ __forceinline__ void wgmma_n160(int (&d)[NR], uint32_t alo, uint32_t blo, int scale_d) {
    asm volatile("{\n.reg .pred p;\n.reg .b64 da, db;\nsetp.ne.b32 p, %82, 0;\n"
        "mov.b64 da, {%80, %83};\nmov.b64 db, {%81, %84};\n"
        "wgmma.mma_async.sync.aligned.m64n160k32.s32.s8.s8 "
        "{%0, %1, %2, %3, %4, %5, %6, %7, %8, %9, %10, %11, %12, %13, %14, %15, "
        "%16, %17, %18, %19, %20, %21, %22, %23, %24, %25, %26, %27, %28, %29, %30, %31, "
        "%32, %33, %34, %35, %36, %37, %38, %39, %40, %41, %42, %43, %44, %45, %46, %47, "
        "%48, %49, %50, %51, %52, %53, %54, %55, %56, %57, %58, %59, %60, %61, %62, %63, "
        "%64, %65, %66, %67, %68, %69, %70, %71, %72, %73, %74, %75, %76, %77, %78, %79}, "
        "da, db, p;\n}\n"
        : "+r"(d[0]), "+r"(d[1]), "+r"(d[2]), "+r"(d[3]), "+r"(d[4]), "+r"(d[5]), "+r"(d[6]), "+r"(d[7]),
          "+r"(d[8]), "+r"(d[9]), "+r"(d[10]), "+r"(d[11]), "+r"(d[12]), "+r"(d[13]), "+r"(d[14]), "+r"(d[15]),
          "+r"(d[16]), "+r"(d[17]), "+r"(d[18]), "+r"(d[19]), "+r"(d[20]), "+r"(d[21]), "+r"(d[22]), "+r"(d[23]),
          "+r"(d[24]), "+r"(d[25]), "+r"(d[26]), "+r"(d[27]), "+r"(d[28]), "+r"(d[29]), "+r"(d[30]), "+r"(d[31]),
          "+r"(d[32]), "+r"(d[33]), "+r"(d[34]), "+r"(d[35]), "+r"(d[36]), "+r"(d[37]), "+r"(d[38]), "+r"(d[39]),
          "+r"(d[40]), "+r"(d[41]), "+r"(d[42]), "+r"(d[43]), "+r"(d[44]), "+r"(d[45]), "+r"(d[46]), "+r"(d[47]),
          "+r"(d[48]), "+r"(d[49]), "+r"(d[50]), "+r"(d[51]), "+r"(d[52]), "+r"(d[53]), "+r"(d[54]), "+r"(d[55]),
          "+r"(d[56]), "+r"(d[57]), "+r"(d[58]), "+r"(d[59]), "+r"(d[60]), "+r"(d[61]), "+r"(d[62]), "+r"(d[63]),
          "+r"(d[64]), "+r"(d[65]), "+r"(d[66]), "+r"(d[67]), "+r"(d[68]), "+r"(d[69]), "+r"(d[70]), "+r"(d[71]),
          "+r"(d[72]), "+r"(d[73]), "+r"(d[74]), "+r"(d[75]), "+r"(d[76]), "+r"(d[77]), "+r"(d[78]), "+r"(d[79])
        : "r"(alo), "r"(blo), "r"(scale_d), "r"(DESC_A_HI), "r"(DESC_B_HI));
}
template <int NR> __device__ __forceinline__ void wgmma_t128(int (&d)[NR], uint32_t alo, uint32_t blo, int scale_d) {
    asm volatile("{\n.reg .pred p;\n.reg .b64 da, db;\nsetp.ne.b32 p, %66, 0;\n"
        "mov.b64 da, {%64, %67};\nmov.b64 db, {%65, %68};\n"
        "wgmma.mma_async.sync.aligned.m64n128k32.s32.s8.s8 "
        "{%0, %1, %2, %3, %4, %5, %6, %7, %8, %9, %10, %11, %12, %13, %14, %15, "
        "%16, %17, %18, %19, %20, %21, %22, %23, %24, %25, %26, %27, %28, %29, %30, %31, "
        "%32, %33, %34, %35, %36, %37, %38, %39, %40, %41, %42, %43, %44, %45, %46, %47, "
        "%48, %49, %50, %51, %52, %53, %54, %55, %56, %57, %58, %59, %60, %61, %62, %63}, "
        "da, db, p;\n}\n"
        : "+r"(d[0]), "+r"(d[1]), "+r"(d[2]), "+r"(d[3]), "+r"(d[4]), "+r"(d[5]), "+r"(d[6]), "+r"(d[7]),
          "+r"(d[8]), "+r"(d[9]), "+r"(d[10]), "+r"(d[11]), "+r"(d[12]), "+r"(d[13]), "+r"(d[14]), "+r"(d[15]),
          "+r"(d[16]), "+r"(d[17]), "+r"(d[18]), "+r"(d[19]), "+r"(d[20]), "+r"(d[21]), "+r"(d[22]), "+r"(d[23]),
          "+r"(d[24]), "+r"(d[25]), "+r"(d[26]), "+r"(d[27]), "+r"(d[28]), "+r"(d[29]), "+r"(d[30]), "+r"(d[31]),
          "+r"(d[32]), "+r"(d[33]), "+r"(d[34]), "+r"(d[35]), "+r"(d[36]), "+r"(d[37]), "+r"(d[38]), "+r"(d[39]),
          "+r"(d[40]), "+r"(d[41]), "+r"(d[42]), "+r"(d[43]), "+r"(d[44]), "+r"(d[45]), "+r"(d[46]), "+r"(d[47]),
          "+r"(d[48]), "+r"(d[49]), "+r"(d[50]), "+r"(d[51]), "+r"(d[52]), "+r"(d[53]), "+r"(d[54]), "+r"(d[55]),
          "+r"(d[56]), "+r"(d[57]), "+r"(d[58]), "+r"(d[59]), "+r"(d[60]), "+r"(d[61]), "+r"(d[62]), "+r"(d[63])
        : "r"(alo), "r"(blo), "r"(scale_d), "r"(DESC_B_HI), "r"(DESC_A_HI));
}


__device__ __forceinline__ void wg_fence() { asm volatile("wgmma.fence.sync.aligned;" ::: "memory"); }
__device__ __forceinline__ void wg_commit() { asm volatile("wgmma.commit_group.sync.aligned;" ::: "memory"); }
template <int N> __device__ __forceinline__ void wg_wait() { asm volatile("wgmma.wait_group.sync.aligned %0;" :: "n"(N) : "memory"); }

__host__ __device__ constexpr int unit_of(int piece, int slab) {
    return piece < 2 ? (slab < X1 ? 2 * slab + piece : (piece ? 16 : X1) + slab) : 32 + (piece - 2) * 8 + (slab >> 1);
}
__host__ __device__ constexpr int col_of(int G) { return G == 4 ? 256 : (G > 4 && G < 9) ? 32 * G - 32 : 32 * G; }
struct BJob { int u, slab, G, pos; };
__host__ __device__ constexpr BJob decode_b(int q) {
    BJob j = {};
    if (q < 160) {
        j.u = q / 5; j.pos = q - j.u * 5;
        const int piece = j.u < 2 * X1 ? (j.u & 1) : (j.u >= X1 + 16);
        j.slab = j.u < 2 * X1 ? (j.u >> 1) : j.u - (piece ? 16 : X1);
        j.G = piece * 5 + j.pos;
    } else {
        q -= 160;
        j.u = 32 + (q >> 2); j.pos = q & 3;
        j.slab = (q >> 1) & 15;
        j.G = 10 + (q >> 5) * 2 + (q & 1);
    }
    return j;
}
__host__ __device__ constexpr int fb_of(int u) {
    return u < 2 * X1 ? (u & 1) * 32 + (u >> 1) : u < X1 + 16 ? u - X1 : u < 32 ? 16 + u : u < 40 ? u - 16 : u < 48 ? u + 8 : u - 24;
}
__host__ __device__ constexpr uint64_t slot_table(int piece) {
    uint64_t t = 0;
    if (piece < 2) for (int s = 0; s < 16; s++) t |= (uint64_t)(unit_of(piece, s) % NSLOT) << (4 * s);
    else for (int s = 0; s < 8; s++) t |= (uint64_t)(unit_of(piece, 2 * s) % NSLOT) << (4 * s);
    return t;
}
template <bool k2> __device__ __forceinline__ int stage_w(int t) { return (k2 && t < 9) ? SM_A + (7 + t) * 8192 : SM_STG + (t % 3) * 8192; }
__host__ __device__ constexpr int ford(int g, int m) { return g ? (m < 2 ? 2 + 2 * m : 3 + m) : (m < 2 ? m : m < 3 ? 3 : 5 + m); }
__host__ __device__ constexpr uint64_t ford_table() {
    uint64_t t = 0;
    for (int g = 0; g < 2; g++) for (int m = 0; m < 5; m++) t |= (uint64_t)(g * 8 + m) << (4 * ford(g, m));
    return t;
}
struct Maps { CUtensorMap m[4]; };

__device__ __forceinline__ uint32_t bf2_mul(uint32_t a, uint32_t b) { asm("mul.rn.bf16x2 %0, %0, %1;" : "+r"(a) : "r"(b)); return a; }
__device__ __forceinline__ uint32_t epi(int a, int b, uint32_t zc, uint32_t sx, uint32_t sw, uint32_t bi) {
    uint32_t v;
    float fa = __int2float_rn(a), fb = __int2float_rn(b);
    asm("cvt.rn.bf16x2.f32 %0, %1, %2;" : "=r"(v) : "f"(fb), "f"(fa));
    asm("sub.rn.bf16x2 %0, %0, %1;" : "+r"(v) : "r"(zc));
    if (CFG_EPI == 0) {
        v = bf2_mul(bf2_mul(v, sx), sw);
        asm("add.rn.bf16x2 %0, %0, %1;" : "+r"(v) : "r"(bi));
    } else {
        asm("fma.rn.bf16x2 %0, %0, %1, %2;" : "+r"(v) : "r"(sw), "r"(bi));
    }
    return v;
}
__device__ __forceinline__ uint32_t zero_term(int lo, int hi, float zx) {
    uint32_t z;
    asm("cvt.rn.bf16x2.f32 %0, %1, %2;" : "=r"(z) : "f"(__bfloat162float(__float2bfloat16_rn((float)hi)) * zx),
                                                    "f"(__bfloat162float(__float2bfloat16_rn((float)lo)) * zx));
    return z;
}
__device__ __forceinline__ float ld_zx(const int* zero_x) { return __bfloat162float(__float2bfloat16_rn((float)__ldg(zero_x))); }
struct Par { uint4 zc, sw, bi; };
__device__ __forceinline__ Par ld_par(uint32_t p) { return {lds128(p), lds128(p + TN * 2), lds128(p + TN * 4)}; }
__device__ __forceinline__ uint4 epi_row(const int (&a)[WA / 2], int o, const Par& p, uint32_t sx2) {
    uint4 r;
    r.x = epi(a[o + 0], a[o + 4], p.zc.x, sx2, p.sw.x, p.bi.x);
    r.y = epi(a[o + 8], a[o + 12], p.zc.y, sx2, p.sw.y, p.bi.y);
    r.z = epi(a[o + 1], a[o + 5], p.zc.z, sx2, p.sw.z, p.bi.z);
    r.w = epi(a[o + 9], a[o + 13], p.zc.w, sx2, p.sw.w, p.bi.w);
    return r;
}
template <bool k2> __device__ __forceinline__ void release(uint32_t go, int u, int lane) {
    const int v = u + NSLOT;
    if (k2) {
        const int q = v + lane;
        if (lane < (v < 48 ? 1 : 0)) mbar_arrive_cluster(mapa(go + (q >> 1) * 8, q & 1));
    } else {
        const int q = 5 * v - (v > 34 ? 3 : 0) + lane;
        if (lane < (v > 38 ? 0 : v == 34 ? 2 : 5)) mbar_arrive_cluster(mapa(go + (q >> 4) * 8, q & 15));
    }
}
__device__ __forceinline__ unsigned read_back(const uint4* d, int lane) { return ld_flag((const unsigned*)(d - lane + ((lane + 10) & 15) * 8 + 6)); }
__device__ __forceinline__ void publish(unsigned rb, unsigned mine, unsigned* flag) {
    if (__shfl_sync(~0u, rb ^ mine, 6)) asm volatile("fence.acq_rel.gpu;" ::: "memory");
    if (elect_one()) flag_add(flag);
}
#define CV_B(m, f)                                                                                                      \
    {                                                                                                                   \
        uint4 v0 = lds128(rdB + m * 512), v1 = lds128(rdB + m * 512 + 128);                                             \
        uint4 v2 = lds128(rdB + m * 512 + 256), v3 = lds128(rdB + m * 512 + 384);                                       \
        o[0].f = pack4(v0.x, v1.x, v2.x, v3.x); o[1].f = pack4(v0.y, v1.y, v2.y, v3.y);                                 \
        o[2].f = pack4(v0.z, v1.z, v2.z, v3.z); o[3].f = pack4(v0.w, v1.w, v2.w, v3.w);                                 \
    }

__device__ __forceinline__ void last_columns(const Maps& maps, const __nv_bfloat16* scale_x, const int* zero_x, const __nv_bfloat16* scale_w,
                                             const __nv_bfloat16* bias, uint32_t sb, int warp, int lane, unsigned t0) {
    constexpr int C_FULL = 0, C_EMPTY = 32, C_RAW = 64, C_GO = 80, C_PEER = 81, D3 = CFG_D3;
    const uint32_t bars = sb + SM_BAR;
    const int j = blockIdx.x & 3;
    while ((int)(t0 + CFG_T3 - clk()) > 0) ;
    const int s0 = (j & 1) * 8 + (warp >> 1) * 2;
    if (warp < 8) {
        if (elect_one()) {
#pragma unroll
            for (int i = 0; i < 2; i++) {
                const uint32_t bar = bars + (C_RAW + warp * 2 + i) * 8;
                mbar_init(bar, 1); mbar_expect_tx(bar, 8192);
                raw_load(maps.m + 1, (s0 + (i ^ (j >> 1))) * 64, N_ / 32 - 2 + (warp & 1), sb + SM_A + (warp * 2 + i) * 8192, bar);
            }
#pragma unroll
            for (int i = 0; i < 4; i++) { mbar_init(bars + (C_FULL + warp * 4 + i) * 8, 1); mbar_expect_tx(bars + (C_FULL + warp * 4 + i) * 8, 16384); }
#pragma unroll
            for (int i = 0; i < 4; i++) mbar_init(bars + (C_EMPTY + warp * 4 + i) * 8, 4);
            if (warp == 0) {
                mbar_init(bars + C_GO * 8, 8);
                mbar_init(bars + C_PEER * 8, 1); mbar_expect_tx(bars + C_PEER * 8, 32768 + 4096);
            }
        }
        if (warp < 2) sts32(sb + SM_PAR + threadIdx.x * 4, 0);
        fence_init();
    }
    __syncthreads();
    cluster_arrive();
    cluster_wait();
    if (warp >= 8) {
        asm volatile("setmaxnreg.dec.sync.aligned.u32 40;");
        if (warp < 12) {
            const unsigned ep = (ld_flag(g_epoch + 128 + j) + 1) * 4;
            const int mb = j * 4 + warp - 8, wg = (warp >> 1) & 1;
            unsigned rdy = 0;
            mbar_wait(bars + (wg ? C_EMPTY : C_GO) * 8);
#pragma unroll 1
            for (int s = 0; s < 16; s++) {
                for (int it = 0; !((rdy >> s) & 1); it++) {
                    rdy = __ballot_sync(~0u, (int)(ld_flag(g_flag + mb * 32 + (lane & 15)) - ep) >= 0);
                    if (it > (1 << 22)) __trap();
                }
                if (s >= D3) mbar_wait(bars + (C_EMPTY + (s - D3) * 2 + wg) * 8);
                if (elect_one()) tile_load(sb + SM_A + ((s & 3) * 4 + warp - 8) * 8192, mb * 16 + s, bars + (C_FULL + s * 2 + wg) * 8);
            }
        }
    } else {
        asm volatile("setmaxnreg.inc.sync.aligned.u32 200;");
        const int wg = warp >> 2, w = warp & 3;
        const int c0 = (w >> 1) * 32 + (lane >> 2) * 4 + (w & 1) * 2, r0 = (lane & 3) * 2;
        const uint32_t sx2 = (uint32_t)__ldg((const unsigned short*)scale_x) * 0x10001u;
        uint32_t sw = __ldg((const unsigned*)(scale_w + N_ - WB + c0));
        const uint32_t bi = __ldg((const unsigned*)(bias + N_ - WB + c0));
        const float zxf = ld_zx(zero_x);
        int cs[4] = {0, 0, 0, 0};
        const uint32_t peer = mapa(sb, (j & 1) ^ 1);
#pragma unroll 1
        for (int i = 0; i < 2; i++) {
            const uint32_t rdB = sb + SM_A + (warp * 2 + i) * 8192 + (lane >> 3) * 2048 + (lane & 7) * 16;
            const uint32_t wr = SM_RING + (s0 + (i ^ (j >> 1))) * 4096 + (warp & 1) * 2048 + lane * 16;
            mbar_wait(bars + (C_RAW + warp * 2 + i) * 8);
            uint4 o[4];
            CV_B(0, x) CV_B(1, y) CV_B(2, z) CV_B(3, w)
#pragma unroll
            for (int k = 0; k < 4; k++) {
                sts128(sb + wr + k * 512, o[k]);
                asm volatile("st.async.weak.shared::cluster.mbarrier::complete_tx::bytes.v4.b32 [%0], {%1,%2,%3,%4}, [%5];"
                             :: "r"(peer + wr + k * 512), "r"(o[k].x), "r"(o[k].y), "r"(o[k].z), "r"(o[k].w), "r"(peer + SM_BAR + C_PEER * 8) : "memory");
                cs[k] = sum4(o[k].x, sum4(o[k].y, sum4(o[k].z, sum4(o[k].w, cs[k]))));
            }
        }
        __syncwarp();
        if (elect_one()) mbar_arrive(bars + C_GO * 8);
#pragma unroll
        for (int k = 0; k < 4; k++) {
            const uint32_t ca = SM_PAR + ((warp & 1) * 32 + (lane & 7) * 4 + k) * 4;
            red_shared(sb + ca, cs[k]);
            red_async(peer + ca, cs[k], peer + SM_BAR + C_PEER * 8);
        }
        mbar_wait(bars + C_PEER * 8);
        asm volatile("fence.proxy.async.shared::cta;" ::: "memory");
        asm volatile("bar.sync 1, 256;" ::: "memory");
        if (CFG_EPI) sw = bf2_mul(sw, sx2);
        const uint32_t zc = zero_term(lds32(sb + SM_PAR + c0 * 4), lds32(sb + SM_PAR + c0 * 4 + 4), zxf);
        const uint32_t sd = (sb & 0x3FFFF) >> 4;
        int t[2][64];
        wg_fence();
#pragma unroll 1
        for (int s = 0; s < 16; s++) {
            const uint32_t db = ((sd + (SM_RING >> 4)) | (8 << 16)) + s * 256, da = ((sd + (SM_A >> 4)) | (1 << 16)) + ((s & 3) * 4 + wg * 2) * 512;
            mbar_wait(bars + (C_FULL + s * 2 + wg) * 8);
            wgmma_t128(t[0], db, da, s);
            wgmma_t128(t[1], db, da + 512, s);
            wgmma_t128(t[0], db + 16, da + 2, 1);
            wgmma_t128(t[1], db + 16, da + 514, 1);
            wg_commit();
            wg_wait<0>();
            if (elect_one()) mbar_arrive(bars + (C_EMPTY + s * 2 + wg) * 8);
        }
        asm volatile("bar.sync %0, 128;" :: "r"(3 + wg) : "memory");
        const uint32_t st0 = sb + SM_A + wg * 16384 + r0 * 128 + (((c0 >> 3) ^ r0) << 4) + (c0 & 7) * 2;
#pragma unroll
        for (int h = 0; h < 4; h++) {
            const uint32_t off = (h >> 1) * 32768 + (h & 1) * 8192;
#pragma unroll
            for (int q = 0; q < 8; q++) {
                const int o = (h & 1) * 32 + q * 4;
                sts32(st0 + off + q * 1024, epi(t[h >> 1][o], t[h >> 1][o + 2], zc, sx2, sw, bi));
                sts32((st0 ^ (5 * 128 + 5 * 16)) + off + q * 1024, epi(t[h >> 1][o + 1], t[h >> 1][o + 3], zc, sx2, sw, bi));
            }
            asm volatile("fence.proxy.async.shared::cta;" ::: "memory");
            asm volatile("bar.sync %0, 128;" :: "r"(3 + wg) : "memory");
            if (w == 0 && elect_one()) tile_store(maps.m + 2, N_ - WB, j * 512 + wg * 256 + h * 64, sb + SM_A + wg * 16384 + off);
        }
        if (w == 0) {
            asm volatile("cp.async.bulk.commit_group;" ::: "memory");
            asm volatile("cp.async.bulk.wait_group.read 0;" ::: "memory");
        }
        asm volatile("bar.sync 1, 256;" ::: "memory");
        if (threadIdx.x == 0) flag_add(g_epoch + 128 + j);
    }
}

template <bool k2>
__global__ void __cluster_dims__(k2 ? 2 : CS, 1, 1) __launch_bounds__(512, 1)
w8a8_kernel(const char* __restrict__ qw, const __nv_bfloat16* __restrict__ scale_x, const int* __restrict__ zero_x,
            const __nv_bfloat16* __restrict__ scale_w, const __nv_bfloat16* __restrict__ bias, const __grid_constant__ Maps maps) {
    extern __shared__ __align__(1024) unsigned char smem_raw[];
    constexpr int NBJ = k2 ? 12 : 14, NF = NBJ, NU = k2 ? 40 : 48;
    const int b = blockIdx.x + (k2 ? NCTA : 0), r = b & 15, c = k2 ? NCL : b >> 4;
    const unsigned tc = clk();
    const uint32_t sb = (uint32_t)__cvta_generic_to_shared(smem_raw);
    const uint32_t bars = sb + SM_BAR;
    const unsigned tw = __shfl_sync(~0u, (tc & ~15u) | threadIdx.x >> 5, 0), t0 = tw + (k2 ? 0 : T0);
    const int warp = tw & 15, lane = threadIdx.x & 31;

    if (!k2 && warp == 12) {
        const int a = r * NCL + c;
        if (elect_one()) {
            mbar_init(bars + (B_RAWA + 3) * 8, 1);
            mbar_expect_tx(bars + (B_RAWA + 3) * 8, 8192);
            raw_load(maps.m, (a >> 6) * 2, ((a ^ REV) & 63) * 32, sb + SM_A + (a < NAJ % NCTA ? 15 : 13) * 8192, bars + (B_RAWA + 3) * 8);
        }
        __syncwarp();
    }
    if (warp == 9 && elect_one()) asm volatile("prefetch.tensormap [%0];" :: "l"(maps.m + 1) : "memory");
    if (k2 && blockIdx.x >= 16) {
        last_columns(maps, scale_x, zero_x, scale_w, bias, sb, warp, lane, t0);
        return;
    }
    if (warp >= 12) {
        if (!k2 && warp == 14 && elect_one()) { mbar_init(bars + (B_RAWB + 3) * 8, 1); mbar_expect_tx(bars + (B_RAWB + 3) * 8, 8192); }
        __syncwarp();
        cluster_arrive();
        const int t = k2 ? warp - 12 : warp & 1, isw = k2 || warp >= 14;
        const int x = t * 16 + r, a = (x * NCL + c) ^ REV, sx = (x * 26) >> 8;
        static_assert(X1 >= 7, "");
        const uint32_t bar = bars + ((isw ? B_RAWB : B_RAWA) + 3 + t) * 8;
        if (!k2 && warp == 15) cluster_wait();
        else if (!(!k2 && warp == 12) && elect_one()) {
            if (k2 || warp != 14) { mbar_init(bar, 1); mbar_expect_tx(bar, 8192); }
            const unsigned te = t0 + (k2 ? sched2(x) : (isw ? time_w(x) : time_x(x)) * P1);
            while ((int)(te - clk()) > 0) ;
            raw_load(maps.m + isw, isw ? sx * 64 : (a >> 6) * 2,
                     isw ? c * (TN / 32) + (int)((0x9765483210ull >> ((x - sx * 10) * 4)) & 15) : (a & 63) * 32,
                     sb + (k2 ? SM_A + 7 * 8192 : isw ? SM_STG : SM_A + 13 * 8192) + ((isw || r * NCL + c >= NAJ % NCTA) ? t : 2 - 2 * t) * 8192, bar);
        }
        __syncwarp();
    }
    if (warp < 8) {
        const uint32_t p = bars + warp * 104;
        if (elect_one()) {
#pragma unroll
            for (int i = 0; i < 13; i++) mbar_init(p + i * 8, (!k2 && ((warp == 6 && i == 12) || (warp == 7 && i < 2))) ? 2 : 1);
            static_assert(B_FREE == 90 && B_GO == 104, "");
        }
        __syncwarp();
        const int i = warp * 13 + lane;
        if (lane < 13 && i < B_SW) mbar_expect_tx(p + lane * 8, i >= B_PAR ? (i < B_PAR + 2 ? WA * 2 : WB * 2) : (i & 16) || i >= 48 ? 8192 : WA * 64);
        fence_init();
    }
    if (warp < 8 || warp == 10) cluster_arrive();
    if (!k2 && warp == 10 && lane < CFG_PF7) {
        const int n = b * CFG_PF7 + lane, row = n / 10;
        asm volatile("prefetch.global.L2 [%0];" :: "l"(qw + row * (N_ * 4) + NCL * TN * 4 + (n - row * 10) * 128));
    }

    if (warp < 8) {
        if (warp < 2 && elect_one()) asm volatile("prefetch.tensormap [%0];" :: "l"(maps.m + 2 + warp) : "memory");
        asm volatile("setmaxnreg.inc.sync.aligned.u32 200;");
        const int wg = warp >> 2;
        const uint32_t sd = (sb & 0x3FFFF) >> 4;
        const uint32_t sx2 = (uint32_t)__ldg((const unsigned short*)scale_x) * 0x10001u;
        const uint32_t par = sb + SM_PAR + (lane & 3) * 16 + wg * 256;
        const uint32_t go = bars + B_GO * 8;
        const int w = warp & 3, pq = (lane >> 2) ^ (lane & 4);
        uint32_t so = (w * 16 + pq) * 128 + (((lane & 3) ^ pq) << 4);
        const int c0 = (w >> 1) * 32 + (lane >> 2) * 4 + (w & 1) * 2, r0 = (lane & 3) * 2;
        uint32_t pp = sb + SM_PAR + (2 * WA + wg * WB + c0) * 2, st0 = r0 * 128 + (((c0 >> 3) ^ r0) << 4) + (c0 & 7) * 2;
        constexpr int rn = k2 ? 1 : 4;
        int rq = lane < rn ? rn * (32 + wg * 8 + (k2 ? NSLOT : 8)) + (k2 ? 0 : 32) + lane : 1000;
        asm volatile("" : "+r"(so), "+r"(pp), "+r"(st0), "+r"(rq));
        cluster_wait();
        int a0[WA / 2], a1[WA / 2];
        uint32_t barB = bars + (B_FULLB + wg * 32) * 8;
        wg_fence();
        {
            uint64_t tbl = wg ? slot_table(1) : slot_table(0);
            uint32_t da = (sd + (SM_A >> 4)) | (1 << 16);
            int up = 99;
            bool rdy = false;
#pragma unroll 1
            for (int s = 0; s < 16; s++) {
                const uint32_t db = ((sd + (SM_RING >> 4)) | (8 << 16)) + ((uint32_t)tbl & 15) * (SLOT >> 4);
                const bool hold = wg && s == X1;
                if (hold || (!rdy && !mbar_test2(bars + (B_FULLA + s) * 8, barB))) {
                    wg_wait<0>();
                    release<k2>(go, up, lane); up = 99;
                    mbar_wait2(bars + (B_FULLA + s) * 8, barB);
                    if (hold) asm volatile("bar.sync 7, 256;" ::: "memory");
                }
                wgmma_n160(a0, da, db, s);
                wgmma_n160(a1, da + 256, db, s);
                wg_commit();
                if (!wg && s == HOLD) asm volatile("bar.arrive 7, 256;" ::: "memory");
                wg_wait<1>();
                release<k2>(go, up, lane);
                wgmma_n160(a0, da + 2, db + 16, 1);
                wgmma_n160(a1, da + 258, db + 16, 1);
                wg_commit();
                up = s < X1 ? 2 * s + wg : (wg ? 16 : X1) + s;
                tbl >>= 4; da += 512; barB += 8;
                rdy = mbar_test2(bars + (B_FULLA + s + 1) * 8, barB);
                if (s < 15) wg_wait<1>();
            }
        }
        mbar_wait2(bars + (B_PAR + wg) * 8, bars + B_SW * 8);
        Par P = ld_par(par);
        wg_wait<0>();
        release<k2>(go, wg ? 31 : X1 + 15, lane);
        bool ready = mbar_test(barB);
#define FILL_BEGIN(n0, n1) mbar_wait(bars + (B_FREE + (wg ? n1 : n0)) * 8);                                             \
                           const uint32_t buf = sb + SM_STG + (wg ? (n1 + NBJ) % 3 : (n0 + NBJ) % 3) * 8192;
#define FILL_END(n0, n1) __syncwarp();                                                                                  \
                         if (elect_one()) mbar_arrive(bars + (B_FILL + (wg ? n1 % 3 : n0 % 3)) * 8);
#define FILL_PAIR(a, J, PN, m)                                                                                          \
        {                                                                                                               \
            const uint4 v0 = epi_row(a, J * 16, P, sx2);                                                                \
            const Par Q = ld_par(par + J * 64 + 64);                                                                    \
            const uint4 v1 = epi_row(a, J * 16 + 2, P, sx2);                                                            \
            FILL_BEGIN(ford(0, m), ford(1, m))                                                                          \
            sts128(buf + so, v0); sts128(buf + so + 1024, v1);                                                          \
            if ((PN) >= 0) P = ld_par(par + (PN));                                                                      \
            sts128(buf + (so ^ 64), epi_row(a, J * 16 + 16, Q, sx2));                                                   \
            sts128(buf + (so ^ 64) + 1024, epi_row(a, J * 16 + 18, Q, sx2));                                            \
            FILL_END(ford(0, m), ford(1, m))                                                                            \
        }
#define RELEASE_N() { if (rq < (k2 ? NU : NBJ * 16)) mbar_arrive_cluster(mapa(go + (rq >> rn) * 8, rq & ((1 << rn) - 1))); rq += rn; nrel++; }
#define NARROW(p)                                                                                                       \
        {                                                                                                               \
            uint32_t tbl = (uint32_t)slot_table(p), da = (sd + (SM_A >> 4)) | (1 << 16);                                \
            wg_fence();                                                                                                 \
            _Pragma("unroll 1") for (int i = 0; i < 8; i++) {                                                           \
                const uint32_t db = ((sd + (SM_RING >> 4)) | (8 << 16)) + (k2 ? (tbl & 15) * (SLOT >> 4) : ((i + 5) & 7) * 512); \
                if (!ready && !mbar_test(barB)) {                                                                       \
                    wg_wait<0>();                                                                                       \
                    if (p == 2) { _Pragma("unroll 1") while (nrel < i) RELEASE_N() }                                    \
                    mbar_wait(barB);                                                                                    \
                }                                                                                                       \
                _Pragma("unroll") for (int kk = 0; kk < 4; kk++)                                                        \
                    wgmma_t128(t, db + (kk >> 1) * 256 + (kk & 1) * 16, da + (kk >> 1) * 512 + (kk & 1) * 2, kk ? 1 : i); \
                wg_commit();                                                                                            \
                barB += 8;                                                                                              \
                ready = mbar_test(barB);                                                                                \
                if (p == 2 && nrel < i - 1) RELEASE_N()                                                                 \
                tbl >>= 4; da += 1024;                                                                                  \
                wg_wait<1>();                                                                                           \
            }                                                                                                           \
            if (p == 2) { if (nrel < 7) RELEASE_N() P = ld_par(par + 128); }                                            \
            else { mbar_wait(bars + (B_PAR + 3) * 8); zc = lds32(pp); sw = lds32(pp + TN * 2); bi = lds32(pp + TN * 4); } \
            wg_wait<0>();                                                                                               \
            if (p == 2) RELEASE_N()                                                                                     \
        }
        int nrel = 0;
        FILL_PAIR(a0, 0, 128, 0) FILL_PAIR(a0, 2, 0, 1)
        int t[64];
        uint32_t zc, sw, bi;
        FILL_PAIR(a1, 0, -1, 2)
        if (wg == 0) NARROW(2) else P = ld_par(par + 128);
        FILL_PAIR(a1, 2, 512 - wg * 192, 3)
        {
            const uint4 v0 = epi_row(a0, 64, P, sx2), v1 = epi_row(a0, 66, P, sx2);
            if (!wg) mbar_wait(bars + (B_PAR + 2) * 8);
            FILL_BEGIN(ford(0, 4), ford(1, 4))
            const uint32_t s4 = buf + ((so >> 1) & ~63u) + (lane & 3) * 16;
            sts128(s4, v0); sts128(s4 + 512, v1);
            sts128(s4 + 4096, epi_row(a1, 64, P, sx2)); sts128(s4 + 4608, epi_row(a1, 66, P, sx2));
            FILL_END(ford(0, 4), ford(1, 4))
        }
        if (!(k2 && wg)) {
            if (!k2 && wg == 1) NARROW(3) else { zc = lds32(pp); sw = lds32(pp + TN * 2); bi = lds32(pp + TN * 4); }
#define FILL_T(h)                                                                                                       \
            {                                                                                                           \
                FILL_BEGIN((10 + h), (12 + h))                                                                          \
                _Pragma("unroll") for (int j = 0; j < 8; j++) {                                                         \
                    const int o = h * 32 + j * 4;                                                                       \
                    sts32(buf + st0 + j * 1024, epi(t[o], t[o + 2], zc, sx2, sw, bi));                                  \
                    sts32(buf + (st0 ^ (5 * 128 + 5 * 16)) + j * 1024, epi(t[o + 1], t[o + 3], zc, sx2, sw, bi));       \
                }                                                                                                       \
                FILL_END((10 + h), (12 + h))                                                                            \
            }
            FILL_T(0) FILL_T(1)
        }
        if (threadIdx.x == 0) flag_add(g_epoch + b);
    } else {
        const int g = r * NCL + c, na = k2 ? 0 : NAJ / NCTA + (g < NAJ % NCTA);
        int cw = NF;
        if (warp >= 12) {
            asm volatile("setmaxnreg.dec.sync.aligned.u32 80;");
            if (warp < 14) {
                const int c4 = (lane ^ (lane >> 3)) & 3, ln = ((lane >> 2) ^ (lane & 4)) * 2 + (c4 >> 1);
                const uint32_t rd0 = sb + SM_A + 13 * 8192 + ln * 128 + ((((c4 & 1) << 2) ^ (ln & 7)) << 4);
#pragma unroll 1
                for (int t = warp - 12, sl = na == 9 ? t : 2 - 2 * t; t < na; t += 2, sl = sl ? sl - 1 : 2) {
                    const uint32_t rdA = rd0 + sl * 8192;
                    const int a = (t * NCTA + g) ^ REV, f = (a & 60) * 4 + (a >> 6);
                    uint4* const d = g_s8 + (f * 4 + (a & 3)) * 128 + lane;
                    uint4 o[4];
                    mbar_wait(bars + (B_RAWA + 3 + t) * 8);
#pragma unroll
                    for (int i = 0; i < 4; i++) {
                        uint4 v0 = lds128(rdA + i * 2048), v1 = lds128((rdA ^ 16) + i * 2048);
                        uint4 v2 = lds128((rdA ^ 32) + i * 2048), v3 = lds128((rdA ^ 48) + i * 2048);
                        o[i].x = pack4(v0.x, v0.y, v0.z, v0.w); o[i].y = pack4(v1.x, v1.y, v1.z, v1.w);
                        o[i].z = pack4(v2.x, v2.y, v2.z, v2.w); o[i].w = pack4(v3.x, v3.y, v3.z, v3.w);
                    }
#pragma unroll
                    for (int i = 0; i < 4; i++) stg128(d + i * 32, o[i]);
                    asm volatile("fence.proxy.async.global;" ::: "memory");
                    __syncwarp();
                    const unsigned rb = read_back(d, lane);
                    if (t < 2) cluster_wait();
                    if (elect_one()) mbar_arrive(bars + ((t < na - 3 ? B_RAWA : B_AFREE + 13) + sl) * 8);
                    publish(rb, o[0].x, g_flag + (a & 60) * 8 + (a >> 6));
                }
                cw = warp - 12;
            }
            if (!k2) {
                const int hw = warp & 1;
                const uint32_t rd0 = sb + SM_STG + hw * 4096 + (lane >> 3) * 1024 + (lane & 7) * 16;
                const int myG = decode_b((lane & 15) * 16 + r).G;
#pragma unroll 1
                for (int t = warp < 14 ? TA : 0; t < NBJ; t += warp < 14 ? NBJ : t == TA - 1 ? 2 : 1) {
                    const int sl = t % 3;
                    const uint32_t rdB = rd0 + sl * 8192;
                    char* const d = (char*)g_s8 + (1024 + c * 256 + t * 16 + r) * 2048 + hw * 256 + (lane >> 4) * 128 + (lane & 7) * 16 + (lane & 8);
                    uint2 o[4];
                    mbar_wait(bars + (B_RAWB + 3 + t) * 8);
                    CV_B(0, x) CV_B(1, y)
#pragma unroll
                    for (int i = 0; i < 4; i++) asm volatile("st.global.v2.b32 [%0], {%1,%2};" :: "l"(d + i * 512), "r"(o[i].x), "r"(o[i].y) : "memory");
                    if (t == 0 && warp == 14) cluster_wait();
                    if (elect_one()) mbar_arrive(bars + (t >= NBJ - 3 ? B_FREE + t - (NBJ - 3) : B_RAWB + sl) * 8);
                    asm volatile("fence.proxy.async.global;" ::: "memory");
                    __syncwarp();
                    if (elect_one()) mbar_arrive(bars + (B_GO + t) * 8);
                    int cs[4];
#pragma unroll
                    for (int i = 0; i < 4; i++) cs[i] = sum4(o[i].x, sum4(o[i].y, 0));
                    const int p01 = cs[0] + cs[1] * 65536, p23 = cs[2] + cs[3] * 65536;
                    const bool h = lane & 16;
                    int x = (h ? p23 : p01) + __shfl_xor_sync(~0u, h ? p01 : p23, 16);
                    x += __shfl_xor_sync(~0u, x, 8);
                    const int lo = (int)(short)x, v = (lane & 8) ? (x - lo) >> 16 : lo;
                    const int G = __shfl_sync(~0u, myG, t);
                    if (G != r) {
                        red_async(mapa(sb + SM_CS + lane * 4, G), v, mapa(bars + B_CS * 8, G));
                    } else {
                        red_shared(sb + SM_CS + lane * 4, v);
                        __syncwarp();
                        if (elect_one()) mbar_arrive(bars + B_CS * 8);
                    }
                }
            } else {
                const uint32_t rd0 = sb + (lane >> 3) * 2048 + (lane & 7) * 16;
                const BJob mb = decode_b((lane & 15) * 16 + r);
                const int myG = mb.G | mb.u << 8;
#pragma unroll 1
                for (int t = warp - 12; t < NBJ; t += 4) {
                    const uint32_t rdB = rd0 + stage_w<k2>(t);
                    uint4* const d = g_s8 + (1024 + c * 256 + t * 16 + r) * 128 + lane;
                    uint4 o[4];
                    mbar_wait(bars + (B_RAWB + 3 + t) * 8);
                    CV_B(0, x) CV_B(1, y) CV_B(2, z) CV_B(3, w)
#pragma unroll
                    for (int i = 0; i < 4; i++) stg128(d + i * 32, o[i]);
                    if (t < 4) cluster_wait();
                    if (elect_one()) mbar_arrive(bars + (B_FREE + t - (NBJ - 3)) * 8);
                    asm volatile("fence.proxy.async.global;" ::: "memory");
                    __syncwarp();
                    const unsigned rb = read_back(d, lane), ep = ld_flag(g_epoch + b);
                    int cs[4];
#pragma unroll
                    for (int i = 0; i < 4; i++) cs[i] = sum4(o[i].x, sum4(o[i].y, sum4(o[i].z, sum4(o[i].w, 0))));
                    const bool h = lane & 16, odd = lane & 8;
                    int x = (h ? cs[2] : cs[0]) + __shfl_xor_sync(~0u, h ? cs[0] : cs[2], 16);
                    int y = (h ? cs[3] : cs[1]) + __shfl_xor_sync(~0u, h ? cs[1] : cs[3], 16);
                    const int v = (odd ? y : x) + __shfl_xor_sync(~0u, odd ? x : y, 8);
                    const int gu = __shfl_sync(~0u, myG, t);
                    publish(rb, o[0].x, g_flag + F_W + (gu >> 8));
                    const int old = atomicAdd(g_cs[ep & 1] + col_of(gu & 255) + (lane & 7) * 4 + (lane >> 3), v);
                    if (old == 0x7FFFFFFF) g_sink = old;
                    __syncwarp();
                    if (elect_one()) flag_add(g_flag + F_CS + (t >= 10));
                }
            }
        } else {
            asm volatile("setmaxnreg.dec.sync.aligned.u32 32;");
            if (warp == 11) {
                if (elect_one()) {
#pragma unroll
                    for (int i = 0; i < (k2 ? NU / 2 : NBJ); i++)
                        mbar_init(bars + (B_GO + i) * 8, k2 ? (i * 2 + (r & 1) >= NSLOT ? 9 : 1) : (i * 16 + r >= NSLOT * 5 ? 2 + 4 * CS : 2));
#pragma unroll
                    for (int i = 0; i < 3; i++) mbar_init(bars + (B_FILL + i) * 8, 4);
                }
                const int u2 = lane * 2 + (r & 1), q = k2 ? (u2 < 32 ? 5 * u2 : 4 * u2 + 32) : (lane & 15) * 16 + r;
                const BJob bj = decode_b(q);
                unsigned seen = 0;
                if (!k2) {
                    const int nself = __popc(__ballot_sync(~0u, lane < NBJ && bj.G == r));
                    sts32(sb + SM_CS + lane * 4, 0);
                    if (lane == 0) {
                        mbar_init(bars + B_CS * 8, 1 + 2 * nself);
                        mbar_expect_tx(bars + B_CS * 8, (16 - nself) * 256);
                    }
                    seen = lds32(sb + SM_CS + lane * 4);
                }
                fence_init();
                asm volatile("barrier.cluster.arrive.relaxed.aligned;" :: "r"(seen) : "memory");
                const char* src = (const char*)g_s8 + (1024 + c * 256 + q) * 2048;
                const uint32_t dst = sb + SM_RING + ((!k2 && q >= 160) ? ((q + 20) & 31) * 2048 : (bj.u % NSLOT) * SLOT + bj.pos * 2048);
                const uint32_t fb = bars + (B_FULLB + fb_of(bj.u)) * 8;
                cluster_wait();
                {
                    const uint32_t sx2 = (uint32_t)__ldg((const unsigned short*)scale_x) * 0x10001u;
#pragma unroll
                    for (int i = lane; i < TN / 4; i += 32) {
                        const bool hi = i >= TN / 8;
                        uint4 v = __ldg((const uint4*)((hi ? bias : scale_w) + c * TN) + (hi ? i - TN / 8 : i));
                        if (CFG_EPI && !hi) v = {bf2_mul(v.x, sx2), bf2_mul(v.y, sx2), bf2_mul(v.z, sx2), bf2_mul(v.w, sx2)};
                        sts128(sb + SM_PAR + TN * 2 + i * 16, v);
                    }
                    __syncwarp();
                    if (elect_one()) mbar_arrive(bars + B_SW * 8);
                }
#pragma unroll 1
                for (int i = 0; i < (k2 ? NU / 2 : NBJ); i++) {
                    mbar_wait(bars + (B_GO + i) * 8);
                    if (lane == i) {
                        asm volatile("cp.async.bulk.shared::cluster.global.mbarrier::complete_tx::bytes.multicast::cluster [%0], [%1], %2, [%3], %4;"
                                     :: "r"(dst), "l"(src), "r"(k2 ? (u2 < 32 ? SLOT : 8192) : 2048), "r"(fb), "h"((uint16_t)(k2 ? 3 : 0xFFFF)) : "memory");
                    }
                    __syncwarp();
                }
            } else if (warp == 10) {
                const unsigned ep = (ld_flag(g_epoch + b) + 1) * 4;
                const unsigned* f = g_flag + r * 32 + (lane & 15);
                bool dn = lane >= 16;
                const bool fr = lane < (k2 ? 7 : 13);
                cluster_wait();
                for (int it = 0;; it++) {
                    const unsigned v = ld_flag(f);
                    if (!dn && (int)(v - ep) >= 0 && (fr || mbar_test(bars + (B_AFREE + lane) * 8))) {
                        dn = true;
                        tile_load(sb + SM_A + lane * 8192, r * 16 + lane, bars + (B_FULLA + lane) * 8);
                    }
                    if (__all_sync(~0u, dn)) break;
                    if (it > (1 << 22)) __trap();
                }
            } else {
                const bool isw = warp == 9;
                const uint32_t rb = bars + (isw ? B_RAWB : B_RAWA) * 8;
                if (elect_one()) {
#pragma unroll
                    for (int i = 0; i < 13; i++) if (i < 3 || i >= (k2 ? 7 : 5)) mbar_init(rb + i * 8, (i < 3 && isw && !k2) ? 2 : 1);
                    if (isw) {
#pragma unroll
                        for (int i = 13; i < 17; i++) mbar_init(rb + i * 8, 1);
                        if (!k2) mbar_init(rb + 4 * 8, 1);
                    }
                }
                __syncwarp();
                const int nj = isw ? NBJ : na, j0 = k2 ? 4 : isw ? 1 : 2;
                if (lane >= j0 && lane < nj) mbar_expect_tx(rb + (3 + lane) * 8, 8192);
                fence_init();
                cluster_arrive();
                const unsigned e0 = k2 ? ld_flag(g_epoch + b) : 0;
                const int k = lane / 3, x = lane * 16 + r;
                int sl = lane - k * 3, y, z, T;
                if (isw) {
                    const BJob bj = decode_b(x & 255);
                    y = bj.slab * 64; z = (c * TN + col_of(bj.G)) >> 5; T = time_w(x);
                } else {
                    const int a = (lane * NCTA + g) ^ REV;
                    y = (a >> 6) * 2; z = (a & 63) * 32; T = time_x(x);
                    if (na == 10) sl = sl ? sl - 1 : 2;
                }
                const unsigned te = t0 + (k2 ? sched2(x) : sched(T));
                const uint32_t sd = sb + (isw ? stage_w<k2>(lane) : SM_A + (13 + sl) * 8192);
#pragma unroll 1
                for (int t = j0; t < nj; t++) {
                    if (lane == t) {
                        if (t >= 3 && !k2) mbar_wait(rb + sl * 8, (k & 1) ^ 1);
                        while ((int)(te - clk()) > 0) ;
                        raw_load(maps.m + isw, y, z, sd, rb + (3 + t) * 8);
                    }
                    __syncwarp();
                }
                cluster_wait();
                if (!isw) cw = 2;
                if (k2) {
                    if (!isw) {
                        if (lane < TN / 16) g_cs[(e0 & 1) ^ 1][r * (TN / 16) + lane] = 0;
                        const int u = lane * 2 + (r & 1);
                        const unsigned tg = (e0 + 1) * (u < 32 ? 5 : 4);
                        bool dn = u >= NU;
                        for (int it = 0;; it++) {
                            if (!dn && (int)(ld_flag(g_flag + F_W + u) - tg) >= 0) {
                                dn = true;
                                mbar_arrive(bars + (B_GO + lane) * 8);
                            }
                            if (__all_sync(~0u, dn)) break;
                            if (it > (1 << 22)) __trap();
                        }
                    } else {
                        const float zxf = ld_zx(zero_x);
#pragma unroll 1
                        for (int h = 0; h < 2; h++) {
                            for (int it = 0; (int)(ld_flag(g_flag + F_CS + h) - (e0 + 1) * (h ? 32 : 160)) < 0; it++) if (it > (1 << 22)) __trap();
                            int2 v[5];
#pragma unroll
                            for (int j = 0; j < 5; j++) v[j] = __ldcg((const int2*)g_cs[e0 & 1] + min(h * 160 + j * 32 + lane, TN / 2 - 1));
#pragma unroll
                            for (int j = 0; j < 5; j++) {
                                const int i = h * 160 + j * 32 + lane;
                                const uint32_t z = zero_term(v[j].x, v[j].y, zxf);
                                if (i < TN / 2 - 32) st_async(sb + SM_PAR + i * 4, z, bars + (B_PAR + (i < 128 ? i >> 6 : i < 160 ? (i >> 4) & 1 : 2)) * 8);
                            }
                        }
                    }
                }
            }
        }
        if (!k2 && r < NBJ && warp == (r < 10 ? 8 : 10)) {
            const float zxf = ld_zx(zero_x);
            mbar_wait(bars + B_CS * 8);
            const int w = lane & 15;
            const uint32_t ca = sb + SM_CS + ((w >> 1) + (w & 1) * 16) * 4;
            const uint32_t z = zero_term(lds32(ca), lds32(ca + 32), zxf);
            const int piece = r < 10 ? (r >= 5) : (r - 6) >> 1;
#pragma unroll 1
            for (int i = lane >> 4; i < CS; i += 2) st_async(mapa(sb + SM_PAR + col_of(r) * 2 + w * 4, i), z, mapa(bars + (B_PAR + piece) * 8, i));
        }
#pragma unroll 1
        for (int n = cw, k = 0; n < NF; n += 3, k ^= 1) {
            const int gm = (int)(ford_table() >> (4 * n)), g = (gm >> 3) & 1, m = gm & 7;
            const int x = n >= 10 ? (n >> 1) * 64 : m == 4 ? 256 + g * 32 : g * 128 + (m & 1) * 64;
            const int y = n >= 10 ? (n & 1) * 64 : (m & 2) * 32;
            mbar_wait(bars + (B_FILL + cw) * 8, k);
            asm volatile("fence.proxy.async.shared::cta;" ::: "memory");
            if (elect_one()) tile_store(maps.m + (n < 10 && m == 4 ? 3 : 2), c * TN + x, r * 128 + y, sb + SM_STG + ((cw + NBJ) % 3) * 8192);
            asm volatile("cp.async.bulk.commit_group;" ::: "memory");
            asm volatile("cp.async.bulk.wait_group.read 0;" ::: "memory");
            __syncwarp();
            if (n < NF - 3 && elect_one()) mbar_arrive(bars + (B_FREE + 3 + n) * 8);
        }
    }
}

__global__ void __launch_bounds__(256)
w8a8_plain(const int* __restrict__ qx, const int* __restrict__ qw, const __nv_bfloat16* __restrict__ scale_x, const int* __restrict__ zero_x,
           const __nv_bfloat16* __restrict__ scale_w, const __nv_bfloat16* __restrict__ bias, __nv_bfloat16* __restrict__ out) {
    __shared__ int xs[16][K_ / 4];
    const int n = (blockIdx.x * 256 + threadIdx.x) * 2, m0 = blockIdx.y * 16;
    for (int i = threadIdx.x; i < 16 * K_ / 4; i += 256) {
        const uint4 v = ((const uint4*)qx)[m0 * (K_ / 4) + i];
        xs[i / (K_ / 4)][i % (K_ / 4)] = pack4(v.x, v.y, v.z, v.w);
    }
    __syncthreads();
    int acc[16][2] = {}, cs[2] = {};
    for (int k = 0; k < K_ / 4; k++) {
        uint2 v[4];
#pragma unroll
        for (int i = 0; i < 4; i++) v[i] = *(const uint2*)(qw + (k * 4 + i) * N_ + n);
        const unsigned w0 = pack4(v[0].x, v[1].x, v[2].x, v[3].x), w1 = pack4(v[0].y, v[1].y, v[2].y, v[3].y);
        cs[0] = sum4(w0, cs[0]); cs[1] = sum4(w1, cs[1]);
#pragma unroll
        for (int i = 0; i < 16; i++) { acc[i][0] = __dp4a(xs[i][k], (int)w0, acc[i][0]); acc[i][1] = __dp4a(xs[i][k], (int)w1, acc[i][1]); }
    }
    const uint32_t sx2 = (uint32_t)*(const unsigned short*)scale_x * 0x10001u, zc = zero_term(cs[0], cs[1], ld_zx(zero_x));
    uint32_t sw = *(const unsigned*)(scale_w + n);
    if (CFG_EPI) sw = bf2_mul(sw, sx2);
#pragma unroll
    for (int i = 0; i < 16; i++) *(unsigned*)(out + (m0 + i) * N_ + n) = epi(acc[i][0], acc[i][1], zc, sx2, sw, *(const unsigned*)(bias + n));
}

}

typedef CUresult (*EncodeFn)(CUtensorMap*, CUtensorMapDataType, cuuint32_t, void*, const cuuint64_t*, const cuuint64_t*,
                             const cuuint32_t*, const cuuint32_t*, CUtensorMapInterleave, CUtensorMapSwizzle,
                             CUtensorMapL2promotion, CUtensorMapFloatOOBfill);

extern "C" void kernel_launch(void* const* d_in, const int* in_sizes, int n_in, void* d_out, int out_size) {
    using namespace w8;
    static EncodeFn encode = nullptr;
    static cudaStream_t side;
    static cudaEvent_t started, joined;
    static int clusters = -1;
    cudaLaunchConfig_t cfg = {};
    cfg.gridDim = dim3(NCTA); cfg.blockDim = dim3(512); cfg.dynamicSmemBytes = SM_TOTAL; cfg.stream = cudaStreamPerThread;
    if (clusters < 0) {
        void* fn = nullptr;
        cudaDriverEntryPointQueryResult qr;
        cudaGetDriverEntryPoint("cuTensorMapEncodeTiled", &fn, cudaEnableDefault, &qr);
        encode = (EncodeFn)fn;
        cudaStreamCreateWithFlags(&side, cudaStreamNonBlocking);
        cudaEventCreateWithFlags(&started, cudaEventDisableTiming);
        cudaEventCreateWithFlags(&joined, cudaEventDisableTiming);
        cudaFuncSetAttribute(w8a8_kernel<false>, cudaFuncAttributeMaxDynamicSharedMemorySize, SM_TOTAL);
        cudaFuncSetAttribute(w8a8_kernel<true>, cudaFuncAttributeMaxDynamicSharedMemorySize, SM_TOTAL);
        cudaFuncSetAttribute(w8a8_kernel<false>, cudaFuncAttributeNonPortableClusterSizeAllowed, 1);
        if (cudaOccupancyMaxActiveClusters(&clusters, w8a8_kernel<false>, &cfg) != cudaSuccess) { clusters = 0; cudaGetLastError(); }
    }
    const __nv_bfloat16 *sx = (const __nv_bfloat16*)d_in[2], *sw = (const __nv_bfloat16*)d_in[4], *bias = (const __nv_bfloat16*)d_in[5];
    const int* zx = (const int*)d_in[3];
    if (clusters < NCL) {
        w8a8_plain<<<dim3(N_ / 512, M_ / 16), 256, 0, cudaStreamPerThread>>>((const int*)d_in[0], (const int*)d_in[1], sx, zx, sw, bias, (__nv_bfloat16*)d_out);
        return;
    }
    Maps maps;
    const cuuint32_t es[3] = {1, 1, 1};
    {
        const cuuint64_t dim[3] = {32, K_ / 32, M_}, str[2] = {128, K_ * 4};
        const cuuint32_t box[3] = {32, 2, 32};
        encode(&maps.m[0], CU_TENSOR_MAP_DATA_TYPE_INT32, 3, d_in[0], dim, str, box, es, CU_TENSOR_MAP_INTERLEAVE_NONE,
               CU_TENSOR_MAP_SWIZZLE_128B, CU_TENSOR_MAP_L2_PROMOTION_NONE, CU_TENSOR_MAP_FLOAT_OOB_FILL_NONE);
    }
    {
        const cuuint64_t dim[3] = {32, K_, N_ / 32}, str[2] = {N_ * 4, 128};
        const cuuint32_t box[3] = {32, 64, 1};
        encode(&maps.m[1], CU_TENSOR_MAP_DATA_TYPE_INT32, 3, d_in[1], dim, str, box, es, CU_TENSOR_MAP_INTERLEAVE_NONE,
               CU_TENSOR_MAP_SWIZZLE_NONE, CU_TENSOR_MAP_L2_PROMOTION_NONE, CU_TENSOR_MAP_FLOAT_OOB_FILL_NONE);
    }
    for (int i = 0; i < 2; i++) {
        const cuuint64_t dim[2] = {N_, M_}, str[1] = {N_ * 2};
        const cuuint32_t box[2] = {i ? 32u : 64u, i ? 128u : 64u};
        encode(&maps.m[2 + i], CU_TENSOR_MAP_DATA_TYPE_BFLOAT16, 2, d_out, dim, str, box, es, CU_TENSOR_MAP_INTERLEAVE_NONE,
               i ? CU_TENSOR_MAP_SWIZZLE_NONE : CU_TENSOR_MAP_SWIZZLE_128B, CU_TENSOR_MAP_L2_PROMOTION_NONE, CU_TENSOR_MAP_FLOAT_OOB_FILL_NONE);
    }
    cudaLaunchAttribute at;
    at.id = cudaLaunchAttributeLaunchCompletionEvent;
    at.val.launchCompletionEvent.event = started; at.val.launchCompletionEvent.flags = 0;
    cfg.attrs = &at; cfg.numAttrs = 1;
    cudaLaunchKernelEx(&cfg, w8a8_kernel<false>, (const char*)d_in[1], sx, zx, sw, bias, maps);
    cudaStreamWaitEvent(side, started, 0);
    cfg.gridDim = dim3(20); cfg.stream = side; cfg.numAttrs = 0;
    cudaLaunchKernelEx(&cfg, w8a8_kernel<true>, (const char*)d_in[1], sx, zx, sw, bias, maps);
    cudaEventRecord(joined, side);
    cudaStreamWaitEvent(cudaStreamPerThread, joined, 0);
}
```

```cpp
#include <cuda_runtime.h>
#include <cuda.h>
#include <cuda_bf16.h>
#include <stdint.h>
#include <stddef.h>

#define CFG_X1 13
#define CFG_P1 46
#define CFG_P2 39
#define CFG_PT 100
#define CFG_L0 34
#define CFG_RA 33
#define CFG_T0 -310
#define CFG_Q0 14
#define CFG_Q2 65
#define CFG_Q3 30
#define CFG_T3 400
#define CFG_D3 2
#define CFG_PF7 18
#define CFG_TA 10
#define CFG_HOLD 14
#define CFG_EPI 2

namespace w8 {

constexpr int M_ = 2048, K_ = 1024, N_ = 3584;
constexpr int CS = 16, NCL = 7, NCTA = CS * NCL;
constexpr int WA = 160, WB = 64, TN = 2 * WA + 2 * WB;
constexpr int X1 = CFG_X1;
constexpr int HOLD = CFG_HOLD;
constexpr int NSLOT = 7, SLOT = WA * 64;
constexpr int NAJ = 1024;
constexpr int REV = 60;
constexpr int TA = CFG_TA;

constexpr int L0 = CFG_L0, RA = CFG_RA, RB64 = 64 * RA / (RA - 16);
constexpr int P1 = CFG_P1, P2 = CFG_P2, PT = CFG_PT, T0 = CFG_T0;
__device__ __forceinline__ int time_x(int x) { return max(x, L0 + (((x - L0) * RA) >> 4)); }
__device__ __forceinline__ int time_w(int q) { return min(L0 + ((q * RB64) >> 6), NAJ / NCL + q); }
__device__ __forceinline__ unsigned sched(int T) { return T * P2 + min(T, PT) * (P1 - P2); }
__device__ __forceinline__ int sched2(int q) { return (min(q, 160) - CFG_Q0) * CFG_Q2 + max(q - 160, 0) * CFG_Q3; }

constexpr int SM_A = 0;
constexpr int SM_RING = 131072;
constexpr int SM_STG = SM_RING + NSLOT * SLOT;
constexpr int SM_PAR = SM_STG + 3 * 8192;
constexpr int SM_CS = SM_PAR + 3 * TN * 2;
constexpr int SM_BAR = SM_CS + 128;
constexpr int B_FULLB = 0, B_FULLA = 56, B_PAR = 72, B_SW = 77, B_AFREE = 74  , B_FREE = 90,
              B_GO = 104, B_FILL = 128, B_CS = 131, B_RAWA = 132, B_RAWB = 145, B_END = 163;
constexpr int SM_TOTAL = SM_BAR + B_END * 8;
static_assert(SM_TOTAL <= 232448, "");

constexpr int F_W = 512, F_CS = 576;
struct Scratch {
    unsigned flag[768];
    int cs[2][TN];
    int sink[384];
    uint4 s8[(1024 + 8 * 256) * 128];
};
static_assert(offsetof(Scratch, s8) == 8192, "");
__device__ __align__(8192) Scratch g_scratch;
__device__ __forceinline__ unsigned* epoch(Scratch* sc, int r, int c) { return sc->flag + r * 32 + 16 + c; }

__device__ __forceinline__ void mbar_init(uint32_t bar, uint32_t cnt) {
    asm volatile("mbarrier.init.shared::cta.b64 [%0], %1;" :: "r"(bar), "r"(cnt) : "memory");
}
__device__ __forceinline__ void mbar_expect_tx(uint32_t bar, uint32_t bytes) {
    asm volatile("mbarrier.arrive.expect_tx.shared::cta.b64 _, [%0], %1;" :: "r"(bar), "r"(bytes) : "memory");
}
__device__ __forceinline__ void mbar_arrive(uint32_t bar) {
    asm volatile("mbarrier.arrive.shared::cta.b64 _, [%0];" :: "r"(bar) : "memory");
}
__device__ __forceinline__ void mbar_arrive_cluster(uint32_t bar) {
    asm volatile("mbarrier.arrive.shared::cluster.b64 _, [%0];" :: "r"(bar) : "memory");
}
__device__ __forceinline__ void mbar_wait(uint32_t bar, uint32_t parity = 0) {
    asm volatile("{\n.reg .pred p;\n.reg .u32 c;\n"
                 "mbarrier.try_wait.parity.shared::cta.b64 p, [%0], %1;\n"
                 "@p bra WAIT_DONE;\n"
                 "mov.u32 c, 0;\n"
                 "WAIT_LOOP:\n"
                 "mbarrier.try_wait.parity.shared::cta.b64 p, [%0], %1;\n"
                 "@p bra WAIT_DONE;\n"
                 "add.u32 c, c, 1;\nsetp.lt.u32 p, c, 0x100000;\n"
                 "@p bra WAIT_LOOP;\n"
                 "trap;\n"
                 "WAIT_DONE:\n}" :: "r"(bar), "r"(parity) : "memory");
}
__device__ __forceinline__ void mbar_wait2(uint32_t bar0, uint32_t bar1) {
    asm volatile("{\n.reg .pred p, q;\n.reg .u32 c;\nmov.u32 c, 0;\n"
                 "WAIT_LOOP:\n"
                 "mbarrier.try_wait.parity.shared::cta.b64 p, [%0], 0;\n"
                 "mbarrier.try_wait.parity.shared::cta.b64 q, [%1], 0;\n"
                 "and.pred p, p, q;\n"
                 "@p bra WAIT_DONE;\n"
                 "add.u32 c, c, 1;\nsetp.lt.u32 p, c, 0x100000;\n"
                 "@p bra WAIT_LOOP;\n"
                 "trap;\n"
                 "WAIT_DONE:\n}" :: "r"(bar0), "r"(bar1) : "memory");
}
__device__ __forceinline__ bool mbar_test(uint32_t bar) {
    uint32_t ok;
    asm volatile("{\n.reg .pred p;\nmbarrier.test_wait.parity.shared::cta.b64 p, [%1], 0;\nselp.u32 %0, 1, 0, p;\n}" : "=r"(ok) : "r"(bar) : "memory");
    return ok;
}
__device__ __forceinline__ bool mbar_test2(uint32_t bar0, uint32_t bar1) {
    uint32_t ok;
    asm volatile("{\n.reg .pred p, q;\nmbarrier.test_wait.parity.shared::cta.b64 p, [%1], 0;\n"
                 "mbarrier.test_wait.parity.shared::cta.b64 q, [%2], 0;\nand.pred p, p, q;\nselp.u32 %0, 1, 0, p;\n}"
                 : "=r"(ok) : "r"(bar0), "r"(bar1) : "memory");
    return ok;
}
__device__ __forceinline__ bool elect_one() {
    uint32_t ok;
    asm volatile("{\n.reg .pred p;\nelect.sync _|p, 0xffffffff;\nselp.u32 %0, 1, 0, p;\n}" : "=r"(ok));
    return ok;
}
__device__ __forceinline__ unsigned ld_flag(const unsigned* p) {
    unsigned v;
    asm volatile("ld.relaxed.gpu.global.u32 %0, [%1];" : "=r"(v) : "l"(p) : "memory");
    return v;
}
__device__ __forceinline__ uint4 lds128(uint32_t a) {
    uint4 v;
    asm volatile("ld.shared.v4.b32 {%0,%1,%2,%3}, [%4];" : "=r"(v.x), "=r"(v.y), "=r"(v.z), "=r"(v.w) : "r"(a) : "memory");
    return v;
}
__device__ __forceinline__ void sts128(uint32_t a, uint4 v) {
    asm volatile("st.shared.v4.b32 [%0], {%1,%2,%3,%4};" :: "r"(a), "r"(v.x), "r"(v.y), "r"(v.z), "r"(v.w) : "memory");
}
__device__ __forceinline__ uint32_t lds32(uint32_t a) {
    uint32_t v;
    asm volatile("ld.shared.b32 %0, [%1];" : "=r"(v) : "r"(a) : "memory");
    return v;
}
__device__ __forceinline__ void sts32(uint32_t a, uint32_t v) {
    asm volatile("st.shared.b32 [%0], %1;" :: "r"(a), "r"(v) : "memory");
}
__device__ __forceinline__ void stg128(void* p, uint4 v) {
    asm volatile("st.global.v4.b32 [%0], {%1,%2,%3,%4};" :: "l"(p), "r"(v.x), "r"(v.y), "r"(v.z), "r"(v.w) : "memory");
}
__device__ __forceinline__ unsigned pack4(unsigned a, unsigned b, unsigned c, unsigned d) {
    unsigned lo, r;
    asm("cvt.pack.sat.s8.s32.b32 %0, %1, %2, 0;" : "=r"(lo) : "r"(d), "r"(c));
    asm("cvt.pack.sat.s8.s32.b32 %0, %1, %2, %3;" : "=r"(r) : "r"(b), "r"(a), "r"(lo));
    return r;
}
__device__ __forceinline__ uint32_t mapa(uint32_t a, uint32_t r) {
    uint32_t o;
    asm("mapa.shared::cluster.u32 %0, %1, %2;" : "=r"(o) : "r"(a), "r"(r));
    return o;
}
__device__ __forceinline__ unsigned clk() {
    unsigned t;
    asm volatile("mov.u32 %0, %clock;" : "=r"(t));
    return t;
}
__device__ __forceinline__ void cluster_arrive() { asm volatile("barrier.cluster.arrive.relaxed.aligned;" ::: "memory"); }
__device__ __forceinline__ void cluster_wait() { asm volatile("barrier.cluster.wait.aligned;" ::: "memory"); }
__device__ __forceinline__ void fence_init() { asm volatile("fence.mbarrier_init.release.cluster;" ::: "memory"); }
__device__ __forceinline__ void flag_add(unsigned* p) { asm volatile("red.relaxed.gpu.global.add.u32 [%0], 1;" :: "l"(p) : "memory"); }
__device__ __forceinline__ void raw_load(const void* map, int y, int z, uint32_t dst, uint32_t bar) {
    asm volatile("cp.async.bulk.tensor.3d.shared::cluster.global.tile.mbarrier::complete_tx::bytes [%0], [%1, {0, %2, %3}], [%4];"
                 :: "r"(dst), "l"(map), "r"(y), "r"(z), "r"(bar) : "memory");
}
__device__ __forceinline__ void tile_load(Scratch* sc, uint32_t dst, int tile, uint32_t bar) {
    asm volatile("cp.async.bulk.shared::cluster.global.mbarrier::complete_tx::bytes [%0], [%1], %2, [%3];"
                 :: "r"(dst), "l"((const char*)sc->s8 + tile * 8192), "r"(8192), "r"(bar) : "memory");
}
__device__ __forceinline__ void tile_store(const void* map, int x, int y, uint32_t src) {
    asm volatile("cp.async.bulk.tensor.2d.global.shared::cta.tile.bulk_group [%0, {%1, %2}], [%3];"
                 :: "l"(map), "r"(x), "r"(y), "r"(src) : "memory");
}
__device__ __forceinline__ void st_async(uint32_t a, uint32_t v, uint32_t bar) {
    asm volatile("st.async.weak.shared::cluster.mbarrier::complete_tx::bytes.b32 [%0], %1, [%2];" :: "r"(a), "r"(v), "r"(bar) : "memory");
}
__device__ __forceinline__ void red_async(uint32_t a, int v, uint32_t bar) {
    asm volatile("red.async.relaxed.cluster.shared::cluster.mbarrier::complete_tx::bytes.add.s32 [%0], %1, [%2];" :: "r"(a), "r"(v), "r"(bar) : "memory");
}
__device__ __forceinline__ void red_shared(uint32_t a, int v) { asm volatile("red.shared.add.s32 [%0], %1;" :: "r"(a), "r"(v) : "memory"); }
__device__ __forceinline__ int sum4(unsigned v, int c) { return __dp4a((int)v, 0x01010101, c); }

constexpr uint32_t DESC_A_HI = 0x80000000u | (512 >> 4);
constexpr uint32_t DESC_B_HI = 512 >> 4;
template <int NR> __device__ __forceinline__ void wgmma_n160(int (&d)[NR], uint32_t alo, uint32_t blo, int scale_d) {
    asm volatile("{\n.reg .pred p;\n.reg .b64 da, db;\nsetp.ne.b32 p, %82, 0;\n"
        "mov.b64 da, {%80, %83};\nmov.b64 db, {%81, %84};\n"
        "wgmma.mma_async.sync.aligned.m64n160k32.s32.s8.s8 "
        "{%0, %1, %2, %3, %4, %5, %6, %7, %8, %9, %10, %11, %12, %13, %14, %15, "
        "%16, %17, %18, %19, %20, %21, %22, %23, %24, %25, %26, %27, %28, %29, %30, %31, "
        "%32, %33, %34, %35, %36, %37, %38, %39, %40, %41, %42, %43, %44, %45, %46, %47, "
        "%48, %49, %50, %51, %52, %53, %54, %55, %56, %57, %58, %59, %60, %61, %62, %63, "
        "%64, %65, %66, %67, %68, %69, %70, %71, %72, %73, %74, %75, %76, %77, %78, %79}, "
        "da, db, p;\n}\n"
        : "+r"(d[0]), "+r"(d[1]), "+r"(d[2]), "+r"(d[3]), "+r"(d[4]), "+r"(d[5]), "+r"(d[6]), "+r"(d[7]),
          "+r"(d[8]), "+r"(d[9]), "+r"(d[10]), "+r"(d[11]), "+r"(d[12]), "+r"(d[13]), "+r"(d[14]), "+r"(d[15]),
          "+r"(d[16]), "+r"(d[17]), "+r"(d[18]), "+r"(d[19]), "+r"(d[20]), "+r"(d[21]), "+r"(d[22]), "+r"(d[23]),
          "+r"(d[24]), "+r"(d[25]), "+r"(d[26]), "+r"(d[27]), "+r"(d[28]), "+r"(d[29]), "+r"(d[30]), "+r"(d[31]),
          "+r"(d[32]), "+r"(d[33]), "+r"(d[34]), "+r"(d[35]), "+r"(d[36]), "+r"(d[37]), "+r"(d[38]), "+r"(d[39]),
          "+r"(d[40]), "+r"(d[41]), "+r"(d[42]), "+r"(d[43]), "+r"(d[44]), "+r"(d[45]), "+r"(d[46]), "+r"(d[47]),
          "+r"(d[48]), "+r"(d[49]), "+r"(d[50]), "+r"(d[51]), "+r"(d[52]), "+r"(d[53]), "+r"(d[54]), "+r"(d[55]),
          "+r"(d[56]), "+r"(d[57]), "+r"(d[58]), "+r"(d[59]), "+r"(d[60]), "+r"(d[61]), "+r"(d[62]), "+r"(d[63]),
          "+r"(d[64]), "+r"(d[65]), "+r"(d[66]), "+r"(d[67]), "+r"(d[68]), "+r"(d[69]), "+r"(d[70]), "+r"(d[71]),
          "+r"(d[72]), "+r"(d[73]), "+r"(d[74]), "+r"(d[75]), "+r"(d[76]), "+r"(d[77]), "+r"(d[78]), "+r"(d[79])
        : "r"(alo), "r"(blo), "r"(scale_d), "r"(DESC_A_HI), "r"(DESC_B_HI));
}
template <int NR> __device__ __forceinline__ void wgmma_t128(int (&d)[NR], uint32_t alo, uint32_t blo, int scale_d) {
    asm volatile("{\n.reg .pred p;\n.reg .b64 da, db;\nsetp.ne.b32 p, %66, 0;\n"
        "mov.b64 da, {%64, %67};\nmov.b64 db, {%65, %68};\n"
        "wgmma.mma_async.sync.aligned.m64n128k32.s32.s8.s8 "
        "{%0, %1, %2, %3, %4, %5, %6, %7, %8, %9, %10, %11, %12, %13, %14, %15, "
        "%16, %17, %18, %19, %20, %21, %22, %23, %24, %25, %26, %27, %28, %29, %30, %31, "
        "%32, %33, %34, %35, %36, %37, %38, %39, %40, %41, %42, %43, %44, %45, %46, %47, "
        "%48, %49, %50, %51, %52, %53, %54, %55, %56, %57, %58, %59, %60, %61, %62, %63}, "
        "da, db, p;\n}\n"
        : "+r"(d[0]), "+r"(d[1]), "+r"(d[2]), "+r"(d[3]), "+r"(d[4]), "+r"(d[5]), "+r"(d[6]), "+r"(d[7]),
          "+r"(d[8]), "+r"(d[9]), "+r"(d[10]), "+r"(d[11]), "+r"(d[12]), "+r"(d[13]), "+r"(d[14]), "+r"(d[15]),
          "+r"(d[16]), "+r"(d[17]), "+r"(d[18]), "+r"(d[19]), "+r"(d[20]), "+r"(d[21]), "+r"(d[22]), "+r"(d[23]),
          "+r"(d[24]), "+r"(d[25]), "+r"(d[26]), "+r"(d[27]), "+r"(d[28]), "+r"(d[29]), "+r"(d[30]), "+r"(d[31]),
          "+r"(d[32]), "+r"(d[33]), "+r"(d[34]), "+r"(d[35]), "+r"(d[36]), "+r"(d[37]), "+r"(d[38]), "+r"(d[39]),
          "+r"(d[40]), "+r"(d[41]), "+r"(d[42]), "+r"(d[43]), "+r"(d[44]), "+r"(d[45]), "+r"(d[46]), "+r"(d[47]),
          "+r"(d[48]), "+r"(d[49]), "+r"(d[50]), "+r"(d[51]), "+r"(d[52]), "+r"(d[53]), "+r"(d[54]), "+r"(d[55]),
          "+r"(d[56]), "+r"(d[57]), "+r"(d[58]), "+r"(d[59]), "+r"(d[60]), "+r"(d[61]), "+r"(d[62]), "+r"(d[63])
        : "r"(alo), "r"(blo), "r"(scale_d), "r"(DESC_B_HI), "r"(DESC_A_HI));
}


__device__ __forceinline__ void wg_fence() { asm volatile("wgmma.fence.sync.aligned;" ::: "memory"); }
__device__ __forceinline__ void wg_commit() { asm volatile("wgmma.commit_group.sync.aligned;" ::: "memory"); }
template <int N> __device__ __forceinline__ void wg_wait() { asm volatile("wgmma.wait_group.sync.aligned %0;" :: "n"(N) : "memory"); }

__host__ __device__ constexpr int unit_of(int piece, int slab) {
    return piece < 2 ? (slab < X1 ? 2 * slab + piece : (piece ? 16 : X1) + slab) : 32 + (piece - 2) * 8 + (slab >> 1);
}
__host__ __device__ constexpr int col_of(int G) { return G == 4 ? 256 : (G > 4 && G < 9) ? 32 * G - 32 : 32 * G; }
struct BJob { int u, slab, G, pos; };
__host__ __device__ constexpr BJob decode_b(int q) {
    BJob j = {};
    if (q < 160) {
        j.u = q / 5; j.pos = q - j.u * 5;
        const int piece = j.u < 2 * X1 ? (j.u & 1) : (j.u >= X1 + 16);
        j.slab = j.u < 2 * X1 ? (j.u >> 1) : j.u - (piece ? 16 : X1);
        j.G = piece * 5 + j.pos;
    } else {
        q -= 160;
        j.u = 32 + (q >> 2); j.pos = q & 3;
        j.slab = (q >> 1) & 15;
        j.G = 10 + (q >> 5) * 2 + (q & 1);
    }
    return j;
}
__host__ __device__ constexpr int fb_of(int u) {
    return u < 2 * X1 ? (u & 1) * 32 + (u >> 1) : u < X1 + 16 ? u - X1 : u < 32 ? 16 + u : u < 40 ? u - 16 : u < 48 ? u + 8 : u - 24;
}
__host__ __device__ constexpr uint64_t slot_table(int piece) {
    uint64_t t = 0;
    if (piece < 2) for (int s = 0; s < 16; s++) t |= (uint64_t)(unit_of(piece, s) % NSLOT) << (4 * s);
    else for (int s = 0; s < 8; s++) t |= (uint64_t)(unit_of(piece, 2 * s) % NSLOT) << (4 * s);
    return t;
}
template <bool k2> __device__ __forceinline__ int stage_w(int t) { return (k2 && t < 9) ? SM_A + (7 + t) * 8192 : SM_STG + (t % 3) * 8192; }
__host__ __device__ constexpr int ford(int g, int m) { return g ? (m < 2 ? 2 + 2 * m : 3 + m) : (m < 2 ? m : m < 3 ? 3 : 5 + m); }
__host__ __device__ constexpr uint64_t ford_table() {
    uint64_t t = 0;
    for (int g = 0; g < 2; g++) for (int m = 0; m < 5; m++) t |= (uint64_t)(g * 8 + m) << (4 * ford(g, m));
    return t;
}
struct Maps { CUtensorMap m[4]; };

__device__ __forceinline__ uint32_t bf2_mul(uint32_t a, uint32_t b) { asm("mul.rn.bf16x2 %0, %0, %1;" : "+r"(a) : "r"(b)); return a; }
__device__ __forceinline__ uint32_t epi(int a, int b, uint32_t zc, uint32_t sx, uint32_t sw, uint32_t bi) {
    uint32_t v;
    float fa = __int2float_rn(a), fb = __int2float_rn(b);
    asm("cvt.rn.bf16x2.f32 %0, %1, %2;" : "=r"(v) : "f"(fb), "f"(fa));
    asm("sub.rn.bf16x2 %0, %0, %1;" : "+r"(v) : "r"(zc));
    if (CFG_EPI == 0) {
        v = bf2_mul(bf2_mul(v, sx), sw);
        asm("add.rn.bf16x2 %0, %0, %1;" : "+r"(v) : "r"(bi));
    } else {
        asm("fma.rn.bf16x2 %0, %0, %1, %2;" : "+r"(v) : "r"(sw), "r"(bi));
    }
    return v;
}
__device__ __forceinline__ uint32_t zero_term(int lo, int hi, float zx) {
    uint32_t z;
    asm("cvt.rn.bf16x2.f32 %0, %1, %2;" : "=r"(z) : "f"(__bfloat162float(__float2bfloat16_rn((float)hi)) * zx),
                                                    "f"(__bfloat162float(__float2bfloat16_rn((float)lo)) * zx));
    return z;
}
__device__ __forceinline__ float ld_zx(const int* zero_x) { return __bfloat162float(__float2bfloat16_rn((float)__ldg(zero_x))); }
struct Par { uint4 zc, sw, bi; };
__device__ __forceinline__ Par ld_par(uint32_t p) { return {lds128(p), lds128(p + TN * 2), lds128(p + TN * 4)}; }
__device__ __forceinline__ uint4 epi_row(const int (&a)[WA / 2], int o, const Par& p, uint32_t sx2) {
    uint4 r;
    r.x = epi(a[o + 0], a[o + 4], p.zc.x, sx2, p.sw.x, p.bi.x);
    r.y = epi(a[o + 8], a[o + 12], p.zc.y, sx2, p.sw.y, p.bi.y);
    r.z = epi(a[o + 1], a[o + 5], p.zc.z, sx2, p.sw.z, p.bi.z);
    r.w = epi(a[o + 9], a[o + 13], p.zc.w, sx2, p.sw.w, p.bi.w);
    return r;
}
template <bool k2> __device__ __forceinline__ void release(uint32_t go, int u, int lane) {
    const int v = u + NSLOT;
    if (k2) {
        const int q = v + lane;
        if (lane < (v < 48 ? 1 : 0)) mbar_arrive_cluster(mapa(go + (q >> 1) * 8, q & 1));
    } else {
        const int q = 5 * v - (v > 34 ? 3 : 0) + lane;
        if (lane < (v > 38 ? 0 : v == 34 ? 2 : 5)) mbar_arrive_cluster(mapa(go + (q >> 4) * 8, q & 15));
    }
}
__device__ __forceinline__ unsigned read_back(const uint4* d, int lane) { return ld_flag((const unsigned*)(d - lane + ((lane + 10) & 15) * 8 + 6)); }
__device__ __forceinline__ void publish(unsigned rb, unsigned mine, unsigned* flag) {
    if (__shfl_sync(~0u, rb ^ mine, 6)) asm volatile("fence.acq_rel.gpu;" ::: "memory");
    if (elect_one()) flag_add(flag);
}
#define CV_B(m, f)                                                                                                      \
    {                                                                                                                   \
        uint4 v0 = lds128(rdB + m * 512), v1 = lds128(rdB + m * 512 + 128);                                             \
        uint4 v2 = lds128(rdB + m * 512 + 256), v3 = lds128(rdB + m * 512 + 384);                                       \
        o[0].f = pack4(v0.x, v1.x, v2.x, v3.x); o[1].f = pack4(v0.y, v1.y, v2.y, v3.y);                                 \
        o[2].f = pack4(v0.z, v1.z, v2.z, v3.z); o[3].f = pack4(v0.w, v1.w, v2.w, v3.w);                                 \
    }

__device__ __forceinline__ void last_columns(Scratch* sc, const Maps& maps, const __nv_bfloat16* scale_x, const int* zero_x, const __nv_bfloat16* scale_w,
                                             const __nv_bfloat16* bias, uint32_t sb, int warp, int lane, unsigned t0) {
    constexpr int C_FULL = 0, C_EMPTY = 32, C_RAW = 64, C_GO = 80, C_PEER = 81, D3 = CFG_D3;
    const uint32_t bars = sb + SM_BAR;
    const int j = blockIdx.x & 3;
    while ((int)(t0 + CFG_T3 - clk()) > 0) ;
    const int s0 = (j & 1) * 8 + (warp >> 1) * 2;
    if (warp < 8) {
        if (elect_one()) {
#pragma unroll
            for (int i = 0; i < 2; i++) {
                const uint32_t bar = bars + (C_RAW + warp * 2 + i) * 8;
                mbar_init(bar, 1); mbar_expect_tx(bar, 8192);
                raw_load(maps.m + 1, (s0 + (i ^ (j >> 1))) * 64, N_ / 32 - 2 + (warp & 1), sb + SM_A + (warp * 2 + i) * 8192, bar);
            }
#pragma unroll
            for (int i = 0; i < 4; i++) { mbar_init(bars + (C_FULL + warp * 4 + i) * 8, 1); mbar_expect_tx(bars + (C_FULL + warp * 4 + i) * 8, 16384); }
#pragma unroll
            for (int i = 0; i < 4; i++) mbar_init(bars + (C_EMPTY + warp * 4 + i) * 8, 4);
            if (warp == 0) {
                mbar_init(bars + C_GO * 8, 8);
                mbar_init(bars + C_PEER * 8, 1); mbar_expect_tx(bars + C_PEER * 8, 32768 + 4096);
            }
        }
        if (warp < 2) sts32(sb + SM_PAR + threadIdx.x * 4, 0);
        fence_init();
    }
    __syncthreads();
    cluster_arrive();
    cluster_wait();
    if (warp >= 8) {
        asm volatile("setmaxnreg.dec.sync.aligned.u32 40;");
        if (warp < 12) {
            const unsigned ep = (ld_flag(epoch(sc, j * 4, 8)) + 1) * 4;
            const int mb = j * 4 + warp - 8, wg = (warp >> 1) & 1;
            unsigned rdy = 0;
            mbar_wait(bars + (wg ? C_EMPTY : C_GO) * 8);
#pragma unroll 1
            for (int s = 0; s < 16; s++) {
                for (int it = 0; !((rdy >> s) & 1); it++) {
                    rdy = __ballot_sync(~0u, (int)(ld_flag(sc->flag + mb * 32 + (lane & 15)) - ep) >= 0);
                    if (it > (1 << 22)) __trap();
                }
                if (s >= D3) mbar_wait(bars + (C_EMPTY + (s - D3) * 2 + wg) * 8);
                if (elect_one()) tile_load(sc, sb + SM_A + ((s & 3) * 4 + warp - 8) * 8192, mb * 16 + s, bars + (C_FULL + s * 2 + wg) * 8);
            }
        }
    } else {
        asm volatile("setmaxnreg.inc.sync.aligned.u32 200;");
        const int wg = warp >> 2, w = warp & 3;
        const int c0 = (w >> 1) * 32 + (lane >> 2) * 4 + (w & 1) * 2, r0 = (lane & 3) * 2;
        const uint32_t sx2 = (uint32_t)__ldg((const unsigned short*)scale_x) * 0x10001u;
        uint32_t sw = __ldg((const unsigned*)(scale_w + N_ - WB + c0));
        const uint32_t bi = __ldg((const unsigned*)(bias + N_ - WB + c0));
        const float zxf = ld_zx(zero_x);
        int cs[4] = {0, 0, 0, 0};
        const uint32_t peer = mapa(sb, (j & 1) ^ 1);
#pragma unroll 1
        for (int i = 0; i < 2; i++) {
            const uint32_t rdB = sb + SM_A + (warp * 2 + i) * 8192 + (lane >> 3) * 2048 + (lane & 7) * 16;
            const uint32_t wr = SM_RING + (s0 + (i ^ (j >> 1))) * 4096 + (warp & 1) * 2048 + lane * 16;
            mbar_wait(bars + (C_RAW + warp * 2 + i) * 8);
            uint4 o[4];
            CV_B(0, x) CV_B(1, y) CV_B(2, z) CV_B(3, w)
#pragma unroll
            for (int k = 0; k < 4; k++) {
                sts128(sb + wr + k * 512, o[k]);
                asm volatile("st.async.weak.shared::cluster.mbarrier::complete_tx::bytes.v4.b32 [%0], {%1,%2,%3,%4}, [%5];"
                             :: "r"(peer + wr + k * 512), "r"(o[k].x), "r"(o[k].y), "r"(o[k].z), "r"(o[k].w), "r"(peer + SM_BAR + C_PEER * 8) : "memory");
                cs[k] = sum4(o[k].x, sum4(o[k].y, sum4(o[k].z, sum4(o[k].w, cs[k]))));
            }
        }
        __syncwarp();
        if (elect_one()) mbar_arrive(bars + C_GO * 8);
#pragma unroll
        for (int k = 0; k < 4; k++) {
            const uint32_t ca = SM_PAR + ((warp & 1) * 32 + (lane & 7) * 4 + k) * 4;
            red_shared(sb + ca, cs[k]);
            red_async(peer + ca, cs[k], peer + SM_BAR + C_PEER * 8);
        }
        mbar_wait(bars + C_PEER * 8);
        asm volatile("fence.proxy.async.shared::cta;" ::: "memory");
        asm volatile("bar.sync 1, 256;" ::: "memory");
        if (CFG_EPI) sw = bf2_mul(sw, sx2);
        const uint32_t zc = zero_term(lds32(sb + SM_PAR + c0 * 4), lds32(sb + SM_PAR + c0 * 4 + 4), zxf);
        const uint32_t sd = (sb & 0x3FFFF) >> 4;
        int t[2][64];
        wg_fence();
#pragma unroll 1
        for (int s = 0; s < 16; s++) {
            const uint32_t db = ((sd + (SM_RING >> 4)) | (8 << 16)) + s * 256, da = ((sd + (SM_A >> 4)) | (1 << 16)) + ((s & 3) * 4 + wg * 2) * 512;
            mbar_wait(bars + (C_FULL + s * 2 + wg) * 8);
            wgmma_t128(t[0], db, da, s);
            wgmma_t128(t[1], db, da + 512, s);
            wgmma_t128(t[0], db + 16, da + 2, 1);
            wgmma_t128(t[1], db + 16, da + 514, 1);
            wg_commit();
            wg_wait<0>();
            if (elect_one()) mbar_arrive(bars + (C_EMPTY + s * 2 + wg) * 8);
        }
        asm volatile("bar.sync %0, 128;" :: "r"(3 + wg) : "memory");
        const uint32_t st0 = sb + SM_A + wg * 16384 + r0 * 128 + (((c0 >> 3) ^ r0) << 4) + (c0 & 7) * 2;
#pragma unroll
        for (int h = 0; h < 4; h++) {
            const uint32_t off = (h >> 1) * 32768 + (h & 1) * 8192;
#pragma unroll
            for (int q = 0; q < 8; q++) {
                const int o = (h & 1) * 32 + q * 4;
                sts32(st0 + off + q * 1024, epi(t[h >> 1][o], t[h >> 1][o + 2], zc, sx2, sw, bi));
                sts32((st0 ^ (5 * 128 + 5 * 16)) + off + q * 1024, epi(t[h >> 1][o + 1], t[h >> 1][o + 3], zc, sx2, sw, bi));
            }
            asm volatile("fence.proxy.async.shared::cta;" ::: "memory");
            asm volatile("bar.sync %0, 128;" :: "r"(3 + wg) : "memory");
            if (w == 0 && elect_one()) tile_store(maps.m + 2, N_ - WB, j * 512 + wg * 256 + h * 64, sb + SM_A + wg * 16384 + off);
        }
        if (w == 0) {
            asm volatile("cp.async.bulk.commit_group;" ::: "memory");
            asm volatile("cp.async.bulk.wait_group.read 0;" ::: "memory");
        }
        asm volatile("bar.sync 1, 256;" ::: "memory");
        if (threadIdx.x == 0) flag_add(epoch(sc, j * 4, 8));
    }
}

template <bool k2>
__global__ void __cluster_dims__(k2 ? 2 : CS, 1, 1) __launch_bounds__(512, 1)
w8a8_kernel(Scratch* sc, const char* __restrict__ qw, const __nv_bfloat16* __restrict__ scale_x, const int* __restrict__ zero_x,
            const __nv_bfloat16* __restrict__ scale_w, const __nv_bfloat16* __restrict__ bias, const __grid_constant__ Maps maps) {
    extern __shared__ __align__(1024) unsigned char smem_raw[];
    constexpr int NBJ = k2 ? 12 : 14, NF = NBJ, NU = k2 ? 40 : 48;
    const int b = blockIdx.x + (k2 ? NCTA : 0), r = b & 15, c = k2 ? NCL : b >> 4;
    const unsigned tc = clk();
    const uint32_t sb = (uint32_t)__cvta_generic_to_shared(smem_raw);
    const uint32_t bars = sb + SM_BAR;
    const unsigned tw = __shfl_sync(~0u, (tc & ~15u) | threadIdx.x >> 5, 0), t0 = tw + (k2 ? 0 : T0);
    const int warp = tw & 15, lane = threadIdx.x & 31;

    if (!k2 && warp == 12) {
        const int a = r * NCL + c;
        if (elect_one()) {
            mbar_init(bars + (B_RAWA + 3) * 8, 1);
            mbar_expect_tx(bars + (B_RAWA + 3) * 8, 8192);
            raw_load(maps.m, (a >> 6) * 2, ((a ^ REV) & 63) * 32, sb + SM_A + (a < NAJ % NCTA ? 15 : 13) * 8192, bars + (B_RAWA + 3) * 8);
        }
        __syncwarp();
    }
    if (warp == 9 && elect_one()) asm volatile("prefetch.tensormap [%0];" :: "l"(maps.m + 1) : "memory");
    if (k2 && blockIdx.x >= 16) {
        last_columns(sc, maps, scale_x, zero_x, scale_w, bias, sb, warp, lane, t0);
        return;
    }
    if (warp >= 12) {
        const int isw = k2 || warp == 14, t = k2 ? warp - 12 : isw ? 0 : (warp - 11) >> 1;
        const uint32_t bar = bars + ((isw ? B_RAWB : B_RAWA) + 3 + t) * 8;
        if ((k2 || warp != 12) && elect_one()) { mbar_init(bar, 1); mbar_expect_tx(bar, 8192); }
        __syncwarp();
        cluster_arrive();
        const int x = t * 16 + r, a = (x * NCL + c) ^ REV, sx = (x * 26) >> 8;
        static_assert(X1 >= 7, "");
        if ((k2 || warp != 12) && elect_one()) {
            const unsigned te = t0 + (k2 ? sched2(x) : (isw ? time_w(x) : time_x(x)) * P1);
            while ((int)(te - clk()) > 0) ;
            raw_load(maps.m + isw, isw ? sx * 64 : (a >> 6) * 2,
                     isw ? c * (TN / 32) + (int)((0x9765483210ull >> ((x - sx * 10) * 4)) & 15) : (a & 63) * 32,
                     sb + (k2 ? SM_A + 7 * 8192 : isw ? SM_STG : SM_A + 13 * 8192) + (t - (!isw && r * NCL + c < NAJ % NCTA)) * 8192, bar);
        }
        __syncwarp();
        if (!k2 && warp == 15) cluster_wait();
    }
    if (warp < 8) {
        const uint32_t p = bars + warp * 104;
        if (elect_one()) {
#pragma unroll
            for (int i = 0; i < 13; i++) mbar_init(p + i * 8, (!k2 && ((warp == 6 && i == 12) || (warp == 7 && i < 2))) ? 2 : 1);
            static_assert(B_FREE == 90 && B_GO == 104, "");
        }
        __syncwarp();
        const int i = warp * 13 + lane;
        if (lane < 13 && i < B_SW) mbar_expect_tx(p + lane * 8, i >= B_PAR ? (i < B_PAR + 2 ? WA * 2 : WB * 2) : (i & 16) || i >= 48 ? 8192 : WA * 64);
        fence_init();
    }
    if (warp < 8 || warp == 10) cluster_arrive();
    if (!k2 && warp == 10 && lane < CFG_PF7) {
        const int n = b * CFG_PF7 + lane, row = n / 10;
        asm volatile("prefetch.global.L2 [%0];" :: "l"(qw + row * (N_ * 4) + NCL * TN * 4 + (n - row * 10) * 128));
    }

    if (warp < 8) {
        asm volatile("setmaxnreg.inc.sync.aligned.u32 200;");
        const int wg = warp >> 2;
        const uint32_t sd = (sb & 0x3FFFF) >> 4;
        const uint32_t sx2 = (uint32_t)__ldg((const unsigned short*)scale_x) * 0x10001u;
        const uint32_t par = sb + SM_PAR + (lane & 3) * 16 + wg * 256;
        const uint32_t go = bars + B_GO * 8;
        const int w = warp & 3, pq = (lane >> 2) ^ (lane & 4);
        uint32_t so = (w * 16 + pq) * 128 + (((lane & 3) ^ pq) << 4);
        const int c0 = (w >> 1) * 32 + (lane >> 2) * 4 + (w & 1) * 2, r0 = (lane & 3) * 2;
        uint32_t pp = sb + SM_PAR + (2 * WA + wg * WB + c0) * 2, st0 = r0 * 128 + (((c0 >> 3) ^ r0) << 4) + (c0 & 7) * 2;
        constexpr int rn = k2 ? 1 : 4;
        int rq = lane < rn ? rn * (32 + wg * 8 + (k2 ? NSLOT : 8)) + (k2 ? 0 : 32) + lane : 1000;
        asm volatile("" : "+r"(so), "+r"(pp), "+r"(st0), "+r"(rq));
        cluster_wait();
        int a0[WA / 2], a1[WA / 2];
        uint32_t barB = bars + (B_FULLB + wg * 32) * 8;
        wg_fence();
        {
            uint64_t tbl = wg ? slot_table(1) : slot_table(0);
            uint32_t da = (sd + (SM_A >> 4)) | (1 << 16);
            int up = 99;
            bool rdy = false;
#pragma unroll 1
            for (int s = 0; s < 16; s++) {
                const uint32_t db = ((sd + (SM_RING >> 4)) | (8 << 16)) + ((uint32_t)tbl & 15) * (SLOT >> 4);
                const bool hold = wg && s == X1;
                if (hold || (!rdy && !mbar_test2(bars + (B_FULLA + s) * 8, barB))) {
                    wg_wait<0>();
                    release<k2>(go, up, lane); up = 99;
                    mbar_wait2(bars + (B_FULLA + s) * 8, barB);
                    if (hold) asm volatile("bar.sync 7, 256;" ::: "memory");
                }
                wgmma_n160(a0, da, db, s);
                wgmma_n160(a1, da + 256, db, s);
                wg_commit();
                if (!wg && s == HOLD) asm volatile("bar.arrive 7, 256;" ::: "memory");
                wg_wait<1>();
                release<k2>(go, up, lane);
                wgmma_n160(a0, da + 2, db + 16, 1);
                wgmma_n160(a1, da + 258, db + 16, 1);
                wg_commit();
                up = s < X1 ? 2 * s + wg : (wg ? 16 : X1) + s;
                tbl >>= 4; da += 512; barB += 8;
                rdy = mbar_test2(bars + (B_FULLA + s + 1) * 8, barB);
                if (s < 15) wg_wait<1>();
            }
        }
        mbar_wait2(bars + (B_PAR + wg) * 8, bars + B_SW * 8);
        Par P = ld_par(par);
        wg_wait<0>();
        release<k2>(go, wg ? 31 : X1 + 15, lane);
        bool ready = mbar_test(barB);
#define FILL_BEGIN(n0, n1) mbar_wait(bars + (B_FREE + (wg ? n1 : n0)) * 8);                                             \
                           const uint32_t buf = sb + SM_STG + (wg ? (n1 + NBJ) % 3 : (n0 + NBJ) % 3) * 8192;
#define FILL_END(n0, n1) __syncwarp();                                                                                  \
                         if (elect_one()) mbar_arrive(bars + (B_FILL + (wg ? n1 % 3 : n0 % 3)) * 8);
#define FILL_PAIR(a, J, PN, m)                                                                                          \
        {                                                                                                               \
            const uint4 v0 = epi_row(a, J * 16, P, sx2);                                                                \
            const Par Q = ld_par(par + J * 64 + 64);                                                                    \
            const uint4 v1 = epi_row(a, J * 16 + 2, P, sx2);                                                            \
            FILL_BEGIN(ford(0, m), ford(1, m))                                                                          \
            sts128(buf + so, v0); sts128(buf + so + 1024, v1);                                                          \
            if ((PN) >= 0) P = ld_par(par + (PN));                                                                      \
            sts128(buf + (so ^ 64), epi_row(a, J * 16 + 16, Q, sx2));                                                   \
            sts128(buf + (so ^ 64) + 1024, epi_row(a, J * 16 + 18, Q, sx2));                                            \
            FILL_END(ford(0, m), ford(1, m))                                                                            \
        }
#define RELEASE_N() { if (rq < (k2 ? NU : NBJ * 16)) mbar_arrive_cluster(mapa(go + (rq >> rn) * 8, rq & ((1 << rn) - 1))); rq += rn; nrel++; }
#define NARROW(p)                                                                                                       \
        {                                                                                                               \
            uint32_t tbl = (uint32_t)slot_table(p), da = (sd + (SM_A >> 4)) | (1 << 16);                                \
            wg_fence();                                                                                                 \
            _Pragma("unroll 1") for (int i = 0; i < 8; i++) {                                                           \
                const uint32_t db = ((sd + (SM_RING >> 4)) | (8 << 16)) + (k2 ? (tbl & 15) * (SLOT >> 4) : ((i + 5) & 7) * 512); \
                if (!ready && !mbar_test(barB)) {                                                                       \
                    wg_wait<0>();                                                                                       \
                    if (p == 2) { _Pragma("unroll 1") while (nrel < i) RELEASE_N() }                                    \
                    mbar_wait(barB);                                                                                    \
                }                                                                                                       \
                _Pragma("unroll") for (int kk = 0; kk < 4; kk++)                                                        \
                    wgmma_t128(t, db + (kk >> 1) * 256 + (kk & 1) * 16, da + (kk >> 1) * 512 + (kk & 1) * 2, kk ? 1 : i); \
                wg_commit();                                                                                            \
                barB += 8;                                                                                              \
                ready = mbar_test(barB);                                                                                \
                if (p == 2 && nrel < i - 1) RELEASE_N()                                                                 \
                tbl >>= 4; da += 1024;                                                                                  \
                wg_wait<1>();                                                                                           \
            }                                                                                                           \
            if (p == 2) { if (nrel < 7) RELEASE_N() P = ld_par(par + 128); }                                            \
            else { mbar_wait(bars + (B_PAR + 3) * 8); zc = lds32(pp); sw = lds32(pp + TN * 2); bi = lds32(pp + TN * 4); } \
            wg_wait<0>();                                                                                               \
            if (p == 2) RELEASE_N()                                                                                     \
        }
        int nrel = 0;
        FILL_PAIR(a0, 0, 128, 0) FILL_PAIR(a0, 2, 0, 1)
        int t[64];
        uint32_t zc, sw, bi;
        FILL_PAIR(a1, 0, -1, 2)
        if (wg == 0) NARROW(2) else P = ld_par(par + 128);
        FILL_PAIR(a1, 2, 512 - wg * 192, 3)
        {
            const uint4 v0 = epi_row(a0, 64, P, sx2), v1 = epi_row(a0, 66, P, sx2);
            if (!wg) mbar_wait(bars + (B_PAR + 2) * 8);
            FILL_BEGIN(ford(0, 4), ford(1, 4))
            const uint32_t s4 = buf + ((so >> 1) & ~63u) + (lane & 3) * 16;
            sts128(s4, v0); sts128(s4 + 512, v1);
            sts128(s4 + 4096, epi_row(a1, 64, P, sx2)); sts128(s4 + 4608, epi_row(a1, 66, P, sx2));
            FILL_END(ford(0, 4), ford(1, 4))
        }
        if (!(k2 && wg)) {
            if (!k2 && wg == 1) NARROW(3) else { zc = lds32(pp); sw = lds32(pp + TN * 2); bi = lds32(pp + TN * 4); }
#define FILL_T(h)                                                                                                       \
            {                                                                                                           \
                FILL_BEGIN((10 + h), (12 + h))                                                                          \
                _Pragma("unroll") for (int j = 0; j < 8; j++) {                                                         \
                    const int o = h * 32 + j * 4;                                                                       \
                    sts32(buf + st0 + j * 1024, epi(t[o], t[o + 2], zc, sx2, sw, bi));                                  \
                    sts32(buf + (st0 ^ (5 * 128 + 5 * 16)) + j * 1024, epi(t[o + 1], t[o + 3], zc, sx2, sw, bi));       \
                }                                                                                                       \
                FILL_END((10 + h), (12 + h))                                                                            \
            }
            FILL_T(0) FILL_T(1)
        }
        if (threadIdx.x == 0) flag_add(epoch(sc, r, c));
    } else {
        const int g = r * NCL + c, na = k2 ? 0 : NAJ / NCTA + (g < NAJ % NCTA);
        int cw = NF;
        if (warp >= 12) {
            asm volatile("setmaxnreg.dec.sync.aligned.u32 80;");
            if (warp < 14) {
                const int c4 = (lane ^ (lane >> 3)) & 3, ln = ((lane >> 2) ^ (lane & 4)) * 2 + (c4 >> 1);
                const uint32_t rd0 = sb + SM_A + 13 * 8192 + ln * 128 + ((((c4 & 1) << 2) ^ (ln & 7)) << 4);
#pragma unroll 1
                for (int t = warp - 12, sl = na == 9 ? t : 2 - 2 * t; t < na; t += 2, sl = sl ? sl - 1 : 2) {
                    const uint32_t rdA = rd0 + sl * 8192;
                    const int a = (t * NCTA + g) ^ REV, f = (a & 60) * 4 + (a >> 6);
                    uint4* const d = sc->s8 + (f * 4 + (a & 3)) * 128 + lane;
                    uint4 o[4];
                    mbar_wait(bars + (B_RAWA + 3 + t) * 8);
#pragma unroll
                    for (int i = 0; i < 4; i++) {
                        uint4 v0 = lds128(rdA + i * 2048), v1 = lds128((rdA ^ 16) + i * 2048);
                        uint4 v2 = lds128((rdA ^ 32) + i * 2048), v3 = lds128((rdA ^ 48) + i * 2048);
                        o[i].x = pack4(v0.x, v0.y, v0.z, v0.w); o[i].y = pack4(v1.x, v1.y, v1.z, v1.w);
                        o[i].z = pack4(v2.x, v2.y, v2.z, v2.w); o[i].w = pack4(v3.x, v3.y, v3.z, v3.w);
                    }
#pragma unroll
                    for (int i = 0; i < 4; i++) stg128(d + i * 32, o[i]);
                    asm volatile("fence.proxy.async.global;" ::: "memory");
                    __syncwarp();
                    const unsigned rb = read_back(d, lane);
                    if (t < 2) cluster_wait();
                    if (elect_one()) mbar_arrive(bars + ((t < na - 3 ? B_RAWA : B_AFREE + 13) + sl) * 8);
                    publish(rb, o[0].x, sc->flag + (a & 60) * 8 + (a >> 6));
                }
                cw = warp - 12;
            }
            if (!k2) {
                const int hw = warp & 1;
                const uint32_t rd0 = sb + SM_STG + hw * 4096 + (lane >> 3) * 1024 + (lane & 7) * 16;
                const int myG = decode_b((lane & 15) * 16 + r).G;
#pragma unroll 1
                for (int t = warp < 14 ? TA : 0; t < NBJ; t += warp < 14 ? NBJ : t == TA - 1 ? 2 : 1) {
                    const int sl = t % 3;
                    const uint32_t rdB = rd0 + sl * 8192;
                    char* const d = (char*)sc->s8 + (1024 + c * 256 + t * 16 + r) * 2048 + hw * 256 + (lane >> 4) * 128 + (lane & 7) * 16 + (lane & 8);
                    uint2 o[4];
                    mbar_wait(bars + (B_RAWB + 3 + t) * 8);
                    CV_B(0, x) CV_B(1, y)
#pragma unroll
                    for (int i = 0; i < 4; i++) asm volatile("st.global.v2.b32 [%0], {%1,%2};" :: "l"(d + i * 512), "r"(o[i].x), "r"(o[i].y) : "memory");
                    if (t == 0 && warp == 14) cluster_wait();
                    if (elect_one()) mbar_arrive(bars + (t >= NBJ - 3 ? B_FREE + t - (NBJ - 3) : B_RAWB + sl) * 8);
                    asm volatile("fence.proxy.async.global;" ::: "memory");
                    __syncwarp();
                    if (elect_one()) mbar_arrive(bars + (B_GO + t) * 8);
                    int cs[4];
#pragma unroll
                    for (int i = 0; i < 4; i++) cs[i] = sum4(o[i].x, sum4(o[i].y, 0));
                    const int p01 = cs[0] + cs[1] * 65536, p23 = cs[2] + cs[3] * 65536;
                    const bool h = lane & 16;
                    int x = (h ? p23 : p01) + __shfl_xor_sync(~0u, h ? p01 : p23, 16);
                    x += __shfl_xor_sync(~0u, x, 8);
                    const int lo = (int)(short)x, v = (lane & 8) ? (x - lo) >> 16 : lo;
                    const int G = __shfl_sync(~0u, myG, t);
                    if (G != r) {
                        red_async(mapa(sb + SM_CS + lane * 4, G), v, mapa(bars + B_CS * 8, G));
                    } else {
                        red_shared(sb + SM_CS + lane * 4, v);
                        __syncwarp();
                        if (elect_one()) mbar_arrive(bars + B_CS * 8);
                    }
                }
            } else {
                const uint32_t rd0 = sb + (lane >> 3) * 2048 + (lane & 7) * 16;
                const BJob mb = decode_b((lane & 15) * 16 + r);
                const int myG = mb.G | mb.u << 8;
#pragma unroll 1
                for (int t = warp - 12; t < NBJ; t += 4) {
                    const uint32_t rdB = rd0 + stage_w<k2>(t);
                    uint4* const d = sc->s8 + (1024 + c * 256 + t * 16 + r) * 128 + lane;
                    uint4 o[4];
                    mbar_wait(bars + (B_RAWB + 3 + t) * 8);
                    CV_B(0, x) CV_B(1, y) CV_B(2, z) CV_B(3, w)
#pragma unroll
                    for (int i = 0; i < 4; i++) stg128(d + i * 32, o[i]);
                    if (t < 4) cluster_wait();
                    if (elect_one()) mbar_arrive(bars + (B_FREE + t - (NBJ - 3)) * 8);
                    asm volatile("fence.proxy.async.global;" ::: "memory");
                    __syncwarp();
                    const unsigned rb = read_back(d, lane), ep = ld_flag(epoch(sc, r, c));
                    int cs[4];
#pragma unroll
                    for (int i = 0; i < 4; i++) cs[i] = sum4(o[i].x, sum4(o[i].y, sum4(o[i].z, sum4(o[i].w, 0))));
                    const bool h = lane & 16, odd = lane & 8;
                    int x = (h ? cs[2] : cs[0]) + __shfl_xor_sync(~0u, h ? cs[0] : cs[2], 16);
                    int y = (h ? cs[3] : cs[1]) + __shfl_xor_sync(~0u, h ? cs[1] : cs[3], 16);
                    const int v = (odd ? y : x) + __shfl_xor_sync(~0u, odd ? x : y, 8);
                    const int gu = __shfl_sync(~0u, myG, t);
                    publish(rb, o[0].x, sc->flag + F_W + (gu >> 8));
                    const int old = atomicAdd(sc->cs[ep & 1] + col_of(gu & 255) + (lane & 7) * 4 + (lane >> 3), v);
                    if (old == 0x7FFFFFFF) sc->sink[0] = old;
                    __syncwarp();
                    if (elect_one()) flag_add(sc->flag + F_CS + (t >= 10));
                }
            }
        } else {
            asm volatile("setmaxnreg.dec.sync.aligned.u32 32;");
            if (warp == 11) {
                if (elect_one()) {
#pragma unroll
                    for (int i = 0; i < (k2 ? NU / 2 : NBJ); i++)
                        mbar_init(bars + (B_GO + i) * 8, k2 ? (i * 2 + (r & 1) >= NSLOT ? 9 : 1) : (i * 16 + r >= NSLOT * 5 ? 2 + 4 * CS : 2));
#pragma unroll
                    for (int i = 0; i < 3; i++) mbar_init(bars + (B_FILL + i) * 8, 4);
                }
                const int u2 = lane * 2 + (r & 1), q = k2 ? (u2 < 32 ? 5 * u2 : 4 * u2 + 32) : (lane & 15) * 16 + r;
                const BJob bj = decode_b(q);
                unsigned seen = 0;
                if (!k2) {
                    const int nself = __popc(__ballot_sync(~0u, lane < NBJ && bj.G == r));
                    sts32(sb + SM_CS + lane * 4, 0);
                    if (lane == 0) {
                        mbar_init(bars + B_CS * 8, 1 + 2 * nself);
                        mbar_expect_tx(bars + B_CS * 8, (16 - nself) * 256);
                    }
                    seen = lds32(sb + SM_CS + lane * 4);
                }
                fence_init();
                asm volatile("barrier.cluster.arrive.relaxed.aligned;" :: "r"(seen) : "memory");
                const char* src = (const char*)sc->s8 + (1024 + c * 256 + q) * 2048;
                const uint32_t dst = sb + SM_RING + ((!k2 && q >= 160) ? ((q + 20) & 31) * 2048 : (bj.u % NSLOT) * SLOT + bj.pos * 2048);
                const uint32_t fb = bars + (B_FULLB + fb_of(bj.u)) * 8;
                cluster_wait();
                {
                    const uint32_t sx2 = (uint32_t)__ldg((const unsigned short*)scale_x) * 0x10001u;
#pragma unroll
                    for (int i = lane; i < TN / 4; i += 32) {
                        const bool hi = i >= TN / 8;
                        uint4 v = __ldg((const uint4*)((hi ? bias : scale_w) + c * TN) + (hi ? i - TN / 8 : i));
                        if (CFG_EPI && !hi) v = {bf2_mul(v.x, sx2), bf2_mul(v.y, sx2), bf2_mul(v.z, sx2), bf2_mul(v.w, sx2)};
                        sts128(sb + SM_PAR + TN * 2 + i * 16, v);
                    }
                    __syncwarp();
                    if (elect_one()) mbar_arrive(bars + B_SW * 8);
                }
#pragma unroll 1
                for (int i = 0; i < (k2 ? NU / 2 : NBJ); i++) {
                    mbar_wait(bars + (B_GO + i) * 8);
                    if (lane == i) {
                        asm volatile("cp.async.bulk.shared::cluster.global.mbarrier::complete_tx::bytes.multicast::cluster [%0], [%1], %2, [%3], %4;"
                                     :: "r"(dst), "l"(src), "r"(k2 ? (u2 < 32 ? SLOT : 8192) : 2048), "r"(fb), "h"((uint16_t)(k2 ? 3 : 0xFFFF)) : "memory");
                    }
                    __syncwarp();
                }
            } else if (warp == 10) {
                const unsigned ep = (__shfl_sync(~0u, ld_flag(sc->flag + r * 32 + (lane < 16 ? lane : 16 + c)), 16) + 1) * 4;
                const unsigned* f = sc->flag + r * 32 + (lane & 15);
                bool dn = lane >= 16;
                const bool fr = lane < (k2 ? 7 : 13);
                cluster_wait();
                for (int it = 0;; it++) {
                    const unsigned v = ld_flag(f);
                    if (!dn && (int)(v - ep) >= 0 && (fr || mbar_test(bars + (B_AFREE + lane) * 8))) {
                        dn = true;
                        tile_load(sc, sb + SM_A + lane * 8192, r * 16 + lane, bars + (B_FULLA + lane) * 8);
                    }
                    if (__all_sync(~0u, dn)) break;
                    if (it > (1 << 22)) __trap();
                }
            } else {
                const bool isw = warp == 9;
                const uint32_t rb = bars + (isw ? B_RAWB : B_RAWA) * 8;
                if (elect_one()) {
#pragma unroll
                    for (int i = 0; i < 13; i++) if (i < 3 || i >= (k2 ? 7 : 6)) mbar_init(rb + i * 8, (i < 3 && isw && !k2) ? 2 : 1);
                    if (isw) {
#pragma unroll
                        for (int i = 13; i < 17; i++) mbar_init(rb + i * 8, 1);
                        if (!k2) { mbar_init(rb + 4 * 8, 1); mbar_init(rb + 5 * 8, 1); }
                    }
                }
                __syncwarp();
                const int nj = isw ? NBJ : na, j0 = k2 ? 4 : isw ? 1 : 3;
                if (lane >= j0 && lane < nj) mbar_expect_tx(rb + (3 + lane) * 8, 8192);
                fence_init();
                cluster_arrive();
                const unsigned e0 = k2 ? ld_flag(epoch(sc, r, c)) : 0;
                const int k = lane / 3, x = lane * 16 + r;
                int sl = lane - k * 3, y, z, T;
                if (isw) {
                    const BJob bj = decode_b(x & 255);
                    y = bj.slab * 64; z = (c * TN + col_of(bj.G)) >> 5; T = time_w(x);
                } else {
                    const int a = (lane * NCTA + g) ^ REV;
                    y = (a >> 6) * 2; z = (a & 63) * 32; T = time_x(x);
                    if (na == 10) sl = sl ? sl - 1 : 2;
                }
                const unsigned te = t0 + (k2 ? sched2(x) : sched(T));
                const uint32_t sd = sb + (isw ? stage_w<k2>(lane) : SM_A + (13 + sl) * 8192);
#pragma unroll 1
                for (int t = j0; t < nj; t++) {
                    if (lane == t) {
                        if (t >= 3 && !k2) mbar_wait(rb + sl * 8, (k & 1) ^ 1);
                        while ((int)(te - clk()) > 0) ;
                        raw_load(maps.m + isw, y, z, sd, rb + (3 + t) * 8);
                    }
                    __syncwarp();
                }
                cluster_wait();
                if (elect_one()) asm volatile("prefetch.tensormap [%0];" :: "l"(maps.m + 2 + isw) : "memory");
                if (!isw) cw = 2;
                if (k2) {
                    if (!isw) {
                        if (lane < TN / 16) sc->cs[(e0 & 1) ^ 1][r * (TN / 16) + lane] = 0;
                        const int u = lane * 2 + (r & 1);
                        const unsigned tg = (e0 + 1) * (u < 32 ? 5 : 4);
                        bool dn = u >= NU;
                        for (int it = 0;; it++) {
                            if (!dn && (int)(ld_flag(sc->flag + F_W + u) - tg) >= 0) {
                                dn = true;
                                mbar_arrive(bars + (B_GO + lane) * 8);
                            }
                            if (__all_sync(~0u, dn)) break;
                            if (it > (1 << 22)) __trap();
                        }
                    } else {
                        const float zxf = ld_zx(zero_x);
#pragma unroll 1
                        for (int h = 0; h < 2; h++) {
                            for (int it = 0; (int)(ld_flag(sc->flag + F_CS + h) - (e0 + 1) * (h ? 32 : 160)) < 0; it++) if (it > (1 << 22)) __trap();
                            int2 v[5];
#pragma unroll
                            for (int j = 0; j < 5; j++) v[j] = __ldcg((const int2*)sc->cs[e0 & 1] + min(h * 160 + j * 32 + lane, TN / 2 - 1));
#pragma unroll
                            for (int j = 0; j < 5; j++) {
                                const int i = h * 160 + j * 32 + lane;
                                const uint32_t z = zero_term(v[j].x, v[j].y, zxf);
                                if (i < TN / 2 - 32) st_async(sb + SM_PAR + i * 4, z, bars + (B_PAR + (i < 128 ? i >> 6 : i < 160 ? (i >> 4) & 1 : 2)) * 8);
                            }
                        }
                    }
                }
            }
        }
        if (!k2 && r < NBJ && warp == (r < 10 ? 8 : 10)) {
            const float zxf = ld_zx(zero_x);
            mbar_wait(bars + B_CS * 8);
            const int w = lane & 15;
            const uint32_t ca = sb + SM_CS + ((w >> 1) + (w & 1) * 16) * 4;
            const uint32_t z = zero_term(lds32(ca), lds32(ca + 32), zxf);
            const int piece = r < 10 ? (r >= 5) : (r - 6) >> 1;
#pragma unroll 1
            for (int i = lane >> 4; i < CS; i += 2) st_async(mapa(sb + SM_PAR + col_of(r) * 2 + w * 4, i), z, mapa(bars + (B_PAR + piece) * 8, i));
        }
#pragma unroll 1
        for (int n = cw, k = 0; n < NF; n += 3, k ^= 1) {
            const int gm = (int)(ford_table() >> (4 * n)), g = (gm >> 3) & 1, m = gm & 7;
            const int x = n >= 10 ? (n >> 1) * 64 : m == 4 ? 256 + g * 32 : g * 128 + (m & 1) * 64;
            const int y = n >= 10 ? (n & 1) * 64 : (m & 2) * 32;
            mbar_wait(bars + (B_FILL + cw) * 8, k);
            asm volatile("fence.proxy.async.shared::cta;" ::: "memory");
            if (elect_one()) tile_store(maps.m + (n < 10 && m == 4 ? 3 : 2), c * TN + x, r * 128 + y, sb + SM_STG + ((cw + NBJ) % 3) * 8192);
            asm volatile("cp.async.bulk.commit_group;" ::: "memory");
            asm volatile("cp.async.bulk.wait_group.read 0;" ::: "memory");
            __syncwarp();
            if (n < NF - 3 && elect_one()) mbar_arrive(bars + (B_FREE + 3 + n) * 8);
        }
    }
}

__global__ void __launch_bounds__(256)
w8a8_plain(const int* __restrict__ qx, const int* __restrict__ qw, const __nv_bfloat16* __restrict__ scale_x, const int* __restrict__ zero_x,
           const __nv_bfloat16* __restrict__ scale_w, const __nv_bfloat16* __restrict__ bias, __nv_bfloat16* __restrict__ out) {
    __shared__ int xs[16][K_ / 4];
    const int n = (blockIdx.x * 256 + threadIdx.x) * 2, m0 = blockIdx.y * 16;
    for (int i = threadIdx.x; i < 16 * K_ / 4; i += 256) {
        const uint4 v = ((const uint4*)qx)[m0 * (K_ / 4) + i];
        xs[i / (K_ / 4)][i % (K_ / 4)] = pack4(v.x, v.y, v.z, v.w);
    }
    __syncthreads();
    int acc[16][2] = {}, cs[2] = {};
    for (int k = 0; k < K_ / 4; k++) {
        uint2 v[4];
#pragma unroll
        for (int i = 0; i < 4; i++) v[i] = *(const uint2*)(qw + (k * 4 + i) * N_ + n);
        const unsigned w0 = pack4(v[0].x, v[1].x, v[2].x, v[3].x), w1 = pack4(v[0].y, v[1].y, v[2].y, v[3].y);
        cs[0] = sum4(w0, cs[0]); cs[1] = sum4(w1, cs[1]);
#pragma unroll
        for (int i = 0; i < 16; i++) { acc[i][0] = __dp4a(xs[i][k], (int)w0, acc[i][0]); acc[i][1] = __dp4a(xs[i][k], (int)w1, acc[i][1]); }
    }
    const uint32_t sx2 = (uint32_t)*(const unsigned short*)scale_x * 0x10001u, zc = zero_term(cs[0], cs[1], ld_zx(zero_x));
    uint32_t sw = *(const unsigned*)(scale_w + n);
    if (CFG_EPI) sw = bf2_mul(sw, sx2);
#pragma unroll
    for (int i = 0; i < 16; i++) *(unsigned*)(out + (m0 + i) * N_ + n) = epi(acc[i][0], acc[i][1], zc, sx2, sw, *(const unsigned*)(bias + n));
}

}

typedef CUresult (*EncodeFn)(CUtensorMap*, CUtensorMapDataType, cuuint32_t, void*, const cuuint64_t*, const cuuint64_t*,
                             const cuuint32_t*, const cuuint32_t*, CUtensorMapInterleave, CUtensorMapSwizzle,
                             CUtensorMapL2promotion, CUtensorMapFloatOOBfill);

extern "C" void kernel_launch(void* const* d_in, const int* in_sizes, int n_in, void* d_out, int out_size) {
    using namespace w8;
    static EncodeFn encode = nullptr;
    static cudaStream_t side;
    static cudaEvent_t started, joined;
    static int clusters = -1;
    static Scratch* sc;
    cudaLaunchConfig_t cfg = {};
    cfg.gridDim = dim3(NCTA); cfg.blockDim = dim3(512); cfg.dynamicSmemBytes = SM_TOTAL; cfg.stream = cudaStreamPerThread;
    if (clusters < 0) {
        void* fn = nullptr;
        cudaDriverEntryPointQueryResult qr;
        cudaGetDriverEntryPoint("cuTensorMapEncodeTiled", &fn, cudaEnableDefault, &qr);
        encode = (EncodeFn)fn;
        cudaGetSymbolAddress((void**)&sc, g_scratch);
        cudaStreamCreateWithFlags(&side, cudaStreamNonBlocking);
        cudaEventCreateWithFlags(&started, cudaEventDisableTiming);
        cudaEventCreateWithFlags(&joined, cudaEventDisableTiming);
        cudaFuncSetAttribute(w8a8_kernel<false>, cudaFuncAttributeMaxDynamicSharedMemorySize, SM_TOTAL);
        cudaFuncSetAttribute(w8a8_kernel<true>, cudaFuncAttributeMaxDynamicSharedMemorySize, SM_TOTAL);
        cudaFuncSetAttribute(w8a8_kernel<false>, cudaFuncAttributeNonPortableClusterSizeAllowed, 1);
        if (cudaOccupancyMaxActiveClusters(&clusters, w8a8_kernel<false>, &cfg) != cudaSuccess) { clusters = 0; cudaGetLastError(); }
    }
    const __nv_bfloat16 *sx = (const __nv_bfloat16*)d_in[2], *sw = (const __nv_bfloat16*)d_in[4], *bias = (const __nv_bfloat16*)d_in[5];
    const int* zx = (const int*)d_in[3];
    if (clusters < NCL) {
        w8a8_plain<<<dim3(N_ / 512, M_ / 16), 256, 0, cudaStreamPerThread>>>((const int*)d_in[0], (const int*)d_in[1], sx, zx, sw, bias, (__nv_bfloat16*)d_out);
        return;
    }
    Maps maps;
    const cuuint32_t es[3] = {1, 1, 1};
    {
        const cuuint64_t dim[3] = {32, K_ / 32, M_}, str[2] = {128, K_ * 4};
        const cuuint32_t box[3] = {32, 2, 32};
        encode(&maps.m[0], CU_TENSOR_MAP_DATA_TYPE_INT32, 3, d_in[0], dim, str, box, es, CU_TENSOR_MAP_INTERLEAVE_NONE,
               CU_TENSOR_MAP_SWIZZLE_128B, CU_TENSOR_MAP_L2_PROMOTION_NONE, CU_TENSOR_MAP_FLOAT_OOB_FILL_NONE);
    }
    {
        const cuuint64_t dim[3] = {32, K_, N_ / 32}, str[2] = {N_ * 4, 128};
        const cuuint32_t box[3] = {32, 64, 1};
        encode(&maps.m[1], CU_TENSOR_MAP_DATA_TYPE_INT32, 3, d_in[1], dim, str, box, es, CU_TENSOR_MAP_INTERLEAVE_NONE,
               CU_TENSOR_MAP_SWIZZLE_NONE, CU_TENSOR_MAP_L2_PROMOTION_NONE, CU_TENSOR_MAP_FLOAT_OOB_FILL_NONE);
    }
    for (int i = 0; i < 2; i++) {
        const cuuint64_t dim[2] = {N_, M_}, str[1] = {N_ * 2};
        const cuuint32_t box[2] = {i ? 32u : 64u, i ? 128u : 64u};
        encode(&maps.m[2 + i], CU_TENSOR_MAP_DATA_TYPE_BFLOAT16, 2, d_out, dim, str, box, es, CU_TENSOR_MAP_INTERLEAVE_NONE,
               i ? CU_TENSOR_MAP_SWIZZLE_NONE : CU_TENSOR_MAP_SWIZZLE_128B, CU_TENSOR_MAP_L2_PROMOTION_NONE, CU_TENSOR_MAP_FLOAT_OOB_FILL_NONE);
    }
    cudaLaunchAttribute at;
    at.id = cudaLaunchAttributeLaunchCompletionEvent;
    at.val.launchCompletionEvent.event = started; at.val.launchCompletionEvent.flags = 0;
    cfg.attrs = &at; cfg.numAttrs = 1;
    cudaLaunchKernelEx(&cfg, w8a8_kernel<false>, sc, (const char*)d_in[1], sx, zx, sw, bias, maps);
    cudaStreamWaitEvent(side, started, 0);
    cfg.gridDim = dim3(20); cfg.stream = side; cfg.numAttrs = 0;
    cudaLaunchKernelEx(&cfg, w8a8_kernel<true>, sc, (const char*)d_in[1], sx, zx, sw, bias, maps);
    cudaEventRecord(joined, side);
    cudaStreamWaitEvent(cudaStreamPerThread, joined, 0);
}
```

```cpp
#include <cuda_runtime.h>
#include <cuda.h>
#include <cuda_bf16.h>
#include <stdint.h>
#include <stddef.h>

#define CFG_X1 13
#define CFG_P1 46
#define CFG_P2 39
#define CFG_PT 100
#define CFG_L0 34
#define CFG_RA 33
#define CFG_T0 -310
#define CFG_Q0 14
#define CFG_Q2 69
#define CFG_Q3 30
#define CFG_T3 400
#define CFG_D3 2
#define CFG_PF7 18
#define CFG_TA 10
#define CFG_HOLD 14
#define CFG_EPI 3
#define CFG_X2 11
#define CFG_HOLD2 15
#define CFG_NA1 3
#define CFG_NA2 5
#define CFG_ORD1 0
#define CFG_ORD2 1
#define CFG_S3 12
#define CFG_D4 4

namespace w8 {

constexpr int M_ = 2048, K_ = 1024, N_ = 3584;
constexpr int CS = 16, NCL = 7, NCTA = CS * NCL;
constexpr int WA = 160, WB = 64, TN = 2 * WA + 2 * WB;
constexpr int NSLOT = 7, SLOT = WA * 64;
constexpr int NAJ = 1024;
constexpr int REV = 60;
constexpr int TA = CFG_TA;

constexpr int L0 = CFG_L0, RA = CFG_RA, RB64 = 64 * RA / (RA - 16);
constexpr int P1 = CFG_P1, P2 = CFG_P2, PT = CFG_PT, T0 = CFG_T0;
__device__ __forceinline__ int time_x(int x) { return max(x, L0 + (((x - L0) * RA) >> 4)); }
__device__ __forceinline__ int time_w(int q) { return min(L0 + ((q * RB64) >> 6), NAJ / NCL + q); }
__device__ __forceinline__ unsigned sched(int T) { return T * P2 + min(T, PT) * (P1 - P2); }
__device__ __forceinline__ int sched2(int q) { return (min(q, 160) - CFG_Q0) * CFG_Q2 + max(q - 160, 0) * CFG_Q3; }

constexpr int SM_A = 0;
constexpr int SM_RING = 131072;
constexpr int SM_STG = SM_RING + NSLOT * SLOT;
constexpr int SM_PAR = SM_STG + 3 * 8192;
constexpr int SM_CS = SM_PAR + 3 * TN * 2;
constexpr int SM_BAR = SM_CS + 128;
constexpr int B_FULLB = 0, B_FULLA = 56, B_PAR = 72, B_SW = 77, B_AFREE = 74  , B_FREE = 90,
              B_GO = 104, B_FILL = 128, B_CS = 131, B_RAWA = 132, B_RAWB = 145, B_END = 163;
constexpr int SM_TOTAL = SM_BAR + B_END * 8;
static_assert(SM_TOTAL <= 232448, "");

constexpr int F_W = 512, F_CS = 576;
struct Scratch {
    unsigned flag[768];
    int cs[2][TN];
    int sink[384];
    uint4 s8[(1024 + 8 * 256) * 128];
};
static_assert(offsetof(Scratch, s8) == 8192, "");
__device__ __align__(8192) Scratch g_scratch;
__device__ __forceinline__ unsigned* epoch(Scratch* sc, int r, int c) { return sc->flag + r * 32 + 16 + c; }

__device__ __forceinline__ void mbar_init(uint32_t bar, uint32_t cnt) {
    asm volatile("mbarrier.init.shared::cta.b64 [%0], %1;" :: "r"(bar), "r"(cnt) : "memory");
}
__device__ __forceinline__ void mbar_expect_tx(uint32_t bar, uint32_t bytes) {
    asm volatile("mbarrier.arrive.expect_tx.shared::cta.b64 _, [%0], %1;" :: "r"(bar), "r"(bytes) : "memory");
}
__device__ __forceinline__ void mbar_arrive(uint32_t bar) {
    asm volatile("mbarrier.arrive.shared::cta.b64 _, [%0];" :: "r"(bar) : "memory");
}
__device__ __forceinline__ void mbar_arrive_cluster(uint32_t bar) {
    asm volatile("mbarrier.arrive.shared::cluster.b64 _, [%0];" :: "r"(bar) : "memory");
}
__device__ __forceinline__ void mbar_wait(uint32_t bar, uint32_t parity = 0) {
    asm volatile("{\n.reg .pred p;\n.reg .u32 c;\n"
                 "mbarrier.try_wait.parity.shared::cta.b64 p, [%0], %1;\n"
                 "@p bra WAIT_DONE;\n"
                 "mov.u32 c, 0;\n"
                 "WAIT_LOOP:\n"
                 "mbarrier.try_wait.parity.shared::cta.b64 p, [%0], %1;\n"
                 "@p bra WAIT_DONE;\n"
                 "add.u32 c, c, 1;\nsetp.lt.u32 p, c, 0x100000;\n"
                 "@p bra WAIT_LOOP;\n"
                 "trap;\n"
                 "WAIT_DONE:\n}" :: "r"(bar), "r"(parity) : "memory");
}
__device__ __forceinline__ void mbar_wait2(uint32_t bar0, uint32_t bar1) {
    asm volatile("{\n.reg .pred p, q;\n.reg .u32 c;\nmov.u32 c, 0;\n"
                 "WAIT_LOOP:\n"
                 "mbarrier.try_wait.parity.shared::cta.b64 p, [%0], 0;\n"
                 "mbarrier.try_wait.parity.shared::cta.b64 q, [%1], 0;\n"
                 "and.pred p, p, q;\n"
                 "@p bra WAIT_DONE;\n"
                 "add.u32 c, c, 1;\nsetp.lt.u32 p, c, 0x100000;\n"
                 "@p bra WAIT_LOOP;\n"
                 "trap;\n"
                 "WAIT_DONE:\n}" :: "r"(bar0), "r"(bar1) : "memory");
}
__device__ __forceinline__ bool mbar_test(uint32_t bar) {
    uint32_t ok;
    asm volatile("{\n.reg .pred p;\nmbarrier.test_wait.parity.shared::cta.b64 p, [%1], 0;\nselp.u32 %0, 1, 0, p;\n}" : "=r"(ok) : "r"(bar) : "memory");
    return ok;
}
__device__ __forceinline__ bool mbar_test2(uint32_t bar0, uint32_t bar1) {
    uint32_t ok;
    asm volatile("{\n.reg .pred p, q;\nmbarrier.test_wait.parity.shared::cta.b64 p, [%1], 0;\n"
                 "mbarrier.test_wait.parity.shared::cta.b64 q, [%2], 0;\nand.pred p, p, q;\nselp.u32 %0, 1, 0, p;\n}"
                 : "=r"(ok) : "r"(bar0), "r"(bar1) : "memory");
    return ok;
}
__device__ __forceinline__ bool elect_one() {
    uint32_t ok;
    asm volatile("{\n.reg .pred p;\nelect.sync _|p, 0xffffffff;\nselp.u32 %0, 1, 0, p;\n}" : "=r"(ok));
    return ok;
}
__device__ __forceinline__ unsigned ld_flag(const unsigned* p) {
    unsigned v;
    asm volatile("ld.relaxed.gpu.global.u32 %0, [%1];" : "=r"(v) : "l"(p) : "memory");
    return v;
}
__device__ __forceinline__ uint4 lds128(uint32_t a) {
    uint4 v;
    asm volatile("ld.shared.v4.b32 {%0,%1,%2,%3}, [%4];" : "=r"(v.x), "=r"(v.y), "=r"(v.z), "=r"(v.w) : "r"(a) : "memory");
    return v;
}
__device__ __forceinline__ void sts128(uint32_t a, uint4 v) {
    asm volatile("st.shared.v4.b32 [%0], {%1,%2,%3,%4};" :: "r"(a), "r"(v.x), "r"(v.y), "r"(v.z), "r"(v.w) : "memory");
}
__device__ __forceinline__ uint32_t lds32(uint32_t a) {
    uint32_t v;
    asm volatile("ld.shared.b32 %0, [%1];" : "=r"(v) : "r"(a) : "memory");
    return v;
}
__device__ __forceinline__ void sts32(uint32_t a, uint32_t v) {
    asm volatile("st.shared.b32 [%0], %1;" :: "r"(a), "r"(v) : "memory");
}
__device__ __forceinline__ void stg128(void* p, uint4 v) {
    asm volatile("st.global.v4.b32 [%0], {%1,%2,%3,%4};" :: "l"(p), "r"(v.x), "r"(v.y), "r"(v.z), "r"(v.w) : "memory");
}
__device__ __forceinline__ unsigned pack4(unsigned a, unsigned b, unsigned c, unsigned d) {
    unsigned lo, r;
    asm("cvt.pack.sat.s8.s32.b32 %0, %1, %2, 0;" : "=r"(lo) : "r"(d), "r"(c));
    asm("cvt.pack.sat.s8.s32.b32 %0, %1, %2, %3;" : "=r"(r) : "r"(b), "r"(a), "r"(lo));
    return r;
}
__device__ __forceinline__ uint32_t mapa(uint32_t a, uint32_t r) {
    uint32_t o;
    asm("mapa.shared::cluster.u32 %0, %1, %2;" : "=r"(o) : "r"(a), "r"(r));
    return o;
}
__device__ __forceinline__ unsigned clk() {
    unsigned t;
    asm volatile("mov.u32 %0, %clock;" : "=r"(t));
    return t;
}
__device__ __forceinline__ void cluster_arrive() { asm volatile("barrier.cluster.arrive.relaxed.aligned;" ::: "memory"); }
__device__ __forceinline__ void cluster_wait() { asm volatile("barrier.cluster.wait.aligned;" ::: "memory"); }
__device__ __forceinline__ void fence_init() { asm volatile("fence.mbarrier_init.release.cluster;" ::: "memory"); }
__device__ __forceinline__ void flag_add(unsigned* p) { asm volatile("red.relaxed.gpu.global.add.u32 [%0], 1;" :: "l"(p) : "memory"); }
__device__ __forceinline__ void raw_load(const void* map, int y, int z, uint32_t dst, uint32_t bar) {
    asm volatile("cp.async.bulk.tensor.3d.shared::cluster.global.tile.mbarrier::complete_tx::bytes [%0], [%1, {0, %2, %3}], [%4];"
                 :: "r"(dst), "l"(map), "r"(y), "r"(z), "r"(bar) : "memory");
}
__device__ __forceinline__ void tile_load(Scratch* sc, uint32_t dst, int tile, uint32_t bar) {
    asm volatile("cp.async.bulk.shared::cluster.global.mbarrier::complete_tx::bytes [%0], [%1], %2, [%3];"
                 :: "r"(dst), "l"((const char*)sc->s8 + tile * 8192), "r"(8192), "r"(bar) : "memory");
}
__device__ __forceinline__ void tile_store(const void* map, int x, int y, uint32_t src) {
    asm volatile("cp.async.bulk.tensor.2d.global.shared::cta.tile.bulk_group [%0, {%1, %2}], [%3];"
                 :: "l"(map), "r"(x), "r"(y), "r"(src) : "memory");
}
__device__ __forceinline__ void st_async(uint32_t a, uint32_t v, uint32_t bar) {
    asm volatile("st.async.weak.shared::cluster.mbarrier::complete_tx::bytes.b32 [%0], %1, [%2];" :: "r"(a), "r"(v), "r"(bar) : "memory");
}
__device__ __forceinline__ void red_async(uint32_t a, int v, uint32_t bar) {
    asm volatile("red.async.relaxed.cluster.shared::cluster.mbarrier::complete_tx::bytes.add.s32 [%0], %1, [%2];" :: "r"(a), "r"(v), "r"(bar) : "memory");
}
__device__ __forceinline__ void red_shared(uint32_t a, int v) { asm volatile("red.shared.add.s32 [%0], %1;" :: "r"(a), "r"(v) : "memory"); }
__device__ __forceinline__ int sum4(unsigned v, int c) { return __dp4a((int)v, 0x01010101, c); }

constexpr uint32_t DESC_A_HI = 0x80000000u | (512 >> 4);
constexpr uint32_t DESC_B_HI = 512 >> 4;
template <int NR> __device__ __forceinline__ void wgmma_n160(int (&d)[NR], uint32_t alo, uint32_t blo, int scale_d) {
    asm volatile("{\n.reg .pred p;\n.reg .b64 da, db;\nsetp.ne.b32 p, %82, 0;\n"
        "mov.b64 da, {%80, %83};\nmov.b64 db, {%81, %84};\n"
        "wgmma.mma_async.sync.aligned.m64n160k32.s32.s8.s8 "
        "{%0, %1, %2, %3, %4, %5, %6, %7, %8, %9, %10, %11, %12, %13, %14, %15, "
        "%16, %17, %18, %19, %20, %21, %22, %23, %24, %25, %26, %27, %28, %29, %30, %31, "
        "%32, %33, %34, %35, %36, %37, %38, %39, %40, %41, %42, %43, %44, %45, %46, %47, "
        "%48, %49, %50, %51, %52, %53, %54, %55, %56, %57, %58, %59, %60, %61, %62, %63, "
        "%64, %65, %66, %67, %68, %69, %70, %71, %72, %73, %74, %75, %76, %77, %78, %79}, "
        "da, db, p;\n}\n"
        : "+r"(d[0]), "+r"(d[1]), "+r"(d[2]), "+r"(d[3]), "+r"(d[4]), "+r"(d[5]), "+r"(d[6]), "+r"(d[7]),
          "+r"(d[8]), "+r"(d[9]), "+r"(d[10]), "+r"(d[11]), "+r"(d[12]), "+r"(d[13]), "+r"(d[14]), "+r"(d[15]),
          "+r"(d[16]), "+r"(d[17]), "+r"(d[18]), "+r"(d[19]), "+r"(d[20]), "+r"(d[21]), "+r"(d[22]), "+r"(d[23]),
          "+r"(d[24]), "+r"(d[25]), "+r"(d[26]), "+r"(d[27]), "+r"(d[28]), "+r"(d[29]), "+r"(d[30]), "+r"(d[31]),
          "+r"(d[32]), "+r"(d[33]), "+r"(d[34]), "+r"(d[35]), "+r"(d[36]), "+r"(d[37]), "+r"(d[38]), "+r"(d[39]),
          "+r"(d[40]), "+r"(d[41]), "+r"(d[42]), "+r"(d[43]), "+r"(d[44]), "+r"(d[45]), "+r"(d[46]), "+r"(d[47]),
          "+r"(d[48]), "+r"(d[49]), "+r"(d[50]), "+r"(d[51]), "+r"(d[52]), "+r"(d[53]), "+r"(d[54]), "+r"(d[55]),
          "+r"(d[56]), "+r"(d[57]), "+r"(d[58]), "+r"(d[59]), "+r"(d[60]), "+r"(d[61]), "+r"(d[62]), "+r"(d[63]),
          "+r"(d[64]), "+r"(d[65]), "+r"(d[66]), "+r"(d[67]), "+r"(d[68]), "+r"(d[69]), "+r"(d[70]), "+r"(d[71]),
          "+r"(d[72]), "+r"(d[73]), "+r"(d[74]), "+r"(d[75]), "+r"(d[76]), "+r"(d[77]), "+r"(d[78]), "+r"(d[79])
        : "r"(alo), "r"(blo), "r"(scale_d), "r"(DESC_A_HI), "r"(DESC_B_HI));
}
template <int NR> __device__ __forceinline__ void wgmma_t128(int (&d)[NR], uint32_t alo, uint32_t blo, int scale_d) {
    asm volatile("{\n.reg .pred p;\n.reg .b64 da, db;\nsetp.ne.b32 p, %66, 0;\n"
        "mov.b64 da, {%64, %67};\nmov.b64 db, {%65, %68};\n"
        "wgmma.mma_async.sync.aligned.m64n128k32.s32.s8.s8 "
        "{%0, %1, %2, %3, %4, %5, %6, %7, %8, %9, %10, %11, %12, %13, %14, %15, "
        "%16, %17, %18, %19, %20, %21, %22, %23, %24, %25, %26, %27, %28, %29, %30, %31, "
        "%32, %33, %34, %35, %36, %37, %38, %39, %40, %41, %42, %43, %44, %45, %46, %47, "
        "%48, %49, %50, %51, %52, %53, %54, %55, %56, %57, %58, %59, %60, %61, %62, %63}, "
        "da, db, p;\n}\n"
        : "+r"(d[0]), "+r"(d[1]), "+r"(d[2]), "+r"(d[3]), "+r"(d[4]), "+r"(d[5]), "+r"(d[6]), "+r"(d[7]),
          "+r"(d[8]), "+r"(d[9]), "+r"(d[10]), "+r"(d[11]), "+r"(d[12]), "+r"(d[13]), "+r"(d[14]), "+r"(d[15]),
          "+r"(d[16]), "+r"(d[17]), "+r"(d[18]), "+r"(d[19]), "+r"(d[20]), "+r"(d[21]), "+r"(d[22]), "+r"(d[23]),
          "+r"(d[24]), "+r"(d[25]), "+r"(d[26]), "+r"(d[27]), "+r"(d[28]), "+r"(d[29]), "+r"(d[30]), "+r"(d[31]),
          "+r"(d[32]), "+r"(d[33]), "+r"(d[34]), "+r"(d[35]), "+r"(d[36]), "+r"(d[37]), "+r"(d[38]), "+r"(d[39]),
          "+r"(d[40]), "+r"(d[41]), "+r"(d[42]), "+r"(d[43]), "+r"(d[44]), "+r"(d[45]), "+r"(d[46]), "+r"(d[47]),
          "+r"(d[48]), "+r"(d[49]), "+r"(d[50]), "+r"(d[51]), "+r"(d[52]), "+r"(d[53]), "+r"(d[54]), "+r"(d[55]),
          "+r"(d[56]), "+r"(d[57]), "+r"(d[58]), "+r"(d[59]), "+r"(d[60]), "+r"(d[61]), "+r"(d[62]), "+r"(d[63])
        : "r"(alo), "r"(blo), "r"(scale_d), "r"(DESC_B_HI), "r"(DESC_A_HI));
}


__device__ __forceinline__ void wg_fence() { asm volatile("wgmma.fence.sync.aligned;" ::: "memory"); }
__device__ __forceinline__ void wg_commit() { asm volatile("wgmma.commit_group.sync.aligned;" ::: "memory"); }
template <int N> __device__ __forceinline__ void wg_wait() { asm volatile("wgmma.wait_group.sync.aligned %0;" :: "n"(N) : "memory"); }

__host__ __device__ constexpr int unit_of(int X1, int piece, int slab) {
    return piece < 2 ? (slab < X1 ? 2 * slab + piece : (piece ? 16 : X1) + slab) : 32 + (piece - 2) * 8 + (slab >> 1);
}
__host__ __device__ constexpr int col_of(int G) { return G == 4 ? 256 : (G > 4 && G < 9) ? 32 * G - 32 : 32 * G; }
struct BJob { int u, slab, G, pos; };
__host__ __device__ constexpr BJob decode_b(int X1, int q) {
    BJob j = {};
    if (q < 160) {
        j.u = q / 5; j.pos = q - j.u * 5;
        const int piece = j.u < 2 * X1 ? (j.u & 1) : (j.u >= X1 + 16);
        j.slab = j.u < 2 * X1 ? (j.u >> 1) : j.u - (piece ? 16 : X1);
        j.G = piece * 5 + j.pos;
    } else {
        q -= 160;
        j.u = 32 + (q >> 2); j.pos = q & 3;
        j.slab = (q >> 1) & 15;
        j.G = 10 + (q >> 5) * 2 + (q & 1);
    }
    return j;
}
__host__ __device__ constexpr int fb_of(int X1, int u) {
    return u < 2 * X1 ? (u & 1) * 32 + (u >> 1) : u < X1 + 16 ? u - X1 : u < 32 ? 16 + u : u < 40 ? u - 16 : u < 48 ? u + 8 : u - 24;
}
__host__ __device__ constexpr uint64_t slot_table(int X1, int piece) {
    uint64_t t = 0;
    if (piece < 2) for (int s = 0; s < 16; s++) t |= (uint64_t)(unit_of(X1, piece, s) % NSLOT) << (4 * s);
    else for (int s = 0; s < 8; s++) t |= (uint64_t)(unit_of(X1, piece, 2 * s) % NSLOT) << (4 * s);
    return t;
}
template <bool k2> __device__ __forceinline__ int stage_w(int t) { return (k2 && t < 9) ? SM_A + (7 + t) * 8192 : SM_STG + (t % 3) * 8192; }
template <bool k2> __host__ __device__ constexpr int ford(int g, int m) {
    constexpr int NA = k2 ? CFG_NA2 : CFG_NA1;
    if (k2 ? CFG_ORD2 : CFG_ORD1) return g ? NA + m : m < NA ? m : 5 + m;
    return g ? (m < NA - 1 ? 2 + 2 * m : NA + m) : (m < 2 ? m : m < NA ? 2 * m - 1 : 5 + m);
}
template <bool k2> __host__ __device__ constexpr uint64_t ford_table() {
    uint64_t t = 0;
    for (int g = 0; g < 2; g++) for (int m = 0; m < 5; m++) t |= (uint64_t)(g * 8 + m) << (4 * ford<k2>(g, m));
    return t;
}
struct Maps { CUtensorMap m[4]; };

__device__ __forceinline__ uint32_t bf2_mul(uint32_t a, uint32_t b) { asm("mul.rn.bf16x2 %0, %0, %1;" : "+r"(a) : "r"(b)); return a; }
__device__ __forceinline__ uint32_t epi(int a, int b, uint32_t zc, uint32_t sx, uint32_t sw, uint32_t bi) {
    uint32_t v;
    float fa = __int2float_rn(a), fb = __int2float_rn(b);
    asm("cvt.rn.bf16x2.f32 %0, %1, %2;" : "=r"(v) : "f"(fb), "f"(fa));
    if (CFG_EPI == 3) {
        asm("fma.rn.bf16x2 %0, %0, %1, %2;" : "+r"(v) : "r"(sw), "r"(zc));
        return v;
    }
    asm("sub.rn.bf16x2 %0, %0, %1;" : "+r"(v) : "r"(zc));
    if (CFG_EPI == 0) {
        v = bf2_mul(bf2_mul(v, sx), sw);
        asm("add.rn.bf16x2 %0, %0, %1;" : "+r"(v) : "r"(bi));
    } else {
        asm("fma.rn.bf16x2 %0, %0, %1, %2;" : "+r"(v) : "r"(sw), "r"(bi));
    }
    return v;
}
__device__ __forceinline__ uint32_t zero_term(int lo, int hi, float zx) {
    uint32_t z;
    asm("cvt.rn.bf16x2.f32 %0, %1, %2;" : "=r"(z) : "f"(__bfloat162float(__float2bfloat16_rn((float)hi)) * zx),
                                                    "f"(__bfloat162float(__float2bfloat16_rn((float)lo)) * zx));
    return z;
}
__device__ __forceinline__ uint32_t fold(uint32_t z, uint32_t sw, uint32_t bi) {
    if (CFG_EPI == 3) asm("fma.rn.bf16x2 %0, %1, %2, %3;" : "=r"(z) : "r"(z ^ 0x80008000u), "r"(sw), "r"(bi));
    return z;
}
__device__ __forceinline__ float ld_zx(const int* zero_x) { return __bfloat162float(__float2bfloat16_rn((float)__ldg(zero_x))); }
struct Par { uint4 zc, sw, bi; };
__device__ __forceinline__ Par ld_par(uint32_t p) { return {lds128(p), lds128(p + TN * 2), CFG_EPI == 3 ? uint4{} : lds128(p + TN * 4)}; }
__device__ __forceinline__ uint4 epi_row(const int (&a)[WA / 2], int o, const Par& p, uint32_t sx2) {
    uint4 r;
    r.x = epi(a[o + 0], a[o + 4], p.zc.x, sx2, p.sw.x, p.bi.x);
    r.y = epi(a[o + 8], a[o + 12], p.zc.y, sx2, p.sw.y, p.bi.y);
    r.z = epi(a[o + 1], a[o + 5], p.zc.z, sx2, p.sw.z, p.bi.z);
    r.w = epi(a[o + 9], a[o + 13], p.zc.w, sx2, p.sw.w, p.bi.w);
    return r;
}
template <bool k2> __device__ __forceinline__ void release(uint32_t go, int u, int lane) {
    const int v = u + NSLOT;
    if (k2) {
        const int q = v + lane;
        if (lane < (v < 48 ? 1 : 0)) mbar_arrive_cluster(mapa(go + (q >> 1) * 8, q & 1));
    } else {
        const int q = 5 * v - (v > 34 ? 3 : 0) + lane;
        if (lane < (v > 38 ? 0 : v == 34 ? 2 : 5)) mbar_arrive_cluster(mapa(go + (q >> 4) * 8, q & 15));
    }
}
__device__ __forceinline__ unsigned read_back(const uint4* d, int lane) { return ld_flag((const unsigned*)(d - lane + ((lane + 10) & 15) * 8 + 6)); }
__device__ __forceinline__ void publish(unsigned rb, unsigned mine, unsigned* flag) {
    if (__shfl_sync(~0u, rb ^ mine, 6)) asm volatile("fence.acq_rel.gpu;" ::: "memory");
    if (elect_one()) flag_add(flag);
}
#define CV_B(m, f)                                                                                                      \
    {                                                                                                                   \
        uint4 v0 = lds128(rdB + m * 512), v1 = lds128(rdB + m * 512 + 128);                                             \
        uint4 v2 = lds128(rdB + m * 512 + 256), v3 = lds128(rdB + m * 512 + 384);                                       \
        o[0].f = pack4(v0.x, v1.x, v2.x, v3.x); o[1].f = pack4(v0.y, v1.y, v2.y, v3.y);                                 \
        o[2].f = pack4(v0.z, v1.z, v2.z, v3.z); o[3].f = pack4(v0.w, v1.w, v2.w, v3.w);                                 \
    }

__device__ __forceinline__ void last_columns(Scratch* sc, const Maps& maps, const __nv_bfloat16* scale_x, const int* zero_x, const __nv_bfloat16* scale_w,
                                             const __nv_bfloat16* bias, uint32_t sb, int warp, int lane, unsigned t0) {
    constexpr int C_FULL = 0, C_EMPTY = 32, C_RAW = 64, C_GO = 80, C_PEER = 81, D3 = CFG_D3;
    const uint32_t bars = sb + SM_BAR;
    const int j = blockIdx.x & 3;
    while ((int)(t0 + CFG_T3 - clk()) > 0) ;
    const int s0 = (j & 1) * 8 + (warp >> 1) * 2;
    if (warp < 8) {
        if (elect_one()) {
#pragma unroll
            for (int i = 0; i < 2; i++) {
                const uint32_t bar = bars + (C_RAW + warp * 2 + i) * 8;
                mbar_init(bar, 1); mbar_expect_tx(bar, 8192);
                raw_load(maps.m + 1, (s0 + (i ^ (j >> 1))) * 64, N_ / 32 - 2 + (warp & 1), sb + SM_A + (warp * 2 + i) * 8192, bar);
            }
#pragma unroll
            for (int i = 0; i < 4; i++) { mbar_init(bars + (C_FULL + warp * 4 + i) * 8, 1); mbar_expect_tx(bars + (C_FULL + warp * 4 + i) * 8, 16384); }
#pragma unroll
            for (int i = 0; i < 4; i++) mbar_init(bars + (C_EMPTY + warp * 4 + i) * 8, 4);
            if (warp == 0) {
                mbar_init(bars + C_GO * 8, 8);
                mbar_init(bars + C_PEER * 8, 1); mbar_expect_tx(bars + C_PEER * 8, 32768 + 4096);
            }
        }
        if (warp < 2) sts32(sb + SM_PAR + threadIdx.x * 4, 0);
        fence_init();
    }
    __syncthreads();
    cluster_arrive();
    cluster_wait();
    if (warp >= 8) {
        asm volatile("setmaxnreg.dec.sync.aligned.u32 40;");
        if (warp < 12) {
            const unsigned ep = (ld_flag(epoch(sc, j * 4, 8)) + 1) * 4;
            const int mb = j * 4 + warp - 8, wg = (warp >> 1) & 1;
            unsigned rdy = 0;
            mbar_wait(bars + (wg ? C_EMPTY : C_GO) * 8);
#pragma unroll 1
            for (int s = 0; s < 16; s++) {
                for (int it = 0; !((rdy >> s) & 1); it++) {
                    rdy = __ballot_sync(~0u, (int)(ld_flag(sc->flag + mb * 32 + (lane & 15)) - ep) >= 0);
                    if (it > (1 << 22)) __trap();
                }
                if (s >= D3) mbar_wait(bars + (C_EMPTY + (s - (s < CFG_S3 ? D3 : CFG_D4)) * 2 + wg) * 8);
                if (elect_one()) tile_load(sc, sb + SM_A + ((s & 3) * 4 + warp - 8) * 8192, mb * 16 + s, bars + (C_FULL + s * 2 + wg) * 8);
            }
        }
    } else {
        asm volatile("setmaxnreg.inc.sync.aligned.u32 200;");
        const int wg = warp >> 2, w = warp & 3;
        const int c0 = (w >> 1) * 32 + (lane >> 2) * 4 + (w & 1) * 2, r0 = (lane & 3) * 2;
        const uint32_t sx2 = (uint32_t)__ldg((const unsigned short*)scale_x) * 0x10001u;
        uint32_t sw = __ldg((const unsigned*)(scale_w + N_ - WB + c0));
        const uint32_t bi = __ldg((const unsigned*)(bias + N_ - WB + c0));
        const float zxf = ld_zx(zero_x);
        int cs[4] = {0, 0, 0, 0};
        const uint32_t peer = mapa(sb, (j & 1) ^ 1);
#pragma unroll 1
        for (int i = 0; i < 2; i++) {
            const uint32_t rdB = sb + SM_A + (warp * 2 + i) * 8192 + (lane >> 3) * 2048 + (lane & 7) * 16;
            const uint32_t wr = SM_RING + (s0 + (i ^ (j >> 1))) * 4096 + (warp & 1) * 2048 + lane * 16;
            mbar_wait(bars + (C_RAW + warp * 2 + i) * 8);
            uint4 o[4];
            CV_B(0, x) CV_B(1, y) CV_B(2, z) CV_B(3, w)
#pragma unroll
            for (int k = 0; k < 4; k++) {
                sts128(sb + wr + k * 512, o[k]);
                asm volatile("st.async.weak.shared::cluster.mbarrier::complete_tx::bytes.v4.b32 [%0], {%1,%2,%3,%4}, [%5];"
                             :: "r"(peer + wr + k * 512), "r"(o[k].x), "r"(o[k].y), "r"(o[k].z), "r"(o[k].w), "r"(peer + SM_BAR + C_PEER * 8) : "memory");
                cs[k] = sum4(o[k].x, sum4(o[k].y, sum4(o[k].z, sum4(o[k].w, cs[k]))));
            }
        }
        __syncwarp();
        if (elect_one()) mbar_arrive(bars + C_GO * 8);
#pragma unroll
        for (int k = 0; k < 4; k++) {
            const uint32_t ca = SM_PAR + ((warp & 1) * 32 + (lane & 7) * 4 + k) * 4;
            red_shared(sb + ca, cs[k]);
            red_async(peer + ca, cs[k], peer + SM_BAR + C_PEER * 8);
        }
        mbar_wait(bars + C_PEER * 8);
        asm volatile("fence.proxy.async.shared::cta;" ::: "memory");
        asm volatile("bar.sync 1, 256;" ::: "memory");
        if (CFG_EPI) sw = bf2_mul(sw, sx2);
        const uint32_t zc = fold(zero_term(lds32(sb + SM_PAR + c0 * 4), lds32(sb + SM_PAR + c0 * 4 + 4), zxf), sw, bi);
        const uint32_t sd = (sb & 0x3FFFF) >> 4;
        int t[2][64];
        wg_fence();
#pragma unroll 1
        for (int s = 0; s < 16; s++) {
            const uint32_t db = ((sd + (SM_RING >> 4)) | (8 << 16)) + s * 256, da = ((sd + (SM_A >> 4)) | (1 << 16)) + ((s & 3) * 4 + wg * 2) * 512;
            mbar_wait(bars + (C_FULL + s * 2 + wg) * 8);
            wgmma_t128(t[0], db, da, s);
            wgmma_t128(t[1], db, da + 512, s);
            wgmma_t128(t[0], db + 16, da + 2, 1);
            wgmma_t128(t[1], db + 16, da + 514, 1);
            wg_commit();
            wg_wait<0>();
            if (elect_one()) mbar_arrive(bars + (C_EMPTY + s * 2 + wg) * 8);
        }
        asm volatile("bar.sync %0, 128;" :: "r"(3 + wg) : "memory");
        const uint32_t st0 = sb + SM_A + wg * 16384 + r0 * 128 + (((c0 >> 3) ^ r0) << 4) + (c0 & 7) * 2;
#pragma unroll
        for (int h = 0; h < 4; h++) {
            const uint32_t off = (h >> 1) * 32768 + (h & 1) * 8192;
#pragma unroll
            for (int q = 0; q < 8; q++) {
                const int o = (h & 1) * 32 + q * 4;
                sts32(st0 + off + q * 1024, epi(t[h >> 1][o], t[h >> 1][o + 2], zc, sx2, sw, bi));
                sts32((st0 ^ (5 * 128 + 5 * 16)) + off + q * 1024, epi(t[h >> 1][o + 1], t[h >> 1][o + 3], zc, sx2, sw, bi));
            }
            asm volatile("fence.proxy.async.shared::cta;" ::: "memory");
            asm volatile("bar.sync %0, 128;" :: "r"(3 + wg) : "memory");
            if (w == 0 && elect_one()) tile_store(maps.m + 2, N_ - WB, j * 512 + wg * 256 + h * 64, sb + SM_A + wg * 16384 + off);
        }
        if (w == 0) {
            asm volatile("cp.async.bulk.commit_group;" ::: "memory");
            asm volatile("cp.async.bulk.wait_group.read 0;" ::: "memory");
        }
        asm volatile("bar.sync 1, 256;" ::: "memory");
        if (threadIdx.x == 0) flag_add(epoch(sc, j * 4, 8));
    }
}

template <bool k2>
__global__ void __cluster_dims__(k2 ? 2 : CS, 1, 1) __launch_bounds__(512, 1)
w8a8_kernel(Scratch* sc, const char* __restrict__ qw, const __nv_bfloat16* __restrict__ scale_x, const int* __restrict__ zero_x,
            const __nv_bfloat16* __restrict__ scale_w, const __nv_bfloat16* __restrict__ bias, const __grid_constant__ Maps maps) {
    extern __shared__ __align__(1024) unsigned char smem_raw[];
    constexpr int NBJ = k2 ? 12 : 14, NF = NBJ, NU = k2 ? 40 : 48;
    constexpr int X1 = k2 ? CFG_X2 : CFG_X1;
    constexpr int HOLD = k2 ? CFG_HOLD2 : CFG_HOLD;
    constexpr int NA = k2 ? CFG_NA2 : CFG_NA1;
    const int b = blockIdx.x + (k2 ? NCTA : 0), r = b & 15, c = k2 ? NCL : b >> 4;
    const unsigned tc = clk();
    const uint32_t sb = (uint32_t)__cvta_generic_to_shared(smem_raw);
    const uint32_t bars = sb + SM_BAR;
    const unsigned tw = __shfl_sync(~0u, (tc & ~15u) | threadIdx.x >> 5, 0), t0 = tw + (k2 ? 0 : T0);
    const int warp = tw & 15, lane = threadIdx.x & 31;

    if (!k2 && warp == 12) {
        const int a = r * NCL + c;
        if (elect_one()) {
            mbar_init(bars + (B_RAWA + 3) * 8, 1);
            mbar_expect_tx(bars + (B_RAWA + 3) * 8, 8192);
            raw_load(maps.m, (a >> 6) * 2, ((a ^ REV) & 63) * 32, sb + SM_A + (a < NAJ % NCTA ? 15 : 13) * 8192, bars + (B_RAWA + 3) * 8);
        }
        __syncwarp();
    }
    if (warp == 9 && elect_one()) asm volatile("prefetch.tensormap [%0];" :: "l"(maps.m + 1) : "memory");
    if (k2 && blockIdx.x >= 16) {
        last_columns(sc, maps, scale_x, zero_x, scale_w, bias, sb, warp, lane, t0);
        return;
    }
    if (warp >= 12) {
        const int isw = k2 || warp == 14, t = k2 ? warp - 12 : isw ? 0 : (warp - 11) >> 1;
        const uint32_t bar = bars + ((isw ? B_RAWB : B_RAWA) + 3 + t) * 8;
        if ((k2 || warp != 12) && elect_one()) { mbar_init(bar, 1); mbar_expect_tx(bar, 8192); }
        __syncwarp();
        cluster_arrive();
        const int x = t * 16 + r, a = (x * NCL + c) ^ REV, sx = (x * 26) >> 8;
        static_assert(X1 >= 7, "");
        if ((k2 || warp != 12) && elect_one()) {
            const unsigned te = t0 + (k2 ? sched2(x) : (isw ? time_w(x) : time_x(x)) * P1);
            while ((int)(te - clk()) > 0) ;
            raw_load(maps.m + isw, isw ? sx * 64 : (a >> 6) * 2,
                     isw ? c * (TN / 32) + (int)((0x9765483210ull >> ((x - sx * 10) * 4)) & 15) : (a & 63) * 32,
                     sb + (k2 ? SM_A + 7 * 8192 : isw ? SM_STG : SM_A + 13 * 8192) + (t - (!isw && r * NCL + c < NAJ % NCTA)) * 8192, bar);
        }
        __syncwarp();
        if (!k2 && warp == 15) cluster_wait();
    }
    if (warp < 8) {
        const uint32_t p = bars + warp * 104;
        if (elect_one()) {
#pragma unroll
            for (int i = 0; i < 13; i++) mbar_init(p + i * 8, (!k2 && ((warp == 6 && i == 12) || (warp == 7 && i < 2))) ? 2 : 1);
            static_assert(B_FREE == 90 && B_GO == 104, "");
        }
        __syncwarp();
        const int i = warp * 13 + lane;
        if (lane < 13 && i < B_SW) mbar_expect_tx(p + lane * 8, i >= B_PAR ? (i < B_PAR + 2 ? WA * 2 : WB * 2) : (i & 16) || i >= 48 ? 8192 : WA * 64);
        fence_init();
    }
    if (warp < 8 || warp == 10) cluster_arrive();
    if (!k2 && warp == 10 && lane < CFG_PF7) {
        const int n = b * CFG_PF7 + lane, row = n / 10;
        asm volatile("prefetch.global.L2 [%0];" :: "l"(qw + row * (N_ * 4) + NCL * TN * 4 + (n - row * 10) * 128));
    }

    if (warp < 8) {
        asm volatile("setmaxnreg.inc.sync.aligned.u32 200;");
        const int wg = warp >> 2;
        const uint32_t sd = (sb & 0x3FFFF) >> 4;
        const uint32_t sx2 = (uint32_t)__ldg((const unsigned short*)scale_x) * 0x10001u;
        const uint32_t par = sb + SM_PAR + (lane & 3) * 16 + wg * 256;
        const uint32_t go = bars + B_GO * 8;
        const int w = warp & 3, pq = (lane >> 2) ^ (lane & 4);
        uint32_t so = (w * 16 + pq) * 128 + (((lane & 3) ^ pq) << 4);
        const int c0 = (w >> 1) * 32 + (lane >> 2) * 4 + (w & 1) * 2, r0 = (lane & 3) * 2;
        uint32_t pp = sb + SM_PAR + (2 * WA + wg * WB + c0) * 2, st0 = r0 * 128 + (((c0 >> 3) ^ r0) << 4) + (c0 & 7) * 2;
        constexpr int rn = k2 ? 1 : 4;
        int rq = lane < rn ? rn * (32 + wg * 8 + (k2 ? NSLOT : 8)) + (k2 ? 0 : 32) + lane : 1000;
        asm volatile("" : "+r"(so), "+r"(pp), "+r"(st0), "+r"(rq));
        cluster_wait();
        int a0[WA / 2], a1[WA / 2];
        uint32_t barB = bars + (B_FULLB + wg * 32) * 8;
        wg_fence();
        {
            uint64_t tbl = wg ? slot_table(X1, 1) : slot_table(X1, 0);
            uint32_t da = (sd + (SM_A >> 4)) | (1 << 16);
            int up = 99;
            bool rdy = false;
#pragma unroll 1
            for (int s = 0; s < 16; s++) {
                const uint32_t db = ((sd + (SM_RING >> 4)) | (8 << 16)) + ((uint32_t)tbl & 15) * (SLOT >> 4);
                const bool hold = wg && s == X1;
                if (hold || (!rdy && !mbar_test2(bars + (B_FULLA + s) * 8, barB))) {
                    wg_wait<0>();
                    release<k2>(go, up, lane); up = 99;
                    mbar_wait2(bars + (B_FULLA + s) * 8, barB);
                    if (hold) asm volatile("bar.sync 7, 256;" ::: "memory");
                }
                wgmma_n160(a0, da, db, s);
                wgmma_n160(a1, da + 256, db, s);
                wg_commit();
                if (!wg && s == HOLD) asm volatile("bar.arrive 7, 256;" ::: "memory");
                wg_wait<1>();
                release<k2>(go, up, lane);
                wgmma_n160(a0, da + 2, db + 16, 1);
                wgmma_n160(a1, da + 258, db + 16, 1);
                wg_commit();
                up = s < X1 ? 2 * s + wg : (wg ? 16 : X1) + s;
                tbl >>= 4; da += 512; barB += 8;
                rdy = mbar_test2(bars + (B_FULLA + s + 1) * 8, barB);
                if (s < 15) wg_wait<1>();
            }
        }
        mbar_wait2(bars + (B_PAR + wg) * 8, bars + B_SW * 8);
        Par P = ld_par(par);
        wg_wait<0>();
        release<k2>(go, wg ? 31 : X1 + 15, lane);
        bool ready = mbar_test(barB);
#define FILL_BEGIN(n0, n1) mbar_wait(bars + (B_FREE + (wg ? n1 : n0)) * 8);                                             \
                           const uint32_t buf = sb + SM_STG + (wg ? (n1 + NBJ) % 3 : (n0 + NBJ) % 3) * 8192;
#define FILL_END(n0, n1) __syncwarp();                                                                                  \
                         if (elect_one()) mbar_arrive(bars + (B_FILL + (wg ? n1 % 3 : n0 % 3)) * 8);
#define FILL_PAIR(a, J, PN, m)                                                                                          \
        {                                                                                                               \
            const uint4 v0 = epi_row(a, J * 16, P, sx2);                                                                \
            const Par Q = ld_par(par + J * 64 + 64);                                                                    \
            const uint4 v1 = epi_row(a, J * 16 + 2, P, sx2);                                                            \
            FILL_BEGIN(ford<k2>(0, m), ford<k2>(1, m))                                                                          \
            sts128(buf + so, v0); sts128(buf + so + 1024, v1);                                                          \
            if ((PN) >= 0) P = ld_par(par + (PN));                                                                      \
            sts128(buf + (so ^ 64), epi_row(a, J * 16 + 16, Q, sx2));                                                   \
            sts128(buf + (so ^ 64) + 1024, epi_row(a, J * 16 + 18, Q, sx2));                                            \
            FILL_END(ford<k2>(0, m), ford<k2>(1, m))                                                                            \
        }
#define RELEASE_N() { if (rq < (k2 ? NU : NBJ * 16)) mbar_arrive_cluster(mapa(go + (rq >> rn) * 8, rq & ((1 << rn) - 1))); rq += rn; nrel++; }
#define NARROW(p)                                                                                                       \
        {                                                                                                               \
            uint32_t tbl = (uint32_t)slot_table(X1, p), da = (sd + (SM_A >> 4)) | (1 << 16);                                \
            wg_fence();                                                                                                 \
            _Pragma("unroll 1") for (int i = 0; i < 8; i++) {                                                           \
                const uint32_t db = ((sd + (SM_RING >> 4)) | (8 << 16)) + (k2 ? (tbl & 15) * (SLOT >> 4) : ((i + 5) & 7) * 512); \
                if (!ready && !mbar_test(barB)) {                                                                       \
                    wg_wait<0>();                                                                                       \
                    if (p == 2) { _Pragma("unroll 1") while (nrel < i) RELEASE_N() }                                    \
                    mbar_wait(barB);                                                                                    \
                }                                                                                                       \
                _Pragma("unroll") for (int kk = 0; kk < 4; kk++)                                                        \
                    wgmma_t128(t, db + (kk >> 1) * 256 + (kk & 1) * 16, da + (kk >> 1) * 512 + (kk & 1) * 2, kk ? 1 : i); \
                wg_commit();                                                                                            \
                barB += 8;                                                                                              \
                ready = mbar_test(barB);                                                                                \
                if (p == 2 && nrel < i - 1) RELEASE_N()                                                                 \
                tbl >>= 4; da += 1024;                                                                                  \
                wg_wait<1>();                                                                                           \
            }                                                                                                           \
            if (p == 2) { if (nrel < 7) RELEASE_N() if (NA < 5) P = ld_par(par + pn); }                                            \
            else { mbar_wait(bars + (B_PAR + 3) * 8); zc = lds32(pp); sw = lds32(pp + TN * 2); bi = CFG_EPI == 3 ? 0 : lds32(pp + TN * 4); } \
            wg_wait<0>();                                                                                               \
            if (p == 2) RELEASE_N()                                                                                     \
        }
        int nrel = 0;
        const int pn = NA == 2 ? 0 : NA == 3 ? 128 : 512 - wg * 192;
        FILL_PAIR(a0, 0, 128, 0) FILL_PAIR(a0, 2, NA == 2 ? -1 : 0, 1)
        int t[64];
        uint32_t zc, sw, bi;
        if (NA == 2) { if (wg == 0) NARROW(2) else P = ld_par(par + pn); }
        FILL_PAIR(a1, 0, NA == 3 ? -1 : 128, 2)
        if (NA == 3) { if (wg == 0) NARROW(2) else P = ld_par(par + pn); }
        FILL_PAIR(a1, 2, NA == 4 ? -1 : 512 - wg * 192, 3)
        if (NA == 4) { if (wg == 0) NARROW(2) else P = ld_par(par + pn); }
        {
            const uint4 v0 = epi_row(a0, 64, P, sx2), v1 = epi_row(a0, 66, P, sx2);
            if (NA < 5 && !wg) mbar_wait(bars + (B_PAR + 2) * 8);
            FILL_BEGIN(ford<k2>(0, 4), ford<k2>(1, 4))
            const uint32_t s4 = buf + ((so >> 1) & ~63u) + (lane & 3) * 16;
            sts128(s4, v0); sts128(s4 + 512, v1);
            sts128(s4 + 4096, epi_row(a1, 64, P, sx2)); sts128(s4 + 4608, epi_row(a1, 66, P, sx2));
            FILL_END(ford<k2>(0, 4), ford<k2>(1, 4))
        }
        if (!(k2 && wg)) {
            if (NA == 5 && wg == 0) { NARROW(2) mbar_wait(bars + (B_PAR + 2) * 8); }
            if (!k2 && wg == 1) NARROW(3) else { zc = lds32(pp); sw = lds32(pp + TN * 2); bi = CFG_EPI == 3 ? 0 : lds32(pp + TN * 4); }
#define FILL_T(h)                                                                                                       \
            {                                                                                                           \
                FILL_BEGIN((10 + h), (12 + h))                                                                          \
                _Pragma("unroll") for (int j = 0; j < 8; j++) {                                                         \
                    const int o = h * 32 + j * 4;                                                                       \
                    sts32(buf + st0 + j * 1024, epi(t[o], t[o + 2], zc, sx2, sw, bi));                                  \
                    sts32(buf + (st0 ^ (5 * 128 + 5 * 16)) + j * 1024, epi(t[o + 1], t[o + 3], zc, sx2, sw, bi));       \
                }                                                                                                       \
                FILL_END((10 + h), (12 + h))                                                                            \
            }
            FILL_T(0) FILL_T(1)
        }
        if (threadIdx.x == 0) flag_add(epoch(sc, r, c));
    } else {
        const int g = r * NCL + c, na = k2 ? 0 : NAJ / NCTA + (g < NAJ % NCTA);
        int cw = NF;
        if (warp >= 12) {
            asm volatile("setmaxnreg.dec.sync.aligned.u32 80;");
            if (warp < 14) {
                const int c4 = (lane ^ (lane >> 3)) & 3, ln = ((lane >> 2) ^ (lane & 4)) * 2 + (c4 >> 1);
                const uint32_t rd0 = sb + SM_A + 13 * 8192 + ln * 128 + ((((c4 & 1) << 2) ^ (ln & 7)) << 4);
#pragma unroll 1
                for (int t = warp - 12, sl = na == 9 ? t : 2 - 2 * t; t < na; t += 2, sl = sl ? sl - 1 : 2) {
                    const uint32_t rdA = rd0 + sl * 8192;
                    const int a = (t * NCTA + g) ^ REV, f = (a & 60) * 4 + (a >> 6);
                    uint4* const d = sc->s8 + (f * 4 + (a & 3)) * 128 + lane;
                    uint4 o[4];
                    mbar_wait(bars + (B_RAWA + 3 + t) * 8);
#pragma unroll
                    for (int i = 0; i < 4; i++) {
                        uint4 v0 = lds128(rdA + i * 2048), v1 = lds128((rdA ^ 16) + i * 2048);
                        uint4 v2 = lds128((rdA ^ 32) + i * 2048), v3 = lds128((rdA ^ 48) + i * 2048);
                        o[i].x = pack4(v0.x, v0.y, v0.z, v0.w); o[i].y = pack4(v1.x, v1.y, v1.z, v1.w);
                        o[i].z = pack4(v2.x, v2.y, v2.z, v2.w); o[i].w = pack4(v3.x, v3.y, v3.z, v3.w);
                    }
#pragma unroll
                    for (int i = 0; i < 4; i++) stg128(d + i * 32, o[i]);
                    asm volatile("fence.proxy.async.global;" ::: "memory");
                    __syncwarp();
                    const unsigned rb = read_back(d, lane);
                    if (t < 2) cluster_wait();
                    if (elect_one()) mbar_arrive(bars + ((t < na - 3 ? B_RAWA : B_AFREE + 13) + sl) * 8);
                    publish(rb, o[0].x, sc->flag + (a & 60) * 8 + (a >> 6));
                }
                cw = warp - 12;
            }
            if (!k2) {
                const int hw = warp & 1;
                const uint32_t rd0 = sb + SM_STG + hw * 4096 + (lane >> 3) * 1024 + (lane & 7) * 16;
                const int myG = decode_b(X1, (lane & 15) * 16 + r).G;
#pragma unroll 1
                for (int t = warp < 14 ? TA : 0; t < NBJ; t += warp < 14 ? NBJ : t == TA - 1 ? 2 : 1) {
                    const int sl = t % 3;
                    const uint32_t rdB = rd0 + sl * 8192;
                    char* const d = (char*)sc->s8 + (1024 + c * 256 + t * 16 + r) * 2048 + hw * 256 + (lane >> 4) * 128 + (lane & 7) * 16 + (lane & 8);
                    uint2 o[4];
                    mbar_wait(bars + (B_RAWB + 3 + t) * 8);
                    CV_B(0, x) CV_B(1, y)
#pragma unroll
                    for (int i = 0; i < 4; i++) asm volatile("st.global.v2.b32 [%0], {%1,%2};" :: "l"(d + i * 512), "r"(o[i].x), "r"(o[i].y) : "memory");
                    if (t == 0 && warp == 14) cluster_wait();
                    if (elect_one()) mbar_arrive(bars + (t >= NBJ - 3 ? B_FREE + t - (NBJ - 3) : B_RAWB + sl) * 8);
                    asm volatile("fence.proxy.async.global;" ::: "memory");
                    __syncwarp();
                    if (elect_one()) mbar_arrive(bars + (B_GO + t) * 8);
                    int cs[4];
#pragma unroll
                    for (int i = 0; i < 4; i++) cs[i] = sum4(o[i].x, sum4(o[i].y, 0));
                    const int p01 = cs[0] + cs[1] * 65536, p23 = cs[2] + cs[3] * 65536;
                    const bool h = lane & 16;
                    int x = (h ? p23 : p01) + __shfl_xor_sync(~0u, h ? p01 : p23, 16);
                    x += __shfl_xor_sync(~0u, x, 8);
                    const int lo = (int)(short)x, v = (lane & 8) ? (x - lo) >> 16 : lo;
                    const int G = __shfl_sync(~0u, myG, t);
                    if (G != r) {
                        red_async(mapa(sb + SM_CS + lane * 4, G), v, mapa(bars + B_CS * 8, G));
                    } else {
                        red_shared(sb + SM_CS + lane * 4, v);
                        __syncwarp();
                        if (elect_one()) mbar_arrive(bars + B_CS * 8);
                    }
                }
            } else {
                const uint32_t rd0 = sb + (lane >> 3) * 2048 + (lane & 7) * 16;
                const BJob mb = decode_b(X1, (lane & 15) * 16 + r);
                const int myG = mb.G | mb.u << 8;
#pragma unroll 1
                for (int t = warp - 12; t < NBJ; t += 4) {
                    const uint32_t rdB = rd0 + stage_w<k2>(t);
                    uint4* const d = sc->s8 + (1024 + c * 256 + t * 16 + r) * 128 + lane;
                    uint4 o[4];
                    mbar_wait(bars + (B_RAWB + 3 + t) * 8);
                    CV_B(0, x) CV_B(1, y) CV_B(2, z) CV_B(3, w)
#pragma unroll
                    for (int i = 0; i < 4; i++) stg128(d + i * 32, o[i]);
                    if (t < 4) cluster_wait();
                    if (elect_one()) mbar_arrive(bars + (B_FREE + t - (NBJ - 3)) * 8);
                    asm volatile("fence.proxy.async.global;" ::: "memory");
                    __syncwarp();
                    const unsigned rb = read_back(d, lane), ep = ld_flag(epoch(sc, r, c));
                    int cs[4];
#pragma unroll
                    for (int i = 0; i < 4; i++) cs[i] = sum4(o[i].x, sum4(o[i].y, sum4(o[i].z, sum4(o[i].w, 0))));
                    const bool h = lane & 16, odd = lane & 8;
                    int x = (h ? cs[2] : cs[0]) + __shfl_xor_sync(~0u, h ? cs[0] : cs[2], 16);
                    int y = (h ? cs[3] : cs[1]) + __shfl_xor_sync(~0u, h ? cs[1] : cs[3], 16);
                    const int v = (odd ? y : x) + __shfl_xor_sync(~0u, odd ? x : y, 8);
                    const int gu = __shfl_sync(~0u, myG, t);
                    publish(rb, o[0].x, sc->flag + F_W + (gu >> 8));
                    const int old = atomicAdd(sc->cs[ep & 1] + col_of(gu & 255) + (lane & 7) * 4 + (lane >> 3), v);
                    if (old == 0x7FFFFFFF) sc->sink[0] = old;
                    __syncwarp();
                    if (elect_one()) flag_add(sc->flag + F_CS + (gu & 255) / 5);
                }
            }
        } else {
            asm volatile("setmaxnreg.dec.sync.aligned.u32 32;");
            if (warp == 11) {
                if (elect_one()) {
#pragma unroll
                    for (int i = 0; i < (k2 ? NU / 2 : NBJ); i++)
                        mbar_init(bars + (B_GO + i) * 8, k2 ? (i * 2 + (r & 1) >= NSLOT ? 9 : 1) : (i * 16 + r >= NSLOT * 5 ? 2 + 4 * CS : 2));
#pragma unroll
                    for (int i = 0; i < 3; i++) mbar_init(bars + (B_FILL + i) * 8, 4);
                }
                const int u2 = lane * 2 + (r & 1), q = k2 ? (u2 < 32 ? 5 * u2 : 4 * u2 + 32) : (lane & 15) * 16 + r;
                const BJob bj = decode_b(X1, q);
                unsigned seen = 0;
                if (!k2) {
                    const int nself = __popc(__ballot_sync(~0u, lane < NBJ && bj.G == r));
                    sts32(sb + SM_CS + lane * 4, 0);
                    if (lane == 0) {
                        mbar_init(bars + B_CS * 8, 1 + 2 * nself);
                        mbar_expect_tx(bars + B_CS * 8, (16 - nself) * 256);
                    }
                    seen = lds32(sb + SM_CS + lane * 4);
                }
                fence_init();
                asm volatile("barrier.cluster.arrive.relaxed.aligned;" :: "r"(seen) : "memory");
                const char* src = (const char*)sc->s8 + (1024 + c * 256 + q) * 2048;
                const uint32_t dst = sb + SM_RING + ((!k2 && q >= 160) ? ((q + 20) & 31) * 2048 : (bj.u % NSLOT) * SLOT + bj.pos * 2048);
                const uint32_t fb = bars + (B_FULLB + fb_of(X1, bj.u)) * 8;
                cluster_wait();
                {
                    const uint32_t sx2 = (uint32_t)__ldg((const unsigned short*)scale_x) * 0x10001u;
#pragma unroll
                    for (int i = lane; i < TN / 4; i += 32) {
                        const bool hi = i >= TN / 8;
                        uint4 v = __ldg((const uint4*)((hi ? bias : scale_w) + c * TN) + (hi ? i - TN / 8 : i));
                        if (CFG_EPI && !hi) v = {bf2_mul(v.x, sx2), bf2_mul(v.y, sx2), bf2_mul(v.z, sx2), bf2_mul(v.w, sx2)};
                        sts128(sb + SM_PAR + TN * 2 + i * 16, v);
                    }
                    __syncwarp();
                    if (elect_one()) mbar_arrive(bars + B_SW * 8);
                }
#pragma unroll 1
                for (int i = 0; i < (k2 ? NU / 2 : NBJ); i++) {
                    mbar_wait(bars + (B_GO + i) * 8);
                    if (lane == i) {
                        asm volatile("cp.async.bulk.shared::cluster.global.mbarrier::complete_tx::bytes.multicast::cluster [%0], [%1], %2, [%3], %4;"
                                     :: "r"(dst), "l"(src), "r"(k2 ? (u2 < 32 ? SLOT : 8192) : 2048), "r"(fb), "h"((uint16_t)(k2 ? 3 : 0xFFFF)) : "memory");
                    }
                    __syncwarp();
                }
            } else if (warp == 10) {
                const unsigned ep = (__shfl_sync(~0u, ld_flag(sc->flag + r * 32 + (lane < 16 ? lane : 16 + c)), 16) + 1) * 4;
                const unsigned* f = sc->flag + r * 32 + (lane & 15);
                bool dn = lane >= 16;
                const bool fr = lane < (k2 ? 7 : 13);
                cluster_wait();
                for (int it = 0;; it++) {
                    const unsigned v = ld_flag(f);
                    if (!dn && (int)(v - ep) >= 0 && (fr || mbar_test(bars + (B_AFREE + lane) * 8))) {
                        dn = true;
                        tile_load(sc, sb + SM_A + lane * 8192, r * 16 + lane, bars + (B_FULLA + lane) * 8);
                    }
                    if (__all_sync(~0u, dn)) break;
                    if (it > (1 << 22)) __trap();
                }
            } else {
                const bool isw = warp == 9;
                const uint32_t rb = bars + (isw ? B_RAWB : B_RAWA) * 8;
                if (elect_one()) {
#pragma unroll
                    for (int i = 0; i < 13; i++) if (i < 3 || i >= (k2 ? 7 : 6)) mbar_init(rb + i * 8, (i < 3 && isw && !k2) ? 2 : 1);
                    if (isw) {
#pragma unroll
                        for (int i = 13; i < 17; i++) mbar_init(rb + i * 8, 1);
                        if (!k2) { mbar_init(rb + 4 * 8, 1); mbar_init(rb + 5 * 8, 1); }
                    }
                }
                __syncwarp();
                const int nj = isw ? NBJ : na, j0 = k2 ? 4 : isw ? 1 : 3;
                if (lane >= j0 && lane < nj) mbar_expect_tx(rb + (3 + lane) * 8, 8192);
                fence_init();
                cluster_arrive();
                const unsigned e0 = k2 ? ld_flag(epoch(sc, r, c)) : 0;
                const int k = lane / 3, x = lane * 16 + r;
                int sl = lane - k * 3, y, z, T;
                if (isw) {
                    const BJob bj = decode_b(X1, x & 255);
                    y = bj.slab * 64; z = (c * TN + col_of(bj.G)) >> 5; T = time_w(x);
                } else {
                    const int a = (lane * NCTA + g) ^ REV;
                    y = (a >> 6) * 2; z = (a & 63) * 32; T = time_x(x);
                    if (na == 10) sl = sl ? sl - 1 : 2;
                }
                const unsigned te = t0 + (k2 ? sched2(x) : sched(T));
                const uint32_t sd = sb + (isw ? stage_w<k2>(lane) : SM_A + (13 + sl) * 8192);
#pragma unroll 1
                for (int t = j0; t < nj; t++) {
                    if (lane == t) {
                        if (t >= 3 && !k2) mbar_wait(rb + sl * 8, (k & 1) ^ 1);
                        while ((int)(te - clk()) > 0) ;
                        raw_load(maps.m + isw, y, z, sd, rb + (3 + t) * 8);
                    }
                    __syncwarp();
                }
                cluster_wait();
                if (elect_one()) asm volatile("prefetch.tensormap [%0];" :: "l"(maps.m + 2 + isw) : "memory");
                if (!isw) cw = 2;
                if (k2) {
                    if (!isw) {
                        if (lane < TN / 16) sc->cs[(e0 & 1) ^ 1][r * (TN / 16) + lane] = 0;
                        const int u = lane * 2 + (r & 1);
                        const unsigned tg = (e0 + 1) * (u < 32 ? 5 : 4);
                        bool dn = u >= NU;
                        for (int it = 0;; it++) {
                            if (!dn && (int)(ld_flag(sc->flag + F_W + u) - tg) >= 0) {
                                dn = true;
                                mbar_arrive(bars + (B_GO + lane) * 8);
                            }
                            if (__all_sync(~0u, dn)) break;
                            if (it > (1 << 22)) __trap();
                        }
                    } else {
                        const float zxf = ld_zx(zero_x);
                        if (CFG_EPI == 3) mbar_wait(bars + B_SW * 8);
#pragma unroll 1
                        for (int h = 0; h < 3; h++) {
                            for (int it = 0; (int)(ld_flag(sc->flag + F_CS + h) - (e0 + 1) * (h < 2 ? 80 : 32)) < 0; it++) if (it > (1 << 22)) __trap();
                            int2 v[3];
                            int i[3];
#pragma unroll
                            for (int j = 0; j < 3; j++) {
                                i[j] = (j < 2 ? h * 64 + j * 32 : 128 + h * 16) + lane;
                                v[j] = __ldcg((const int2*)sc->cs[e0 & 1] + i[j]);
                            }
#pragma unroll
                            for (int j = 0; j < 3; j++) {
                                const uint32_t pa = sb + SM_PAR + i[j] * 4;
                                const uint32_t z = fold(zero_term(v[j].x, v[j].y, zxf), lds32(pa + TN * 2), lds32(pa + TN * 4));
                                if (h < 2 ? (j < 2 || lane < 16) : j == 2) st_async(pa, z, bars + (B_PAR + h) * 8);
                            }
                        }
                    }
                }
            }
        }
        if (!k2 && r < NBJ && warp == (r < 10 ? 8 : 10)) {
            const float zxf = ld_zx(zero_x);
            const int w = lane & 15;
            uint32_t sw = 0, bi = 0;
            if (CFG_EPI == 3) { mbar_wait(bars + B_SW * 8); sw = lds32(sb + SM_PAR + TN * 2 + col_of(r) * 2 + w * 4); bi = lds32(sb + SM_PAR + TN * 4 + col_of(r) * 2 + w * 4); }
            mbar_wait(bars + B_CS * 8);
            const uint32_t ca = sb + SM_CS + ((w >> 1) + (w & 1) * 16) * 4;
            const uint32_t z = fold(zero_term(lds32(ca), lds32(ca + 32), zxf), sw, bi);
            const int piece = r < 10 ? (r >= 5) : (r - 6) >> 1;
#pragma unroll 1
            for (int i = lane >> 4; i < CS; i += 2) st_async(mapa(sb + SM_PAR + col_of(r) * 2 + w * 4, i), z, mapa(bars + (B_PAR + piece) * 8, i));
        }
#pragma unroll 1
        for (int n = cw, k = 0; n < NF; n += 3, k ^= 1) {
            const int gm = (int)(ford_table<k2>() >> (4 * n)), g = (gm >> 3) & 1, m = gm & 7;
            const int x = n >= 10 ? (n >> 1) * 64 : m == 4 ? 256 + g * 32 : g * 128 + (m & 1) * 64;
            const int y = n >= 10 ? (n & 1) * 64 : (m & 2) * 32;
            mbar_wait(bars + (B_FILL + cw) * 8, k);
            asm volatile("fence.proxy.async.shared::cta;" ::: "memory");
            if (elect_one()) tile_store(maps.m + (n < 10 && m == 4 ? 3 : 2), c * TN + x, r * 128 + y, sb + SM_STG + ((cw + NBJ) % 3) * 8192);
            asm volatile("cp.async.bulk.commit_group;" ::: "memory");
            asm volatile("cp.async.bulk.wait_group.read 0;" ::: "memory");
            __syncwarp();
            if (n < NF - 3 && elect_one()) mbar_arrive(bars + (B_FREE + 3 + n) * 8);
        }
    }
}

__global__ void __launch_bounds__(256)
w8a8_plain(const int* __restrict__ qx, const int* __restrict__ qw, const __nv_bfloat16* __restrict__ scale_x, const int* __restrict__ zero_x,
           const __nv_bfloat16* __restrict__ scale_w, const __nv_bfloat16* __restrict__ bias, __nv_bfloat16* __restrict__ out) {
    __shared__ int xs[16][K_ / 4];
    const int n = (blockIdx.x * 256 + threadIdx.x) * 2, m0 = blockIdx.y * 16;
    for (int i = threadIdx.x; i < 16 * K_ / 4; i += 256) {
        const uint4 v = ((const uint4*)qx)[m0 * (K_ / 4) + i];
        xs[i / (K_ / 4)][i % (K_ / 4)] = pack4(v.x, v.y, v.z, v.w);
    }
    __syncthreads();
    int acc[16][2] = {}, cs[2] = {};
    for (int k = 0; k < K_ / 4; k++) {
        uint2 v[4];
#pragma unroll
        for (int i = 0; i < 4; i++) v[i] = *(const uint2*)(qw + (k * 4 + i) * N_ + n);
        const unsigned w0 = pack4(v[0].x, v[1].x, v[2].x, v[3].x), w1 = pack4(v[0].y, v[1].y, v[2].y, v[3].y);
        cs[0] = sum4(w0, cs[0]); cs[1] = sum4(w1, cs[1]);
#pragma unroll
        for (int i = 0; i < 16; i++) { acc[i][0] = __dp4a(xs[i][k], (int)w0, acc[i][0]); acc[i][1] = __dp4a(xs[i][k], (int)w1, acc[i][1]); }
    }
    const uint32_t sx2 = (uint32_t)*(const unsigned short*)scale_x * 0x10001u, bi = *(const unsigned*)(bias + n);
    uint32_t sw = *(const unsigned*)(scale_w + n);
    if (CFG_EPI) sw = bf2_mul(sw, sx2);
    const uint32_t zc = fold(zero_term(cs[0], cs[1], ld_zx(zero_x)), sw, bi);
#pragma unroll
    for (int i = 0; i < 16; i++) *(unsigned*)(out + (m0 + i) * N_ + n) = epi(acc[i][0], acc[i][1], zc, sx2, sw, bi);
}

}

typedef CUresult (*EncodeFn)(CUtensorMap*, CUtensorMapDataType, cuuint32_t, void*, const cuuint64_t*, const cuuint64_t*,
                             const cuuint32_t*, const cuuint32_t*, CUtensorMapInterleave, CUtensorMapSwizzle,
                             CUtensorMapL2promotion, CUtensorMapFloatOOBfill);

extern "C" void kernel_launch(void* const* d_in, const int* in_sizes, int n_in, void* d_out, int out_size) {
    using namespace w8;
    static EncodeFn encode = nullptr;
    static cudaStream_t side;
    static cudaEvent_t started, joined;
    static int clusters = -1;
    static Scratch* sc;
    cudaLaunchConfig_t cfg = {};
    cfg.gridDim = dim3(NCTA); cfg.blockDim = dim3(512); cfg.dynamicSmemBytes = SM_TOTAL; cfg.stream = cudaStreamPerThread;
    if (clusters < 0) {
        void* fn = nullptr;
        cudaDriverEntryPointQueryResult qr;
        cudaGetDriverEntryPoint("cuTensorMapEncodeTiled", &fn, cudaEnableDefault, &qr);
        encode = (EncodeFn)fn;
        cudaGetSymbolAddress((void**)&sc, g_scratch);
        cudaStreamCreateWithFlags(&side, cudaStreamNonBlocking);
        cudaEventCreateWithFlags(&started, cudaEventDisableTiming);
        cudaEventCreateWithFlags(&joined, cudaEventDisableTiming);
        cudaFuncSetAttribute(w8a8_kernel<false>, cudaFuncAttributeMaxDynamicSharedMemorySize, SM_TOTAL);
        cudaFuncSetAttribute(w8a8_kernel<true>, cudaFuncAttributeMaxDynamicSharedMemorySize, SM_TOTAL);
        cudaFuncSetAttribute(w8a8_kernel<false>, cudaFuncAttributeNonPortableClusterSizeAllowed, 1);
        if (cudaOccupancyMaxActiveClusters(&clusters, w8a8_kernel<false>, &cfg) != cudaSuccess) { clusters = 0; cudaGetLastError(); }
    }
    const __nv_bfloat16 *sx = (const __nv_bfloat16*)d_in[2], *sw = (const __nv_bfloat16*)d_in[4], *bias = (const __nv_bfloat16*)d_in[5];
    const int* zx = (const int*)d_in[3];
    if (clusters < NCL) {
        w8a8_plain<<<dim3(N_ / 512, M_ / 16), 256, 0, cudaStreamPerThread>>>((const int*)d_in[0], (const int*)d_in[1], sx, zx, sw, bias, (__nv_bfloat16*)d_out);
        return;
    }
    Maps maps;
    const cuuint32_t es[3] = {1, 1, 1};
    {
        const cuuint64_t dim[3] = {32, K_ / 32, M_}, str[2] = {128, K_ * 4};
        const cuuint32_t box[3] = {32, 2, 32};
        encode(&maps.m[0], CU_TENSOR_MAP_DATA_TYPE_INT32, 3, d_in[0], dim, str, box, es, CU_TENSOR_MAP_INTERLEAVE_NONE,
               CU_TENSOR_MAP_SWIZZLE_128B, CU_TENSOR_MAP_L2_PROMOTION_NONE, CU_TENSOR_MAP_FLOAT_OOB_FILL_NONE);
    }
    {
        const cuuint64_t dim[3] = {32, K_, N_ / 32}, str[2] = {N_ * 4, 128};
        const cuuint32_t box[3] = {32, 64, 1};
        encode(&maps.m[1], CU_TENSOR_MAP_DATA_TYPE_INT32, 3, d_in[1], dim, str, box, es, CU_TENSOR_MAP_INTERLEAVE_NONE,
               CU_TENSOR_MAP_SWIZZLE_NONE, CU_TENSOR_MAP_L2_PROMOTION_NONE, CU_TENSOR_MAP_FLOAT_OOB_FILL_NONE);
    }
    for (int i = 0; i < 2; i++) {
        const cuuint64_t dim[2] = {N_, M_}, str[1] = {N_ * 2};
        const cuuint32_t box[2] = {i ? 32u : 64u, i ? 128u : 64u};
        encode(&maps.m[2 + i], CU_TENSOR_MAP_DATA_TYPE_BFLOAT16, 2, d_out, dim, str, box, es, CU_TENSOR_MAP_INTERLEAVE_NONE,
               i ? CU_TENSOR_MAP_SWIZZLE_NONE : CU_TENSOR_MAP_SWIZZLE_128B, CU_TENSOR_MAP_L2_PROMOTION_NONE, CU_TENSOR_MAP_FLOAT_OOB_FILL_NONE);
    }
    cudaLaunchAttribute at;
    at.id = cudaLaunchAttributeProgrammaticEvent;
    at.val.programmaticEvent.event = started; at.val.programmaticEvent.flags = 0; at.val.programmaticEvent.triggerAtBlockStart = 1;
    cfg.attrs = &at; cfg.numAttrs = 1;
    cudaLaunchKernelEx(&cfg, w8a8_kernel<false>, sc, (const char*)d_in[1], sx, zx, sw, bias, maps);
    cudaStreamWaitEvent(side, started, 0);
    cfg.gridDim = dim3(20); cfg.stream = side; cfg.numAttrs = 0;
    cudaLaunchKernelEx(&cfg, w8a8_kernel<true>, sc, (const char*)d_in[1], sx, zx, sw, bias, maps);
    cudaEventRecord(joined, side);
    cudaStreamWaitEvent(cudaStreamPerThread, joined, 0);
}
```

```cpp
#include <cuda_runtime.h>
#include <cuda.h>
#include <cuda_bf16.h>
#include <stdint.h>
#include <stddef.h>

#define CFG_X1 13
#define CFG_P1 46
#define CFG_P2 39
#define CFG_PT 100
#define CFG_L0 34
#define CFG_RA 33
#define CFG_T0 -550
#define CFG_Q0 14
#define CFG_Q2 69
#define CFG_Q3 30
#define CFG_T3 400
#define CFG_D3 2
#define CFG_PF7 18
#define CFG_TA 10
#define CFG_HOLD 14
#define CFG_EPI 3
#define CFG_X2 11
#define CFG_HOLD2 15
#define CFG_NA1 3
#define CFG_NA2 5
#define CFG_ORD1 0
#define CFG_ORD2 1
#define CFG_S3 12
#define CFG_D4 4
#define CFG_PG 8

namespace w8 {

constexpr int M_ = 2048, K_ = 1024, N_ = 3584;
constexpr int CS = 16, NCL = 7, NCTA = CS * NCL;
constexpr int WA = 160, WB = 64, TN = 2 * WA + 2 * WB;
constexpr int NSLOT = 7, SLOT = WA * 64;
constexpr int NAJ = 1024;
constexpr int REV = 60;
constexpr int TA = CFG_TA;

constexpr int L0 = CFG_L0, RA = CFG_RA, RB64 = 64 * RA / (RA - 16);
constexpr int P1 = CFG_P1, P2 = CFG_P2, PT = CFG_PT, T0 = CFG_T0;
__device__ __forceinline__ int time_x(int x) { return max(x, L0 + (((x - L0) * RA) >> 4)); }
__device__ __forceinline__ int time_w(int q) { return min(L0 + ((q * RB64) >> 6), NAJ / NCL + q); }
__device__ __forceinline__ unsigned sched(int T) { return T * P2 + min(T, PT) * (P1 - P2); }
__device__ __forceinline__ int sched2(int q) { return (min(q, 160) - CFG_Q0) * CFG_Q2 + max(q - 160, 0) * CFG_Q3; }

constexpr int SM_A = 0;
constexpr int SM_RING = 131072;
constexpr int SM_STG = SM_RING + NSLOT * SLOT;
constexpr int SM_PAR = SM_STG + 3 * 8192;
constexpr int SM_CS = SM_PAR + 3 * TN * 2;
constexpr int SM_BAR = SM_CS + 128;
constexpr int B_FULLB = 0, B_FULLA = 56, B_PAR = 72, B_SW = 77, B_AFREE = 74  , B_FREE = 90,
              B_GO = 104, B_FILL = 128, B_CS = 131, B_RAWA = 132, B_RAWB = 145, B_END = 163;
constexpr int SM_TOTAL = SM_BAR + B_END * 8;
static_assert(SM_TOTAL <= 232448, "");

constexpr int F_W = 512, F_CS = 576;
struct Scratch {
    unsigned flag[768];
    int cs[2][TN];
    int sink[384];
    uint4 s8[(1024 + 8 * 256) * 128];
};
static_assert(offsetof(Scratch, s8) == 8192, "");
__device__ __align__(8192) Scratch g_scratch;
__device__ __forceinline__ unsigned* epoch(Scratch* sc, int r, int c) { return sc->flag + r * 32 + 16 + c; }

__device__ __forceinline__ void mbar_init(uint32_t bar, uint32_t cnt) {
    asm volatile("mbarrier.init.shared::cta.b64 [%0], %1;" :: "r"(bar), "r"(cnt) : "memory");
}
__device__ __forceinline__ void mbar_expect_tx(uint32_t bar, uint32_t bytes) {
    asm volatile("mbarrier.arrive.expect_tx.shared::cta.b64 _, [%0], %1;" :: "r"(bar), "r"(bytes) : "memory");
}
__device__ __forceinline__ void mbar_arrive(uint32_t bar) {
    asm volatile("mbarrier.arrive.shared::cta.b64 _, [%0];" :: "r"(bar) : "memory");
}
__device__ __forceinline__ void mbar_arrive_cluster(uint32_t bar) {
    asm volatile("mbarrier.arrive.shared::cluster.b64 _, [%0];" :: "r"(bar) : "memory");
}
__device__ __forceinline__ void mbar_wait(uint32_t bar, uint32_t parity = 0) {
    asm volatile("{\n.reg .pred p;\n.reg .u32 c;\n"
                 "mbarrier.try_wait.parity.shared::cta.b64 p, [%0], %1;\n"
                 "@p bra WAIT_DONE;\n"
                 "mov.u32 c, 0;\n"
                 "WAIT_LOOP:\n"
                 "mbarrier.try_wait.parity.shared::cta.b64 p, [%0], %1;\n"
                 "@p bra WAIT_DONE;\n"
                 "add.u32 c, c, 1;\nsetp.lt.u32 p, c, 0x100000;\n"
                 "@p bra WAIT_LOOP;\n"
                 "trap;\n"
                 "WAIT_DONE:\n}" :: "r"(bar), "r"(parity) : "memory");
}
__device__ __forceinline__ void mbar_wait2(uint32_t bar0, uint32_t bar1) {
    asm volatile("{\n.reg .pred p, q;\n.reg .u32 c;\nmov.u32 c, 0;\n"
                 "WAIT_LOOP:\n"
                 "mbarrier.try_wait.parity.shared::cta.b64 p, [%0], 0;\n"
                 "mbarrier.try_wait.parity.shared::cta.b64 q, [%1], 0;\n"
                 "and.pred p, p, q;\n"
                 "@p bra WAIT_DONE;\n"
                 "add.u32 c, c, 1;\nsetp.lt.u32 p, c, 0x100000;\n"
                 "@p bra WAIT_LOOP;\n"
                 "trap;\n"
                 "WAIT_DONE:\n}" :: "r"(bar0), "r"(bar1) : "memory");
}
__device__ __forceinline__ bool mbar_test(uint32_t bar) {
    uint32_t ok;
    asm volatile("{\n.reg .pred p;\nmbarrier.test_wait.parity.shared::cta.b64 p, [%1], 0;\nselp.u32 %0, 1, 0, p;\n}" : "=r"(ok) : "r"(bar) : "memory");
    return ok;
}
__device__ __forceinline__ bool mbar_test2(uint32_t bar0, uint32_t bar1) {
    uint32_t ok;
    asm volatile("{\n.reg .pred p, q;\nmbarrier.test_wait.parity.shared::cta.b64 p, [%1], 0;\n"
                 "mbarrier.test_wait.parity.shared::cta.b64 q, [%2], 0;\nand.pred p, p, q;\nselp.u32 %0, 1, 0, p;\n}"
                 : "=r"(ok) : "r"(bar0), "r"(bar1) : "memory");
    return ok;
}
__device__ __forceinline__ bool elect_one() {
    uint32_t ok;
    asm volatile("{\n.reg .pred p;\nelect.sync _|p, 0xffffffff;\nselp.u32 %0, 1, 0, p;\n}" : "=r"(ok));
    return ok;
}
__device__ __forceinline__ unsigned ld_flag(const unsigned* p) {
    unsigned v;
    asm volatile("ld.relaxed.gpu.global.u32 %0, [%1];" : "=r"(v) : "l"(p) : "memory");
    return v;
}
__device__ __forceinline__ uint4 lds128(uint32_t a) {
    uint4 v;
    asm volatile("ld.shared.v4.b32 {%0,%1,%2,%3}, [%4];" : "=r"(v.x), "=r"(v.y), "=r"(v.z), "=r"(v.w) : "r"(a) : "memory");
    return v;
}
__device__ __forceinline__ void sts128(uint32_t a, uint4 v) {
    asm volatile("st.shared.v4.b32 [%0], {%1,%2,%3,%4};" :: "r"(a), "r"(v.x), "r"(v.y), "r"(v.z), "r"(v.w) : "memory");
}
__device__ __forceinline__ uint32_t lds32(uint32_t a) {
    uint32_t v;
    asm volatile("ld.shared.b32 %0, [%1];" : "=r"(v) : "r"(a) : "memory");
    return v;
}
__device__ __forceinline__ void sts32(uint32_t a, uint32_t v) {
    asm volatile("st.shared.b32 [%0], %1;" :: "r"(a), "r"(v) : "memory");
}
__device__ __forceinline__ void stg128(void* p, uint4 v) {
    asm volatile("st.global.v4.b32 [%0], {%1,%2,%3,%4};" :: "l"(p), "r"(v.x), "r"(v.y), "r"(v.z), "r"(v.w) : "memory");
}
__device__ __forceinline__ unsigned pack4(unsigned a, unsigned b, unsigned c, unsigned d) {
    unsigned lo, r;
    asm("cvt.pack.sat.s8.s32.b32 %0, %1, %2, 0;" : "=r"(lo) : "r"(d), "r"(c));
    asm("cvt.pack.sat.s8.s32.b32 %0, %1, %2, %3;" : "=r"(r) : "r"(b), "r"(a), "r"(lo));
    return r;
}
__device__ __forceinline__ uint32_t mapa(uint32_t a, uint32_t r) {
    uint32_t o;
    asm("mapa.shared::cluster.u32 %0, %1, %2;" : "=r"(o) : "r"(a), "r"(r));
    return o;
}
__device__ __forceinline__ unsigned clk() {
    unsigned t;
    asm volatile("mov.u32 %0, %clock;" : "=r"(t));
    return t;
}
__device__ __forceinline__ void cluster_arrive() { asm volatile("barrier.cluster.arrive.relaxed.aligned;" ::: "memory"); }
__device__ __forceinline__ void cluster_wait() { asm volatile("barrier.cluster.wait.aligned;" ::: "memory"); }
__device__ __forceinline__ void fence_init() { asm volatile("fence.mbarrier_init.release.cluster;" ::: "memory"); }
__device__ __forceinline__ void flag_add(unsigned* p) { asm volatile("red.relaxed.gpu.global.add.u32 [%0], 1;" :: "l"(p) : "memory"); }
__device__ __forceinline__ void raw_load(const void* map, int y, int z, uint32_t dst, uint32_t bar) {
    asm volatile("cp.async.bulk.tensor.3d.shared::cluster.global.tile.mbarrier::complete_tx::bytes [%0], [%1, {0, %2, %3}], [%4];"
                 :: "r"(dst), "l"(map), "r"(y), "r"(z), "r"(bar) : "memory");
}
__device__ __forceinline__ void tile_load(Scratch* sc, uint32_t dst, int tile, uint32_t bar) {
    asm volatile("cp.async.bulk.shared::cluster.global.mbarrier::complete_tx::bytes [%0], [%1], %2, [%3];"
                 :: "r"(dst), "l"((const char*)sc->s8 + tile * 8192), "r"(8192), "r"(bar) : "memory");
}
__device__ __forceinline__ void tile_store(const void* map, int x, int y, uint32_t src) {
    asm volatile("cp.async.bulk.tensor.2d.global.shared::cta.tile.bulk_group [%0, {%1, %2}], [%3];"
                 :: "l"(map), "r"(x), "r"(y), "r"(src) : "memory");
}
__device__ __forceinline__ void st_async(uint32_t a, uint32_t v, uint32_t bar) {
    asm volatile("st.async.weak.shared::cluster.mbarrier::complete_tx::bytes.b32 [%0], %1, [%2];" :: "r"(a), "r"(v), "r"(bar) : "memory");
}
__device__ __forceinline__ void red_async(uint32_t a, int v, uint32_t bar) {
    asm volatile("red.async.relaxed.cluster.shared::cluster.mbarrier::complete_tx::bytes.add.s32 [%0], %1, [%2];" :: "r"(a), "r"(v), "r"(bar) : "memory");
}
__device__ __forceinline__ void red_shared(uint32_t a, int v) { asm volatile("red.shared.add.s32 [%0], %1;" :: "r"(a), "r"(v) : "memory"); }
__device__ __forceinline__ int sum4(unsigned v, int c) { return __dp4a((int)v, 0x01010101, c); }

constexpr uint32_t DESC_A_HI = 0x80000000u | (512 >> 4);
constexpr uint32_t DESC_B_HI = 512 >> 4;
template <int NR> __device__ __forceinline__ void wgmma_n160(int (&d)[NR], uint32_t alo, uint32_t blo, int scale_d) {
    asm volatile("{\n.reg .pred p;\n.reg .b64 da, db;\nsetp.ne.b32 p, %82, 0;\n"
        "mov.b64 da, {%80, %83};\nmov.b64 db, {%81, %84};\n"
        "wgmma.mma_async.sync.aligned.m64n160k32.s32.s8.s8 "
        "{%0, %1, %2, %3, %4, %5, %6, %7, %8, %9, %10, %11, %12, %13, %14, %15, "
        "%16, %17, %18, %19, %20, %21, %22, %23, %24, %25, %26, %27, %28, %29, %30, %31, "
        "%32, %33, %34, %35, %36, %37, %38, %39, %40, %41, %42, %43, %44, %45, %46, %47, "
        "%48, %49, %50, %51, %52, %53, %54, %55, %56, %57, %58, %59, %60, %61, %62, %63, "
        "%64, %65, %66, %67, %68, %69, %70, %71, %72, %73, %74, %75, %76, %77, %78, %79}, "
        "da, db, p;\n}\n"
        : "+r"(d[0]), "+r"(d[1]), "+r"(d[2]), "+r"(d[3]), "+r"(d[4]), "+r"(d[5]), "+r"(d[6]), "+r"(d[7]),
          "+r"(d[8]), "+r"(d[9]), "+r"(d[10]), "+r"(d[11]), "+r"(d[12]), "+r"(d[13]), "+r"(d[14]), "+r"(d[15]),
          "+r"(d[16]), "+r"(d[17]), "+r"(d[18]), "+r"(d[19]), "+r"(d[20]), "+r"(d[21]), "+r"(d[22]), "+r"(d[23]),
          "+r"(d[24]), "+r"(d[25]), "+r"(d[26]), "+r"(d[27]), "+r"(d[28]), "+r"(d[29]), "+r"(d[30]), "+r"(d[31]),
          "+r"(d[32]), "+r"(d[33]), "+r"(d[34]), "+r"(d[35]), "+r"(d[36]), "+r"(d[37]), "+r"(d[38]), "+r"(d[39]),
          "+r"(d[40]), "+r"(d[41]), "+r"(d[42]), "+r"(d[43]), "+r"(d[44]), "+r"(d[45]), "+r"(d[46]), "+r"(d[47]),
          "+r"(d[48]), "+r"(d[49]), "+r"(d[50]), "+r"(d[51]), "+r"(d[52]), "+r"(d[53]), "+r"(d[54]), "+r"(d[55]),
          "+r"(d[56]), "+r"(d[57]), "+r"(d[58]), "+r"(d[59]), "+r"(d[60]), "+r"(d[61]), "+r"(d[62]), "+r"(d[63]),
          "+r"(d[64]), "+r"(d[65]), "+r"(d[66]), "+r"(d[67]), "+r"(d[68]), "+r"(d[69]), "+r"(d[70]), "+r"(d[71]),
          "+r"(d[72]), "+r"(d[73]), "+r"(d[74]), "+r"(d[75]), "+r"(d[76]), "+r"(d[77]), "+r"(d[78]), "+r"(d[79])
        : "r"(alo), "r"(blo), "r"(scale_d), "r"(DESC_A_HI), "r"(DESC_B_HI));
}
template <int NR> __device__ __forceinline__ void wgmma_t128(int (&d)[NR], uint32_t alo, uint32_t blo, int scale_d) {
    asm volatile("{\n.reg .pred p;\n.reg .b64 da, db;\nsetp.ne.b32 p, %66, 0;\n"
        "mov.b64 da, {%64, %67};\nmov.b64 db, {%65, %68};\n"
        "wgmma.mma_async.sync.aligned.m64n128k32.s32.s8.s8 "
        "{%0, %1, %2, %3, %4, %5, %6, %7, %8, %9, %10, %11, %12, %13, %14, %15, "
        "%16, %17, %18, %19, %20, %21, %22, %23, %24, %25, %26, %27, %28, %29, %30, %31, "
        "%32, %33, %34, %35, %36, %37, %38, %39, %40, %41, %42, %43, %44, %45, %46, %47, "
        "%48, %49, %50, %51, %52, %53, %54, %55, %56, %57, %58, %59, %60, %61, %62, %63}, "
        "da, db, p;\n}\n"
        : "+r"(d[0]), "+r"(d[1]), "+r"(d[2]), "+r"(d[3]), "+r"(d[4]), "+r"(d[5]), "+r"(d[6]), "+r"(d[7]),
          "+r"(d[8]), "+r"(d[9]), "+r"(d[10]), "+r"(d[11]), "+r"(d[12]), "+r"(d[13]), "+r"(d[14]), "+r"(d[15]),
          "+r"(d[16]), "+r"(d[17]), "+r"(d[18]), "+r"(d[19]), "+r"(d[20]), "+r"(d[21]), "+r"(d[22]), "+r"(d[23]),
          "+r"(d[24]), "+r"(d[25]), "+r"(d[26]), "+r"(d[27]), "+r"(d[28]), "+r"(d[29]), "+r"(d[30]), "+r"(d[31]),
          "+r"(d[32]), "+r"(d[33]), "+r"(d[34]), "+r"(d[35]), "+r"(d[36]), "+r"(d[37]), "+r"(d[38]), "+r"(d[39]),
          "+r"(d[40]), "+r"(d[41]), "+r"(d[42]), "+r"(d[43]), "+r"(d[44]), "+r"(d[45]), "+r"(d[46]), "+r"(d[47]),
          "+r"(d[48]), "+r"(d[49]), "+r"(d[50]), "+r"(d[51]), "+r"(d[52]), "+r"(d[53]), "+r"(d[54]), "+r"(d[55]),
          "+r"(d[56]), "+r"(d[57]), "+r"(d[58]), "+r"(d[59]), "+r"(d[60]), "+r"(d[61]), "+r"(d[62]), "+r"(d[63])
        : "r"(alo), "r"(blo), "r"(scale_d), "r"(DESC_B_HI), "r"(DESC_A_HI));
}


__device__ __forceinline__ void wg_fence() { asm volatile("wgmma.fence.sync.aligned;" ::: "memory"); }
__device__ __forceinline__ void wg_commit() { asm volatile("wgmma.commit_group.sync.aligned;" ::: "memory"); }
template <int N> __device__ __forceinline__ void wg_wait() { asm volatile("wgmma.wait_group.sync.aligned %0;" :: "n"(N) : "memory"); }

__host__ __device__ constexpr int unit_of(int X1, int piece, int slab) {
    return piece < 2 ? (slab < X1 ? 2 * slab + piece : (piece ? 16 : X1) + slab) : 32 + (piece - 2) * 8 + (slab >> 1);
}
__host__ __device__ constexpr int col_of(int G) { return G == 4 ? 256 : (G > 4 && G < 9) ? 32 * G - 32 : 32 * G; }
struct BJob { int u, slab, G, pos; };
__host__ __device__ constexpr BJob decode_b(int X1, int q) {
    BJob j = {};
    if (q < 160) {
        j.u = q / 5; j.pos = q - j.u * 5;
        const int piece = j.u < 2 * X1 ? (j.u & 1) : (j.u >= X1 + 16);
        j.slab = j.u < 2 * X1 ? (j.u >> 1) : j.u - (piece ? 16 : X1);
        j.G = piece * 5 + j.pos;
    } else {
        q -= 160;
        j.u = 32 + (q >> 2); j.pos = q & 3;
        j.slab = (q >> 1) & 15;
        j.G = 10 + (q >> 5) * 2 + (q & 1);
    }
    return j;
}
__host__ __device__ constexpr int fb_of(int X1, int u) {
    return u < 2 * X1 ? (u & 1) * 32 + (u >> 1) : u < X1 + 16 ? u - X1 : u < 32 ? 16 + u : u < 40 ? u - 16 : u < 48 ? u + 8 : u - 24;
}
__host__ __device__ constexpr uint64_t slot_table(int X1, int piece) {
    uint64_t t = 0;
    if (piece < 2) for (int s = 0; s < 16; s++) t |= (uint64_t)(unit_of(X1, piece, s) % NSLOT) << (4 * s);
    else for (int s = 0; s < 8; s++) t |= (uint64_t)(unit_of(X1, piece, 2 * s) % NSLOT) << (4 * s);
    return t;
}
template <bool k2> __device__ __forceinline__ int stage_w(int t) { return (k2 && t < 9) ? SM_A + (7 + t) * 8192 : SM_STG + (t % 3) * 8192; }
template <bool k2> __host__ __device__ constexpr int ford(int g, int m) {
    constexpr int NA = k2 ? CFG_NA2 : CFG_NA1;
    if (k2 ? CFG_ORD2 : CFG_ORD1) return g ? NA + m : m < NA ? m : 5 + m;
    return g ? (m < NA - 1 ? 2 + 2 * m : NA + m) : (m < 2 ? m : m < NA ? 2 * m - 1 : 5 + m);
}
template <bool k2> __host__ __device__ constexpr uint64_t ford_table() {
    uint64_t t = 0;
    for (int g = 0; g < 2; g++) for (int m = 0; m < 5; m++) t |= (uint64_t)(g * 8 + m) << (4 * ford<k2>(g, m));
    return t;
}
struct Maps { CUtensorMap m[4]; };

__device__ __forceinline__ uint32_t bf2_mul(uint32_t a, uint32_t b) { asm("mul.rn.bf16x2 %0, %0, %1;" : "+r"(a) : "r"(b)); return a; }
__device__ __forceinline__ uint32_t epi(int a, int b, uint32_t zc, uint32_t sx, uint32_t sw, uint32_t bi) {
    uint32_t v;
    float fa = __int2float_rn(a), fb = __int2float_rn(b);
    asm("cvt.rn.bf16x2.f32 %0, %1, %2;" : "=r"(v) : "f"(fb), "f"(fa));
    if (CFG_EPI == 3) {
        asm("fma.rn.bf16x2 %0, %0, %1, %2;" : "+r"(v) : "r"(sw), "r"(zc));
        return v;
    }
    asm("sub.rn.bf16x2 %0, %0, %1;" : "+r"(v) : "r"(zc));
    if (CFG_EPI == 0) {
        v = bf2_mul(bf2_mul(v, sx), sw);
        asm("add.rn.bf16x2 %0, %0, %1;" : "+r"(v) : "r"(bi));
    } else {
        asm("fma.rn.bf16x2 %0, %0, %1, %2;" : "+r"(v) : "r"(sw), "r"(bi));
    }
    return v;
}
__device__ __forceinline__ uint32_t zero_term(int lo, int hi, float zx) {
    uint32_t z;
    asm("cvt.rn.bf16x2.f32 %0, %1, %2;" : "=r"(z) : "f"(__bfloat162float(__float2bfloat16_rn((float)hi)) * zx),
                                                    "f"(__bfloat162float(__float2bfloat16_rn((float)lo)) * zx));
    return z;
}
__device__ __forceinline__ uint32_t fold(uint32_t z, uint32_t sw, uint32_t bi) {
    if (CFG_EPI == 3) asm("fma.rn.bf16x2 %0, %1, %2, %3;" : "=r"(z) : "r"(z ^ 0x80008000u), "r"(sw), "r"(bi));
    return z;
}
__device__ __forceinline__ float ld_zx(const int* zero_x) { return __bfloat162float(__float2bfloat16_rn((float)__ldg(zero_x))); }
struct Par { uint4 zc, sw, bi; };
__device__ __forceinline__ Par ld_par(uint32_t p) { return {lds128(p), lds128(p + TN * 2), CFG_EPI == 3 ? uint4{} : lds128(p + TN * 4)}; }
__device__ __forceinline__ uint4 epi_row(const int (&a)[WA / 2], int o, const Par& p, uint32_t sx2) {
    uint4 r;
    r.x = epi(a[o + 0], a[o + 4], p.zc.x, sx2, p.sw.x, p.bi.x);
    r.y = epi(a[o + 8], a[o + 12], p.zc.y, sx2, p.sw.y, p.bi.y);
    r.z = epi(a[o + 1], a[o + 5], p.zc.z, sx2, p.sw.z, p.bi.z);
    r.w = epi(a[o + 9], a[o + 13], p.zc.w, sx2, p.sw.w, p.bi.w);
    return r;
}
__device__ __forceinline__ void scale_bias(const __nv_bfloat16* scale_x, const __nv_bfloat16* scale_w, const __nv_bfloat16* bias, uint32_t sb, int lane) {
    const uint32_t sx2 = (uint32_t)__ldg((const unsigned short*)scale_x) * 0x10001u;
#pragma unroll
    for (int i = lane; i < TN / 4; i += 32) {
        const bool hi = i >= TN / 8;
        uint4 v = __ldg((const uint4*)(hi ? bias : scale_w) + (hi ? i - TN / 8 : i));
        if (CFG_EPI && !hi) v = {bf2_mul(v.x, sx2), bf2_mul(v.y, sx2), bf2_mul(v.z, sx2), bf2_mul(v.w, sx2)};
        sts128(sb + SM_PAR + TN * 2 + i * 16, v);
    }
    __syncwarp();
    if (elect_one()) mbar_arrive(sb + SM_BAR + B_SW * 8);
}
template <bool k2> __device__ __forceinline__ void release(uint32_t go, int u, int lane) {
    const int v = u + NSLOT;
    if (k2) {
        const int q = v + lane;
        if (lane < (v < 48 ? 1 : 0)) mbar_arrive_cluster(mapa(go + (q >> 1) * 8, q & 1));
    } else {
        const int q = 5 * v - (v > 34 ? 3 : 0) + lane;
        if (lane < (v > 38 ? 0 : v == 34 ? 2 : 5)) mbar_arrive_cluster(mapa(go + (q >> 4) * 8, q & 15));
    }
}
__device__ __forceinline__ unsigned read_back(const uint4* d, int lane) { return ld_flag((const unsigned*)(d - lane + ((lane + 10) & 15) * 8 + 6)); }
__device__ __forceinline__ void publish(unsigned rb, unsigned mine, unsigned* flag) {
    if (__shfl_sync(~0u, rb ^ mine, 6)) asm volatile("fence.acq_rel.gpu;" ::: "memory");
    if (elect_one()) flag_add(flag);
}
#define CV_B(m, f)                                                                                                      \
    {                                                                                                                   \
        uint4 v0 = lds128(rdB + m * 512), v1 = lds128(rdB + m * 512 + 128);                                             \
        uint4 v2 = lds128(rdB + m * 512 + 256), v3 = lds128(rdB + m * 512 + 384);                                       \
        o[0].f = pack4(v0.x, v1.x, v2.x, v3.x); o[1].f = pack4(v0.y, v1.y, v2.y, v3.y);                                 \
        o[2].f = pack4(v0.z, v1.z, v2.z, v3.z); o[3].f = pack4(v0.w, v1.w, v2.w, v3.w);                                 \
    }

__device__ __forceinline__ void last_columns(Scratch* sc, const Maps& maps, const __nv_bfloat16* scale_x, const int* zero_x, const __nv_bfloat16* scale_w,
                                             const __nv_bfloat16* bias, uint32_t sb, int warp, int lane, unsigned t0) {
    constexpr int C_FULL = 0, C_EMPTY = 32, C_RAW = 64, C_GO = 80, C_PEER = 81, D3 = CFG_D3;
    const uint32_t bars = sb + SM_BAR;
    const int j = blockIdx.x & 3;
    while ((int)(t0 + CFG_T3 - clk()) > 0) ;
    const int s0 = (j & 1) * 8 + (warp >> 1) * 2;
    if (warp < 8) {
        if (elect_one()) {
#pragma unroll
            for (int i = 0; i < 2; i++) {
                const uint32_t bar = bars + (C_RAW + warp * 2 + i) * 8;
                mbar_init(bar, 1); mbar_expect_tx(bar, 8192);
                raw_load(maps.m + 1, (s0 + (i ^ (j >> 1))) * 64, N_ / 32 - 2 + (warp & 1), sb + SM_A + (warp * 2 + i) * 8192, bar);
            }
#pragma unroll
            for (int i = 0; i < 4; i++) { mbar_init(bars + (C_FULL + warp * 4 + i) * 8, 1); mbar_expect_tx(bars + (C_FULL + warp * 4 + i) * 8, 16384); }
#pragma unroll
            for (int i = 0; i < 4; i++) mbar_init(bars + (C_EMPTY + warp * 4 + i) * 8, 4);
            if (warp == 0) {
                mbar_init(bars + C_GO * 8, 8);
                mbar_init(bars + C_PEER * 8, 1); mbar_expect_tx(bars + C_PEER * 8, 32768 + 4096);
            }
        }
        if (warp < 2) sts32(sb + SM_PAR + threadIdx.x * 4, 0);
        fence_init();
    }
    __syncthreads();
    cluster_arrive();
    cluster_wait();
    if (warp >= 8) {
        asm volatile("setmaxnreg.dec.sync.aligned.u32 40;");
        if (warp < 12) {
            const unsigned ep = (ld_flag(epoch(sc, j * 4, 8)) + 1) * 4;
            const int mb = j * 4 + warp - 8, wg = (warp >> 1) & 1;
            unsigned rdy = 0;
            mbar_wait(bars + (wg ? C_EMPTY : C_GO) * 8);
#pragma unroll 1
            for (int s = 0; s < 16; s++) {
                for (int it = 0; !((rdy >> s) & 1); it++) {
                    rdy = __ballot_sync(~0u, (int)(ld_flag(sc->flag + mb * 32 + (lane & 15)) - ep) >= 0);
                    if (it > (1 << 22)) __trap();
                }
                if (s >= D3) mbar_wait(bars + (C_EMPTY + (s - (s < CFG_S3 ? D3 : CFG_D4)) * 2 + wg) * 8);
                if (elect_one()) tile_load(sc, sb + SM_A + ((s & 3) * 4 + warp - 8) * 8192, mb * 16 + s, bars + (C_FULL + s * 2 + wg) * 8);
            }
        }
    } else {
        asm volatile("setmaxnreg.inc.sync.aligned.u32 200;");
        const int wg = warp >> 2, w = warp & 3;
        const int c0 = (w >> 1) * 32 + (lane >> 2) * 4 + (w & 1) * 2, r0 = (lane & 3) * 2;
        const uint32_t sx2 = (uint32_t)__ldg((const unsigned short*)scale_x) * 0x10001u;
        uint32_t sw = __ldg((const unsigned*)(scale_w + N_ - WB + c0));
        const uint32_t bi = __ldg((const unsigned*)(bias + N_ - WB + c0));
        const float zxf = ld_zx(zero_x);
        int cs[4] = {0, 0, 0, 0};
        const uint32_t peer = mapa(sb, (j & 1) ^ 1);
#pragma unroll 1
        for (int i = 0; i < 2; i++) {
            const uint32_t rdB = sb + SM_A + (warp * 2 + i) * 8192 + (lane >> 3) * 2048 + (lane & 7) * 16;
            const uint32_t wr = SM_RING + (s0 + (i ^ (j >> 1))) * 4096 + (warp & 1) * 2048 + lane * 16;
            mbar_wait(bars + (C_RAW + warp * 2 + i) * 8);
            uint4 o[4];
            CV_B(0, x) CV_B(1, y) CV_B(2, z) CV_B(3, w)
#pragma unroll
            for (int k = 0; k < 4; k++) {
                sts128(sb + wr + k * 512, o[k]);
                asm volatile("st.async.weak.shared::cluster.mbarrier::complete_tx::bytes.v4.b32 [%0], {%1,%2,%3,%4}, [%5];"
                             :: "r"(peer + wr + k * 512), "r"(o[k].x), "r"(o[k].y), "r"(o[k].z), "r"(o[k].w), "r"(peer + SM_BAR + C_PEER * 8) : "memory");
                cs[k] = sum4(o[k].x, sum4(o[k].y, sum4(o[k].z, sum4(o[k].w, cs[k]))));
            }
        }
        __syncwarp();
        if (elect_one()) mbar_arrive(bars + C_GO * 8);
#pragma unroll
        for (int k = 0; k < 4; k++) {
            const uint32_t ca = SM_PAR + ((warp & 1) * 32 + (lane & 7) * 4 + k) * 4;
            red_shared(sb + ca, cs[k]);
            red_async(peer + ca, cs[k], peer + SM_BAR + C_PEER * 8);
        }
        mbar_wait(bars + C_PEER * 8);
        asm volatile("fence.proxy.async.shared::cta;" ::: "memory");
        asm volatile("bar.sync 1, 256;" ::: "memory");
        if (CFG_EPI) sw = bf2_mul(sw, sx2);
        const uint32_t zc = fold(zero_term(lds32(sb + SM_PAR + c0 * 4), lds32(sb + SM_PAR + c0 * 4 + 4), zxf), sw, bi);
        const uint32_t sd = (sb & 0x3FFFF) >> 4;
        int t[2][64];
        wg_fence();
#pragma unroll 1
        for (int s = 0; s < 16; s++) {
            const uint32_t db = ((sd + (SM_RING >> 4)) | (8 << 16)) + s * 256, da = ((sd + (SM_A >> 4)) | (1 << 16)) + ((s & 3) * 4 + wg * 2) * 512;
            mbar_wait(bars + (C_FULL + s * 2 + wg) * 8);
            wgmma_t128(t[0], db, da, s);
            wgmma_t128(t[1], db, da + 512, s);
            wgmma_t128(t[0], db + 16, da + 2, 1);
            wgmma_t128(t[1], db + 16, da + 514, 1);
            wg_commit();
            wg_wait<0>();
            if (elect_one()) mbar_arrive(bars + (C_EMPTY + s * 2 + wg) * 8);
        }
        asm volatile("bar.sync %0, 128;" :: "r"(3 + wg) : "memory");
        const uint32_t st0 = sb + SM_A + wg * 16384 + r0 * 128 + (((c0 >> 3) ^ r0) << 4) + (c0 & 7) * 2;
#pragma unroll
        for (int h = 0; h < 4; h++) {
            const uint32_t off = (h >> 1) * 32768 + (h & 1) * 8192;
#pragma unroll
            for (int q = 0; q < 8; q++) {
                const int o = (h & 1) * 32 + q * 4;
                sts32(st0 + off + q * 1024, epi(t[h >> 1][o], t[h >> 1][o + 2], zc, sx2, sw, bi));
                sts32((st0 ^ (5 * 128 + 5 * 16)) + off + q * 1024, epi(t[h >> 1][o + 1], t[h >> 1][o + 3], zc, sx2, sw, bi));
            }
            asm volatile("fence.proxy.async.shared::cta;" ::: "memory");
            asm volatile("bar.sync %0, 128;" :: "r"(3 + wg) : "memory");
            if (w == 0 && elect_one()) tile_store(maps.m + 2, N_ - WB, j * 512 + wg * 256 + h * 64, sb + SM_A + wg * 16384 + off);
        }
        if (w == 0) {
            asm volatile("cp.async.bulk.commit_group;" ::: "memory");
            asm volatile("cp.async.bulk.wait_group.read 0;" ::: "memory");
        }
        asm volatile("bar.sync 1, 256;" ::: "memory");
        if (threadIdx.x == 0) flag_add(epoch(sc, j * 4, 8));
    }
}

template <bool k2>
__global__ void __cluster_dims__(k2 ? 2 : CS, 1, 1) __launch_bounds__(512, 1)
w8a8_kernel(Scratch* sc, const char* __restrict__ qx, const char* __restrict__ qw, const __nv_bfloat16* __restrict__ scale_x, const int* __restrict__ zero_x,
            const __nv_bfloat16* __restrict__ scale_w, const __nv_bfloat16* __restrict__ bias, const __grid_constant__ Maps maps) {
    extern __shared__ __align__(1024) unsigned char smem_raw[];
    constexpr int NBJ = k2 ? 12 : 14, NF = NBJ, NU = k2 ? 40 : 48;
    constexpr int X1 = k2 ? CFG_X2 : CFG_X1;
    constexpr int HOLD = k2 ? CFG_HOLD2 : CFG_HOLD;
    constexpr int NA = k2 ? CFG_NA2 : CFG_NA1;
    const int b = blockIdx.x + (k2 ? NCTA : 0), r = b & 15, c = k2 ? NCL : b >> 4;
    const unsigned tc = clk();
    if (!k2) {
        const int a = (r * NCL + c) ^ REV;
        const unsigned off = ((a & 63) * 32 + (threadIdx.x >> 1)) * (K_ * 4) + (a >> 6) * 256 + (threadIdx.x & 1) * 128;
        asm volatile("{\n.reg .pred p;\n.reg .b64 a;\nsetp.lt.u32 p, %2, 64;\n@!p bra PF_DONE;\ncvt.u64.u32 a, %1;\nadd.u64 a, a, %0;\nprefetch.global.L2 [a];\nPF_DONE:\n}"
                     :: "l"(qx), "r"(off), "r"(threadIdx.x));
    }
    const uint32_t sb = (uint32_t)__cvta_generic_to_shared(smem_raw);
    const uint32_t bars = sb + SM_BAR;
    const unsigned tw = __shfl_sync(~0u, (tc & ~15u) | threadIdx.x >> 5, 0), t0 = tw + (k2 ? 0 : T0);
    const int warp = tw & 15, lane = threadIdx.x & 31;

    if (!k2 && warp == 12) {
        const int a = r * NCL + c;
        if (elect_one()) {
            mbar_init(bars + (B_RAWA + 3) * 8, 1);
            mbar_expect_tx(bars + (B_RAWA + 3) * 8, 8192);
            raw_load(maps.m, (a >> 6) * 2, ((a ^ REV) & 63) * 32, sb + SM_A + (a < NAJ % NCTA ? 15 : 13) * 8192, bars + (B_RAWA + 3) * 8);
        }
        __syncwarp();
    }
    if (!k2 && (warp >> 1) == 1 && r < CFG_PG) {
        const int a = (NCTA + r * NCL + c) ^ REV;
        const char* p = qx + ((a & 63) * 32 + (warp & 1) * 16 + (lane >> 1)) * (K_ * 4) + (a >> 6) * 256 + (lane & 1) * 128;
        while ((int)(t0 + (16 + r) * P1 - clk()) > 0) ;
        asm volatile("prefetch.global.L2 [%0];" :: "l"(p));
    }
    if (warp == 9 && elect_one()) asm volatile("prefetch.tensormap [%0];" :: "l"(maps.m + 1) : "memory");
    if (k2 && blockIdx.x >= 16) {
        last_columns(sc, maps, scale_x, zero_x, scale_w, bias, sb, warp, lane, t0);
        return;
    }
    if (warp >= 12) {
        const int isw = k2 || warp == 14, t = k2 ? warp - 12 : isw ? 0 : (warp - 11) >> 1;
        const uint32_t bar = bars + ((isw ? B_RAWB : B_RAWA) + 3 + t) * 8;
        if ((k2 || warp != 12) && elect_one()) { mbar_init(bar, 1); mbar_expect_tx(bar, 8192); }
        __syncwarp();
        cluster_arrive();
        const int x = t * 16 + r, a = (x * NCL + c) ^ REV, sx = (x * 26) >> 8;
        static_assert(X1 >= 7, "");
        if ((k2 || warp != 12) && elect_one()) {
            const unsigned te = t0 + (k2 ? sched2(x) : (isw ? time_w(x) : time_x(x)) * P1);
            while ((int)(te - clk()) > 0) ;
            raw_load(maps.m + isw, isw ? sx * 64 : (a >> 6) * 2,
                     isw ? c * (TN / 32) + (int)((0x9765483210ull >> ((x - sx * 10) * 4)) & 15) : (a & 63) * 32,
                     sb + (k2 ? SM_A + 7 * 8192 : isw ? SM_STG : SM_A + 13 * 8192) + (t - (!isw && r * NCL + c < NAJ % NCTA)) * 8192, bar);
        }
        __syncwarp();
        if (!k2 && warp == 15) cluster_wait();
    }
    if (warp < 8) {
        const uint32_t p = bars + warp * 104;
        if (elect_one()) {
#pragma unroll
            for (int i = 0; i < 13; i++) mbar_init(p + i * 8, (!k2 && ((warp == 6 && i == 12) || (warp == 7 && i < 2))) ? 2 : 1);
            static_assert(B_FREE == 90 && B_GO == 104, "");
        }
        __syncwarp();
        const int i = warp * 13 + lane;
        if (lane < 13 && i < B_SW) mbar_expect_tx(p + lane * 8, i >= B_PAR ? (i < B_PAR + 2 ? WA * 2 : WB * 2) : (i & 16) || i >= 48 ? 8192 : WA * 64);
        fence_init();
    }
    if (warp < 8 || warp == 10) cluster_arrive();
    if (!k2 && warp == 10 && lane < CFG_PF7) {
        const int n = b * CFG_PF7 + lane, row = n / 10;
        asm volatile("prefetch.global.L2 [%0];" :: "l"(qw + row * (N_ * 4) + NCL * TN * 4 + (n - row * 10) * 128));
    }

    if (warp < 8) {
        asm volatile("setmaxnreg.inc.sync.aligned.u32 200;");
        const int wg = warp >> 2;
        const uint32_t sd = (sb & 0x3FFFF) >> 4;
        const uint32_t sx2 = (uint32_t)__ldg((const unsigned short*)scale_x) * 0x10001u;
        const uint32_t par = sb + SM_PAR + (lane & 3) * 16 + wg * 256;
        const uint32_t go = bars + B_GO * 8;
        const int w = warp & 3, pq = (lane >> 2) ^ (lane & 4);
        uint32_t so = (w * 16 + pq) * 128 + (((lane & 3) ^ pq) << 4);
        const int c0 = (w >> 1) * 32 + (lane >> 2) * 4 + (w & 1) * 2, r0 = (lane & 3) * 2;
        uint32_t pp = sb + SM_PAR + (2 * WA + wg * WB + c0) * 2, st0 = r0 * 128 + (((c0 >> 3) ^ r0) << 4) + (c0 & 7) * 2;
        constexpr int rn = k2 ? 1 : 4;
        int rq = lane < rn ? rn * (32 + wg * 8 + (k2 ? NSLOT : 8)) + (k2 ? 0 : 32) + lane : 1000;
        asm volatile("" : "+r"(so), "+r"(pp), "+r"(st0), "+r"(rq));
        cluster_wait();
        int a0[WA / 2], a1[WA / 2];
        uint32_t barB = bars + (B_FULLB + wg * 32) * 8;
        wg_fence();
        {
            uint64_t tbl = wg ? slot_table(X1, 1) : slot_table(X1, 0);
            uint32_t da = (sd + (SM_A >> 4)) | (1 << 16);
            int up = 99;
            bool rdy = false;
#pragma unroll 1
            for (int s = 0; s < 16; s++) {
                const uint32_t db = ((sd + (SM_RING >> 4)) | (8 << 16)) + ((uint32_t)tbl & 15) * (SLOT >> 4);
                const bool hold = wg && s == X1;
                if (hold || (!rdy && !mbar_test2(bars + (B_FULLA + s) * 8, barB))) {
                    wg_wait<0>();
                    release<k2>(go, up, lane); up = 99;
                    mbar_wait2(bars + (B_FULLA + s) * 8, barB);
                    if (hold) asm volatile("bar.sync 7, 256;" ::: "memory");
                }
                wgmma_n160(a0, da, db, s);
                wgmma_n160(a1, da + 256, db, s);
                wg_commit();
                if (!wg && s == HOLD) asm volatile("bar.arrive 7, 256;" ::: "memory");
                wg_wait<1>();
                release<k2>(go, up, lane);
                wgmma_n160(a0, da + 2, db + 16, 1);
                wgmma_n160(a1, da + 258, db + 16, 1);
                wg_commit();
                up = s < X1 ? 2 * s + wg : (wg ? 16 : X1) + s;
                tbl >>= 4; da += 512; barB += 8;
                rdy = mbar_test2(bars + (B_FULLA + s + 1) * 8, barB);
                if (s < 15) wg_wait<1>();
            }
        }
        mbar_wait2(bars + (B_PAR + wg) * 8, bars + B_SW * 8);
        Par P = ld_par(par);
        wg_wait<0>();
        release<k2>(go, wg ? 31 : X1 + 15, lane);
        bool ready = mbar_test(barB);
#define FILL_BEGIN(n0, n1) mbar_wait(bars + (B_FREE + (wg ? n1 : n0)) * 8);                                             \
                           const uint32_t buf = sb + SM_STG + (wg ? (n1 + NBJ) % 3 : (n0 + NBJ) % 3) * 8192;
#define FILL_END(n0, n1) __syncwarp();                                                                                  \
                         if (elect_one()) mbar_arrive(bars + (B_FILL + (wg ? n1 % 3 : n0 % 3)) * 8);
#define FILL_PAIR(a, J, PN, m)                                                                                          \
        {                                                                                                               \
            const uint4 v0 = epi_row(a, J * 16, P, sx2);                                                                \
            const Par Q = ld_par(par + J * 64 + 64);                                                                    \
            const uint4 v1 = epi_row(a, J * 16 + 2, P, sx2);                                                            \
            FILL_BEGIN(ford<k2>(0, m), ford<k2>(1, m))                                                                          \
            sts128(buf + so, v0); sts128(buf + so + 1024, v1);                                                          \
            if ((PN) >= 0) P = ld_par(par + (PN));                                                                      \
            sts128(buf + (so ^ 64), epi_row(a, J * 16 + 16, Q, sx2));                                                   \
            sts128(buf + (so ^ 64) + 1024, epi_row(a, J * 16 + 18, Q, sx2));                                            \
            FILL_END(ford<k2>(0, m), ford<k2>(1, m))                                                                            \
        }
#define RELEASE_N() { if (rq < (k2 ? NU : NBJ * 16)) mbar_arrive_cluster(mapa(go + (rq >> rn) * 8, rq & ((1 << rn) - 1))); rq += rn; nrel++; }
#define NARROW(p)                                                                                                       \
        {                                                                                                               \
            uint32_t tbl = (uint32_t)slot_table(X1, p), da = (sd + (SM_A >> 4)) | (1 << 16);                                \
            wg_fence();                                                                                                 \
            _Pragma("unroll 1") for (int i = 0; i < 8; i++) {                                                           \
                const uint32_t db = ((sd + (SM_RING >> 4)) | (8 << 16)) + (k2 ? (tbl & 15) * (SLOT >> 4) : ((i + 5) & 7) * 512); \
                if (!ready && !mbar_test(barB)) {                                                                       \
                    wg_wait<0>();                                                                                       \
                    if (p == 2) { _Pragma("unroll 1") while (nrel < i) RELEASE_N() }                                    \
                    mbar_wait(barB);                                                                                    \
                }                                                                                                       \
                _Pragma("unroll") for (int kk = 0; kk < 4; kk++)                                                        \
                    wgmma_t128(t, db + (kk >> 1) * 256 + (kk & 1) * 16, da + (kk >> 1) * 512 + (kk & 1) * 2, kk ? 1 : i); \
                wg_commit();                                                                                            \
                barB += 8;                                                                                              \
                ready = mbar_test(barB);                                                                                \
                if (p == 2 && nrel < i - 1) RELEASE_N()                                                                 \
                tbl >>= 4; da += 1024;                                                                                  \
                wg_wait<1>();                                                                                           \
            }                                                                                                           \
            if (p == 2) { if (nrel < 7) RELEASE_N() if (NA < 5) P = ld_par(par + pn); }                                            \
            else { mbar_wait(bars + (B_PAR + 3) * 8); zc = lds32(pp); sw = lds32(pp + TN * 2); bi = CFG_EPI == 3 ? 0 : lds32(pp + TN * 4); } \
            wg_wait<0>();                                                                                               \
            if (p == 2) RELEASE_N()                                                                                     \
        }
        int nrel = 0;
        const int pn = NA == 2 ? 0 : NA == 3 ? 128 : 512 - wg * 192;
        FILL_PAIR(a0, 0, 128, 0) FILL_PAIR(a0, 2, NA == 2 ? -1 : 0, 1)
        int t[64];
        uint32_t zc, sw, bi;
        if (NA == 2) { if (wg == 0) NARROW(2) else P = ld_par(par + pn); }
        FILL_PAIR(a1, 0, NA == 3 ? -1 : 128, 2)
        if (NA == 3) { if (wg == 0) NARROW(2) else P = ld_par(par + pn); }
        FILL_PAIR(a1, 2, NA == 4 ? -1 : 512 - wg * 192, 3)
        if (NA == 4) { if (wg == 0) NARROW(2) else P = ld_par(par + pn); }
        {
            const uint4 v0 = epi_row(a0, 64, P, sx2), v1 = epi_row(a0, 66, P, sx2);
            if (NA < 5 && !wg) mbar_wait(bars + (B_PAR + 2) * 8);
            FILL_BEGIN(ford<k2>(0, 4), ford<k2>(1, 4))
            const uint32_t s4 = buf + ((so >> 1) & ~63u) + (lane & 3) * 16;
            sts128(s4, v0); sts128(s4 + 512, v1);
            sts128(s4 + 4096, epi_row(a1, 64, P, sx2)); sts128(s4 + 4608, epi_row(a1, 66, P, sx2));
            FILL_END(ford<k2>(0, 4), ford<k2>(1, 4))
        }
        if (!(k2 && wg)) {
            if (NA == 5 && wg == 0) { NARROW(2) mbar_wait(bars + (B_PAR + 2) * 8); }
            if (!k2 && wg == 1) NARROW(3) else { zc = lds32(pp); sw = lds32(pp + TN * 2); bi = CFG_EPI == 3 ? 0 : lds32(pp + TN * 4); }
#define FILL_T(h)                                                                                                       \
            {                                                                                                           \
                FILL_BEGIN((10 + h), (12 + h))                                                                          \
                _Pragma("unroll") for (int j = 0; j < 8; j++) {                                                         \
                    const int o = h * 32 + j * 4;                                                                       \
                    sts32(buf + st0 + j * 1024, epi(t[o], t[o + 2], zc, sx2, sw, bi));                                  \
                    sts32(buf + (st0 ^ (5 * 128 + 5 * 16)) + j * 1024, epi(t[o + 1], t[o + 3], zc, sx2, sw, bi));       \
                }                                                                                                       \
                FILL_END((10 + h), (12 + h))                                                                            \
            }
            FILL_T(0) FILL_T(1)
        }
        if (threadIdx.x == 0) flag_add(epoch(sc, r, c));
    } else {
        const int g = r * NCL + c, na = k2 ? 0 : NAJ / NCTA + (g < NAJ % NCTA);
        int cw = NF;
        if (warp >= 12) {
            asm volatile("setmaxnreg.dec.sync.aligned.u32 80;");
            if (warp < 14) {
                const int c4 = (lane ^ (lane >> 3)) & 3, ln = ((lane >> 2) ^ (lane & 4)) * 2 + (c4 >> 1);
                const uint32_t rd0 = sb + SM_A + 13 * 8192 + ln * 128 + ((((c4 & 1) << 2) ^ (ln & 7)) << 4);
#pragma unroll 1
                for (int t = warp - 12, sl = na == 9 ? t : 2 - 2 * t; t < na; t += 2, sl = sl ? sl - 1 : 2) {
                    const uint32_t rdA = rd0 + sl * 8192;
                    const int a = (t * NCTA + g) ^ REV, f = (a & 60) * 4 + (a >> 6);
                    uint4* const d = sc->s8 + (f * 4 + (a & 3)) * 128 + lane;
                    uint4 o[4];
                    mbar_wait(bars + (B_RAWA + 3 + t) * 8);
#pragma unroll
                    for (int i = 0; i < 4; i++) {
                        uint4 v0 = lds128(rdA + i * 2048), v1 = lds128((rdA ^ 16) + i * 2048);
                        uint4 v2 = lds128((rdA ^ 32) + i * 2048), v3 = lds128((rdA ^ 48) + i * 2048);
                        o[i].x = pack4(v0.x, v0.y, v0.z, v0.w); o[i].y = pack4(v1.x, v1.y, v1.z, v1.w);
                        o[i].z = pack4(v2.x, v2.y, v2.z, v2.w); o[i].w = pack4(v3.x, v3.y, v3.z, v3.w);
                    }
#pragma unroll
                    for (int i = 0; i < 4; i++) stg128(d + i * 32, o[i]);
                    asm volatile("fence.proxy.async.global;" ::: "memory");
                    __syncwarp();
                    const unsigned rb = read_back(d, lane);
                    if (t < 2) cluster_wait();
                    if (elect_one()) mbar_arrive(bars + ((t < na - 3 ? B_RAWA : B_AFREE + 13) + sl) * 8);
                    publish(rb, o[0].x, sc->flag + (a & 60) * 8 + (a >> 6));
                }
                cw = warp - 12;
            }
            if (!k2) {
                const int hw = warp & 1;
                const uint32_t rd0 = sb + SM_STG + hw * 4096 + (lane >> 3) * 1024 + (lane & 7) * 16;
                const int myG = decode_b(X1, (lane & 15) * 16 + r).G;
#pragma unroll 1
                for (int t = warp < 14 ? TA : 0; t < NBJ; t += warp < 14 ? NBJ : t == TA - 1 ? 2 : 1) {
                    const int sl = t % 3;
                    const uint32_t rdB = rd0 + sl * 8192;
                    char* const d = (char*)sc->s8 + (1024 + c * 256 + t * 16 + r) * 2048 + hw * 256 + (lane >> 4) * 128 + (lane & 7) * 16 + (lane & 8);
                    uint2 o[4];
                    mbar_wait(bars + (B_RAWB + 3 + t) * 8);
                    CV_B(0, x) CV_B(1, y)
#pragma unroll
                    for (int i = 0; i < 4; i++) asm volatile("st.global.v2.b32 [%0], {%1,%2};" :: "l"(d + i * 512), "r"(o[i].x), "r"(o[i].y) : "memory");
                    if (t == 0 && warp == 14) cluster_wait();
                    if (elect_one()) mbar_arrive(bars + (t >= NBJ - 3 ? B_FREE + t - (NBJ - 3) : B_RAWB + sl) * 8);
                    asm volatile("fence.proxy.async.global;" ::: "memory");
                    __syncwarp();
                    if (elect_one()) mbar_arrive(bars + (B_GO + t) * 8);
                    int cs[4];
#pragma unroll
                    for (int i = 0; i < 4; i++) cs[i] = sum4(o[i].x, sum4(o[i].y, 0));
                    const int p01 = cs[0] + cs[1] * 65536, p23 = cs[2] + cs[3] * 65536;
                    const bool h = lane & 16;
                    int x = (h ? p23 : p01) + __shfl_xor_sync(~0u, h ? p01 : p23, 16);
                    x += __shfl_xor_sync(~0u, x, 8);
                    const int lo = (int)(short)x, v = (lane & 8) ? (x - lo) >> 16 : lo;
                    const int G = __shfl_sync(~0u, myG, t);
                    if (G != r) {
                        red_async(mapa(sb + SM_CS + lane * 4, G), v, mapa(bars + B_CS * 8, G));
                    } else {
                        red_shared(sb + SM_CS + lane * 4, v);
                        __syncwarp();
                        if (elect_one()) mbar_arrive(bars + B_CS * 8);
                    }
                }
            } else {
                const uint32_t rd0 = sb + (lane >> 3) * 2048 + (lane & 7) * 16;
                const BJob mb = decode_b(X1, (lane & 15) * 16 + r);
                const int myG = mb.G | mb.u << 8;
#pragma unroll 1
                for (int t = warp - 12; t < NBJ; t += 4) {
                    const uint32_t rdB = rd0 + stage_w<k2>(t);
                    uint4* const d = sc->s8 + (1024 + c * 256 + t * 16 + r) * 128 + lane;
                    uint4 o[4];
                    mbar_wait(bars + (B_RAWB + 3 + t) * 8);
                    CV_B(0, x) CV_B(1, y) CV_B(2, z) CV_B(3, w)
#pragma unroll
                    for (int i = 0; i < 4; i++) stg128(d + i * 32, o[i]);
                    if (t < 4) cluster_wait();
                    if (elect_one()) mbar_arrive(bars + (B_FREE + t - (NBJ - 3)) * 8);
                    asm volatile("fence.proxy.async.global;" ::: "memory");
                    __syncwarp();
                    const unsigned rb = read_back(d, lane), ep = ld_flag(epoch(sc, r, c));
                    int cs[4];
#pragma unroll
                    for (int i = 0; i < 4; i++) cs[i] = sum4(o[i].x, sum4(o[i].y, sum4(o[i].z, sum4(o[i].w, 0))));
                    const bool h = lane & 16, odd = lane & 8;
                    int x = (h ? cs[2] : cs[0]) + __shfl_xor_sync(~0u, h ? cs[0] : cs[2], 16);
                    int y = (h ? cs[3] : cs[1]) + __shfl_xor_sync(~0u, h ? cs[1] : cs[3], 16);
                    const int v = (odd ? y : x) + __shfl_xor_sync(~0u, odd ? x : y, 8);
                    const int gu = __shfl_sync(~0u, myG, t);
                    publish(rb, o[0].x, sc->flag + F_W + (gu >> 8));
                    const int old = atomicAdd(sc->cs[ep & 1] + col_of(gu & 255) + (lane & 7) * 4 + (lane >> 3), v);
                    if (old == 0x7FFFFFFF) sc->sink[0] = old;
                    __syncwarp();
                    if (elect_one()) flag_add(sc->flag + F_CS + (gu & 255) / 5);
                }
            }
        } else {
            asm volatile("setmaxnreg.dec.sync.aligned.u32 32;");
            if (warp == 11) {
                if (elect_one()) {
#pragma unroll
                    for (int i = 0; i < (k2 ? NU / 2 : NBJ); i++)
                        mbar_init(bars + (B_GO + i) * 8, k2 ? (i * 2 + (r & 1) >= NSLOT ? 9 : 1) : (i * 16 + r >= NSLOT * 5 ? 2 + 4 * CS : 2));
#pragma unroll
                    for (int i = 0; i < 3; i++) mbar_init(bars + (B_FILL + i) * 8, 4);
                }
                const int u2 = lane * 2 + (r & 1), q = k2 ? (u2 < 32 ? 5 * u2 : 4 * u2 + 32) : (lane & 15) * 16 + r;
                const BJob bj = decode_b(X1, q);
                unsigned seen = 0;
                if (!k2) {
                    const int nself = __popc(__ballot_sync(~0u, lane < NBJ && bj.G == r));
                    sts32(sb + SM_CS + lane * 4, 0);
                    if (lane == 0) {
                        mbar_init(bars + B_CS * 8, 1 + 2 * nself);
                        mbar_expect_tx(bars + B_CS * 8, (16 - nself) * 256);
                    }
                    seen = lds32(sb + SM_CS + lane * 4);
                }
                fence_init();
                asm volatile("barrier.cluster.arrive.relaxed.aligned;" :: "r"(seen) : "memory");
                const char* src = (const char*)sc->s8 + (1024 + c * 256 + q) * 2048;
                const uint32_t dst = sb + SM_RING + ((!k2 && q >= 160) ? ((q + 20) & 31) * 2048 : (bj.u % NSLOT) * SLOT + bj.pos * 2048);
                const uint32_t fb = bars + (B_FULLB + fb_of(X1, bj.u)) * 8;
                cluster_wait();
                if (!k2) scale_bias(scale_x, scale_w + c * TN, bias + c * TN, sb, lane);
#pragma unroll 1
                for (int i = 0; i < (k2 ? NU / 2 : NBJ); i++) {
                    mbar_wait(bars + (B_GO + i) * 8);
                    if (lane == i) {
                        asm volatile("cp.async.bulk.shared::cluster.global.mbarrier::complete_tx::bytes.multicast::cluster [%0], [%1], %2, [%3], %4;"
                                     :: "r"(dst), "l"(src), "r"(k2 ? (u2 < 32 ? SLOT : 8192) : 2048), "r"(fb), "h"((uint16_t)(k2 ? 3 : 0xFFFF)) : "memory");
                    }
                    __syncwarp();
                }
            } else if (warp == 10) {
                const unsigned ep = (__shfl_sync(~0u, ld_flag(sc->flag + r * 32 + (lane < 16 ? lane : 16 + c)), 16) + 1) * 4;
                const unsigned* f = sc->flag + r * 32 + (lane & 15);
                bool dn = lane >= 16;
                const bool fr = lane < (k2 ? 7 : 13);
                cluster_wait();
                for (int it = 0;; it++) {
                    const unsigned v = ld_flag(f);
                    if (!dn && (int)(v - ep) >= 0 && (fr || mbar_test(bars + (B_AFREE + lane) * 8))) {
                        dn = true;
                        tile_load(sc, sb + SM_A + lane * 8192, r * 16 + lane, bars + (B_FULLA + lane) * 8);
                    }
                    if (__all_sync(~0u, dn)) break;
                    if (it > (1 << 22)) __trap();
                }
            } else {
                const bool isw = warp == 9;
                const uint32_t rb = bars + (isw ? B_RAWB : B_RAWA) * 8;
                if (elect_one()) {
#pragma unroll
                    for (int i = 0; i < 13; i++) if (i < 3 || i >= (k2 ? 7 : 6)) mbar_init(rb + i * 8, (i < 3 && isw && !k2) ? 2 : 1);
                    if (isw) {
#pragma unroll
                        for (int i = 13; i < 17; i++) mbar_init(rb + i * 8, 1);
                        if (!k2) { mbar_init(rb + 4 * 8, 1); mbar_init(rb + 5 * 8, 1); }
                    }
                }
                __syncwarp();
                const int nj = isw ? NBJ : na, j0 = k2 ? 4 : isw ? 1 : 3;
                if (lane >= j0 && lane < nj) mbar_expect_tx(rb + (3 + lane) * 8, 8192);
                fence_init();
                cluster_arrive();
                const unsigned e0 = k2 ? ld_flag(epoch(sc, r, c)) : 0;
                const int k = lane / 3, x = lane * 16 + r;
                int sl = lane - k * 3, y, z, T;
                if (isw) {
                    const BJob bj = decode_b(X1, x & 255);
                    y = bj.slab * 64; z = (c * TN + col_of(bj.G)) >> 5; T = time_w(x);
                } else {
                    const int a = (lane * NCTA + g) ^ REV;
                    y = (a >> 6) * 2; z = (a & 63) * 32; T = time_x(x);
                    if (na == 10) sl = sl ? sl - 1 : 2;
                }
                const unsigned te = t0 + (k2 ? sched2(x) : sched(T));
                const uint32_t sd = sb + (isw ? stage_w<k2>(lane) : SM_A + (13 + sl) * 8192);
#pragma unroll 1
                for (int t = j0; t < nj; t++) {
                    if (lane == t) {
                        if (t >= 3 && !k2) mbar_wait(rb + sl * 8, (k & 1) ^ 1);
                        while ((int)(te - clk()) > 0) ;
                        raw_load(maps.m + isw, y, z, sd, rb + (3 + t) * 8);
                    }
                    __syncwarp();
                }
                cluster_wait();
                if (elect_one()) asm volatile("prefetch.tensormap [%0];" :: "l"(maps.m + 2 + isw) : "memory");
                if (!isw) cw = 2;
                if (k2) {
                    if (!isw) {
                        if (lane < TN / 16) sc->cs[(e0 & 1) ^ 1][r * (TN / 16) + lane] = 0;
                        const int u = lane * 2 + (r & 1);
                        const unsigned tg = (e0 + 1) * (u < 32 ? 5 : 4);
                        bool dn = u >= NU;
                        for (int it = 0;; it++) {
                            if (!dn && (int)(ld_flag(sc->flag + F_W + u) - tg) >= 0) {
                                dn = true;
                                mbar_arrive(bars + (B_GO + lane) * 8);
                            }
                            if (__all_sync(~0u, dn)) break;
                            if (it > (1 << 22)) __trap();
                        }
                    } else {
                        const float zxf = ld_zx(zero_x);
                        scale_bias(scale_x, scale_w + c * TN, bias + c * TN, sb, lane);
#pragma unroll 1
                        for (int h = 0; h < 3; h++) {
                            for (int it = 0; (int)(ld_flag(sc->flag + F_CS + h) - (e0 + 1) * (h < 2 ? 80 : 32)) < 0; it++) if (it > (1 << 22)) __trap();
                            int2 v[3];
                            int i[3];
#pragma unroll
                            for (int j = 0; j < 3; j++) {
                                i[j] = (j < 2 ? h * 64 + j * 32 : 128 + h * 16) + lane;
                                v[j] = __ldcg((const int2*)sc->cs[e0 & 1] + i[j]);
                            }
#pragma unroll
                            for (int j = 0; j < 3; j++) {
                                const uint32_t pa = sb + SM_PAR + i[j] * 4;
                                const uint32_t z = fold(zero_term(v[j].x, v[j].y, zxf), lds32(pa + TN * 2), lds32(pa + TN * 4));
                                if (h < 2 ? (j < 2 || lane < 16) : j == 2) st_async(pa, z, bars + (B_PAR + h) * 8);
                            }
                        }
                    }
                }
            }
        }
        if (!k2 && r < NBJ && warp == (r < 10 ? 8 : 10)) {
            const float zxf = ld_zx(zero_x);
            const int w = lane & 15;
            uint32_t sw = 0, bi = 0;
            if (CFG_EPI == 3) { mbar_wait(bars + B_SW * 8); sw = lds32(sb + SM_PAR + TN * 2 + col_of(r) * 2 + w * 4); bi = lds32(sb + SM_PAR + TN * 4 + col_of(r) * 2 + w * 4); }
            mbar_wait(bars + B_CS * 8);
            const uint32_t ca = sb + SM_CS + ((w >> 1) + (w & 1) * 16) * 4;
            const uint32_t z = fold(zero_term(lds32(ca), lds32(ca + 32), zxf), sw, bi);
            const int piece = r < 10 ? (r >= 5) : (r - 6) >> 1;
#pragma unroll 1
            for (int i = lane >> 4; i < CS; i += 2) st_async(mapa(sb + SM_PAR + col_of(r) * 2 + w * 4, i), z, mapa(bars + (B_PAR + piece) * 8, i));
        }
#pragma unroll 1
        for (int n = cw, k = 0; n < NF; n += 3, k ^= 1) {
            const int gm = (int)(ford_table<k2>() >> (4 * n)), g = (gm >> 3) & 1, m = gm & 7;
            const int x = n >= 10 ? (n >> 1) * 64 : m == 4 ? 256 + g * 32 : g * 128 + (m & 1) * 64;
            const int y = n >= 10 ? (n & 1) * 64 : (m & 2) * 32;
            mbar_wait(bars + (B_FILL + cw) * 8, k);
            asm volatile("fence.proxy.async.shared::cta;" ::: "memory");
            if (elect_one()) tile_store(maps.m + (n < 10 && m == 4 ? 3 : 2), c * TN + x, r * 128 + y, sb + SM_STG + ((cw + NBJ) % 3) * 8192);
            asm volatile("cp.async.bulk.commit_group;" ::: "memory");
            asm volatile("cp.async.bulk.wait_group.read 0;" ::: "memory");
            __syncwarp();
            if (n < NF - 3 && elect_one()) mbar_arrive(bars + (B_FREE + 3 + n) * 8);
        }
    }
}

__global__ void __launch_bounds__(256)
w8a8_plain(const int* __restrict__ qx, const int* __restrict__ qw, const __nv_bfloat16* __restrict__ scale_x, const int* __restrict__ zero_x,
           const __nv_bfloat16* __restrict__ scale_w, const __nv_bfloat16* __restrict__ bias, __nv_bfloat16* __restrict__ out) {
    __shared__ int xs[16][K_ / 4];
    const int n = (blockIdx.x * 256 + threadIdx.x) * 2, m0 = blockIdx.y * 16;
    for (int i = threadIdx.x; i < 16 * K_ / 4; i += 256) {
        const uint4 v = ((const uint4*)qx)[m0 * (K_ / 4) + i];
        xs[i / (K_ / 4)][i % (K_ / 4)] = pack4(v.x, v.y, v.z, v.w);
    }
    __syncthreads();
    int acc[16][2] = {}, cs[2] = {};
    for (int k = 0; k < K_ / 4; k++) {
        uint2 v[4];
#pragma unroll
        for (int i = 0; i < 4; i++) v[i] = *(const uint2*)(qw + (k * 4 + i) * N_ + n);
        const unsigned w0 = pack4(v[0].x, v[1].x, v[2].x, v[3].x), w1 = pack4(v[0].y, v[1].y, v[2].y, v[3].y);
        cs[0] = sum4(w0, cs[0]); cs[1] = sum4(w1, cs[1]);
#pragma unroll
        for (int i = 0; i < 16; i++) { acc[i][0] = __dp4a(xs[i][k], (int)w0, acc[i][0]); acc[i][1] = __dp4a(xs[i][k], (int)w1, acc[i][1]); }
    }
    const uint32_t sx2 = (uint32_t)*(const unsigned short*)scale_x * 0x10001u, bi = *(const unsigned*)(bias + n);
    uint32_t sw = *(const unsigned*)(scale_w + n);
    if (CFG_EPI) sw = bf2_mul(sw, sx2);
    const uint32_t zc = fold(zero_term(cs[0], cs[1], ld_zx(zero_x)), sw, bi);
#pragma unroll
    for (int i = 0; i < 16; i++) *(unsigned*)(out + (m0 + i) * N_ + n) = epi(acc[i][0], acc[i][1], zc, sx2, sw, bi);
}

}

typedef CUresult (*EncodeFn)(CUtensorMap*, CUtensorMapDataType, cuuint32_t, void*, const cuuint64_t*, const cuuint64_t*,
                             const cuuint32_t*, const cuuint32_t*, CUtensorMapInterleave, CUtensorMapSwizzle,
                             CUtensorMapL2promotion, CUtensorMapFloatOOBfill);

extern "C" void kernel_launch(void* const* d_in, const int* in_sizes, int n_in, void* d_out, int out_size) {
    using namespace w8;
    static EncodeFn encode = nullptr;
    static cudaStream_t side;
    static cudaEvent_t started, joined;
    static int clusters = -1;
    static Scratch* sc;
    cudaLaunchConfig_t cfg = {};
    cfg.gridDim = dim3(NCTA); cfg.blockDim = dim3(512); cfg.dynamicSmemBytes = SM_TOTAL; cfg.stream = cudaStreamPerThread;
    if (clusters < 0) {
        void* fn = nullptr;
        cudaDriverEntryPointQueryResult qr;
        cudaGetDriverEntryPoint("cuTensorMapEncodeTiled", &fn, cudaEnableDefault, &qr);
        encode = (EncodeFn)fn;
        cudaGetSymbolAddress((void**)&sc, g_scratch);
        cudaStreamCreateWithFlags(&side, cudaStreamNonBlocking);
        cudaEventCreateWithFlags(&started, cudaEventDisableTiming);
        cudaEventCreateWithFlags(&joined, cudaEventDisableTiming);
        cudaFuncSetAttribute(w8a8_kernel<false>, cudaFuncAttributeMaxDynamicSharedMemorySize, SM_TOTAL);
        cudaFuncSetAttribute(w8a8_kernel<true>, cudaFuncAttributeMaxDynamicSharedMemorySize, SM_TOTAL);
        cudaFuncSetAttribute(w8a8_kernel<false>, cudaFuncAttributeNonPortableClusterSizeAllowed, 1);
        if (cudaOccupancyMaxActiveClusters(&clusters, w8a8_kernel<false>, &cfg) != cudaSuccess) { clusters = 0; cudaGetLastError(); }
    }
    const __nv_bfloat16 *sx = (const __nv_bfloat16*)d_in[2], *sw = (const __nv_bfloat16*)d_in[4], *bias = (const __nv_bfloat16*)d_in[5];
    const int* zx = (const int*)d_in[3];
    if (clusters < NCL) {
        w8a8_plain<<<dim3(N_ / 512, M_ / 16), 256, 0, cudaStreamPerThread>>>((const int*)d_in[0], (const int*)d_in[1], sx, zx, sw, bias, (__nv_bfloat16*)d_out);
        return;
    }
    Maps maps;
    const cuuint32_t es[3] = {1, 1, 1};
    {
        const cuuint64_t dim[3] = {32, K_ / 32, M_}, str[2] = {128, K_ * 4};
        const cuuint32_t box[3] = {32, 2, 32};
        encode(&maps.m[0], CU_TENSOR_MAP_DATA_TYPE_INT32, 3, d_in[0], dim, str, box, es, CU_TENSOR_MAP_INTERLEAVE_NONE,
               CU_TENSOR_MAP_SWIZZLE_128B, CU_TENSOR_MAP_L2_PROMOTION_NONE, CU_TENSOR_MAP_FLOAT_OOB_FILL_NONE);
    }
    {
        const cuuint64_t dim[3] = {32, K_, N_ / 32}, str[2] = {N_ * 4, 128};
        const cuuint32_t box[3] = {32, 64, 1};
        encode(&maps.m[1], CU_TENSOR_MAP_DATA_TYPE_INT32, 3, d_in[1], dim, str, box, es, CU_TENSOR_MAP_INTERLEAVE_NONE,
               CU_TENSOR_MAP_SWIZZLE_NONE, CU_TENSOR_MAP_L2_PROMOTION_NONE, CU_TENSOR_MAP_FLOAT_OOB_FILL_NONE);
    }
    for (int i = 0; i < 2; i++) {
        const cuuint64_t dim[2] = {N_, M_}, str[1] = {N_ * 2};
        const cuuint32_t box[2] = {i ? 32u : 64u, i ? 128u : 64u};
        encode(&maps.m[2 + i], CU_TENSOR_MAP_DATA_TYPE_BFLOAT16, 2, d_out, dim, str, box, es, CU_TENSOR_MAP_INTERLEAVE_NONE,
               i ? CU_TENSOR_MAP_SWIZZLE_NONE : CU_TENSOR_MAP_SWIZZLE_128B, CU_TENSOR_MAP_L2_PROMOTION_NONE, CU_TENSOR_MAP_FLOAT_OOB_FILL_NONE);
    }
    cudaLaunchAttribute at;
    at.id = cudaLaunchAttributeProgrammaticEvent;
    at.val.programmaticEvent.event = started; at.val.programmaticEvent.flags = 0; at.val.programmaticEvent.triggerAtBlockStart = 1;
    cfg.attrs = &at; cfg.numAttrs = 1;
    cudaLaunchKernelEx(&cfg, w8a8_kernel<false>, sc, (const char*)d_in[0], (const char*)d_in[1], sx, zx, sw, bias, maps);
    cudaStreamWaitEvent(side, started, 0);
    cfg.gridDim = dim3(20); cfg.stream = side; cfg.numAttrs = 0;
    cudaLaunchKernelEx(&cfg, w8a8_kernel<true>, sc, (const char*)d_in[0], (const char*)d_in[1], sx, zx, sw, bias, maps);
    cudaEventRecord(joined, side);
    cudaStreamWaitEvent(cudaStreamPerThread, joined, 0);
}
```

```cpp
#include <cuda_runtime.h>
#include <cuda.h>
#include <cuda_bf16.h>
#include <stdint.h>
#include <stddef.h>

#define CFG_X1 13
#define CFG_P1 46
#define CFG_P2 39
#define CFG_PT 100
#define CFG_L0 34
#define CFG_RA 33
#define CFG_T0 -550
#define CFG_Q0 14
#define CFG_Q2 69
#define CFG_Q3 30
#define CFG_T3 400
#define CFG_D3 2
#define CFG_PF7 18
#define CFG_TA 10
#define CFG_EPI 3
#define CFG_X2 11
#define CFG_S3 12
#define CFG_D4 4
#define CFG_PG 8

namespace w8 {

constexpr int M_ = 2048, K_ = 1024, N_ = 3584;
constexpr int CS = 16, NCL = 7, NCTA = CS * NCL;
constexpr int WA = 160, WB = 64, TN = 2 * WA + 2 * WB;
constexpr int NSLOT = 7, SLOT = WA * 64;
constexpr int NAJ = 1024;
constexpr int REV = 60;
constexpr int TA = CFG_TA;

constexpr int L0 = CFG_L0, RA = CFG_RA, RB64 = 64 * RA / (RA - 16);
constexpr int P1 = CFG_P1, P2 = CFG_P2, PT = CFG_PT, T0 = CFG_T0;
__device__ __forceinline__ int time_x(int x) { return max(x, L0 + (((x - L0) * RA) >> 4)); }
__device__ __forceinline__ int time_w(int q) { return min(L0 + ((q * RB64) >> 6), NAJ / NCL + q); }
__device__ __forceinline__ unsigned sched(int T) { return T * P2 + min(T, PT) * (P1 - P2); }
__device__ __forceinline__ int sched2(int q) { return (min(q, 160) - CFG_Q0) * CFG_Q2 + max(q - 160, 0) * CFG_Q3; }

constexpr int SM_A = 0;
constexpr int SM_RING = 131072;
constexpr int SM_STG = SM_RING + NSLOT * SLOT;
constexpr int SM_PAR = SM_STG + 3 * 8192;
constexpr int SM_CS = SM_PAR + 3 * TN * 2;
constexpr int SM_BAR = SM_CS + 128;
constexpr int B_FULLB = 0, B_FULLA = 56, B_PAR = 72, B_SW = 77, B_AFREE = 74  , B_FREE = 90,
              B_GO = 104, B_FILL = 128, B_CS = 131, B_RAWA = 132, B_RAWB = 145, B_END = 163;
constexpr int SM_TOTAL = SM_BAR + B_END * 8;
static_assert(SM_TOTAL <= 232448, "");

constexpr int F_W = 512, F_CS = 576;
struct Scratch {
    unsigned flag[768];
    int cs[2][TN];
    int sink[384];
    uint4 s8[(1024 + 8 * 256) * 128];
};
static_assert(offsetof(Scratch, s8) == 8192, "");
__device__ __align__(8192) Scratch g_scratch;
__device__ __forceinline__ unsigned* epoch(Scratch* sc, int r, int c) { return sc->flag + r * 32 + 16 + c; }

__device__ __forceinline__ void mbar_init(uint32_t bar, uint32_t cnt) {
    asm volatile("mbarrier.init.shared::cta.b64 [%0], %1;" :: "r"(bar), "r"(cnt) : "memory");
}
__device__ __forceinline__ void mbar_expect_tx(uint32_t bar, uint32_t bytes) {
    asm volatile("mbarrier.arrive.expect_tx.shared::cta.b64 _, [%0], %1;" :: "r"(bar), "r"(bytes) : "memory");
}
__device__ __forceinline__ void mbar_arrive(uint32_t bar) {
    asm volatile("mbarrier.arrive.shared::cta.b64 _, [%0];" :: "r"(bar) : "memory");
}
__device__ __forceinline__ void mbar_arrive_cluster(uint32_t bar) {
    asm volatile("mbarrier.arrive.shared::cluster.b64 _, [%0];" :: "r"(bar) : "memory");
}
__device__ __forceinline__ void mbar_wait(uint32_t bar, uint32_t parity = 0) {
    asm volatile("{\n.reg .pred p;\n.reg .u32 c;\n"
                 "mbarrier.try_wait.parity.shared::cta.b64 p, [%0], %1;\n"
                 "@p bra WAIT_DONE;\n"
                 "mov.u32 c, 0;\n"
                 "WAIT_LOOP:\n"
                 "mbarrier.try_wait.parity.shared::cta.b64 p, [%0], %1;\n"
                 "@p bra WAIT_DONE;\n"
                 "add.u32 c, c, 1;\nsetp.lt.u32 p, c, 0x100000;\n"
                 "@p bra WAIT_LOOP;\n"
                 "trap;\n"
                 "WAIT_DONE:\n}" :: "r"(bar), "r"(parity) : "memory");
}
__device__ __forceinline__ void mbar_wait2(uint32_t bar0, uint32_t bar1) {
    asm volatile("{\n.reg .pred p, q;\n.reg .u32 c;\nmov.u32 c, 0;\n"
                 "WAIT_LOOP:\n"
                 "mbarrier.try_wait.parity.shared::cta.b64 p, [%0], 0;\n"
                 "mbarrier.try_wait.parity.shared::cta.b64 q, [%1], 0;\n"
                 "and.pred p, p, q;\n"
                 "@p bra WAIT_DONE;\n"
                 "add.u32 c, c, 1;\nsetp.lt.u32 p, c, 0x100000;\n"
                 "@p bra WAIT_LOOP;\n"
                 "trap;\n"
                 "WAIT_DONE:\n}" :: "r"(bar0), "r"(bar1) : "memory");
}
__device__ __forceinline__ bool mbar_test(uint32_t bar) {
    uint32_t ok;
    asm volatile("{\n.reg .pred p;\nmbarrier.test_wait.parity.shared::cta.b64 p, [%1], 0;\nselp.u32 %0, 1, 0, p;\n}" : "=r"(ok) : "r"(bar) : "memory");
    return ok;
}
__device__ __forceinline__ bool mbar_test2(uint32_t bar0, uint32_t bar1) {
    uint32_t ok;
    asm volatile("{\n.reg .pred p, q;\nmbarrier.test_wait.parity.shared::cta.b64 p, [%1], 0;\n"
                 "mbarrier.test_wait.parity.shared::cta.b64 q, [%2], 0;\nand.pred p, p, q;\nselp.u32 %0, 1, 0, p;\n}"
                 : "=r"(ok) : "r"(bar0), "r"(bar1) : "memory");
    return ok;
}
__device__ __forceinline__ bool elect_one() {
    uint32_t ok;
    asm volatile("{\n.reg .pred p;\nelect.sync _|p, 0xffffffff;\nselp.u32 %0, 1, 0, p;\n}" : "=r"(ok));
    return ok;
}
__device__ __forceinline__ unsigned ld_flag(const unsigned* p) {
    unsigned v;
    asm volatile("ld.relaxed.gpu.global.u32 %0, [%1];" : "=r"(v) : "l"(p) : "memory");
    return v;
}
__device__ __forceinline__ uint4 lds128(uint32_t a) {
    uint4 v;
    asm volatile("ld.shared.v4.b32 {%0,%1,%2,%3}, [%4];" : "=r"(v.x), "=r"(v.y), "=r"(v.z), "=r"(v.w) : "r"(a) : "memory");
    return v;
}
__device__ __forceinline__ void sts128(uint32_t a, uint4 v) {
    asm volatile("st.shared.v4.b32 [%0], {%1,%2,%3,%4};" :: "r"(a), "r"(v.x), "r"(v.y), "r"(v.z), "r"(v.w) : "memory");
}
__device__ __forceinline__ uint32_t lds32(uint32_t a) {
    uint32_t v;
    asm volatile("ld.shared.b32 %0, [%1];" : "=r"(v) : "r"(a) : "memory");
    return v;
}
__device__ __forceinline__ void sts32(uint32_t a, uint32_t v) {
    asm volatile("st.shared.b32 [%0], %1;" :: "r"(a), "r"(v) : "memory");
}
__device__ __forceinline__ void stg128(void* p, uint4 v) {
    asm volatile("st.global.v4.b32 [%0], {%1,%2,%3,%4};" :: "l"(p), "r"(v.x), "r"(v.y), "r"(v.z), "r"(v.w) : "memory");
}
__device__ __forceinline__ unsigned pack4(unsigned a, unsigned b, unsigned c, unsigned d) {
    unsigned lo, r;
    asm("cvt.pack.sat.s8.s32.b32 %0, %1, %2, 0;" : "=r"(lo) : "r"(d), "r"(c));
    asm("cvt.pack.sat.s8.s32.b32 %0, %1, %2, %3;" : "=r"(r) : "r"(b), "r"(a), "r"(lo));
    return r;
}
__device__ __forceinline__ uint32_t mapa(uint32_t a, uint32_t r) {
    uint32_t o;
    asm("mapa.shared::cluster.u32 %0, %1, %2;" : "=r"(o) : "r"(a), "r"(r));
    return o;
}
__device__ __forceinline__ unsigned clk() {
    unsigned t;
    asm volatile("mov.u32 %0, %clock;" : "=r"(t));
    return t;
}
__device__ __forceinline__ void cluster_arrive() { asm volatile("barrier.cluster.arrive.relaxed.aligned;" ::: "memory"); }
__device__ __forceinline__ void cluster_wait() { asm volatile("barrier.cluster.wait.aligned;" ::: "memory"); }
__device__ __forceinline__ void fence_init() { asm volatile("fence.mbarrier_init.release.cluster;" ::: "memory"); }
__device__ __forceinline__ void flag_add(unsigned* p) { asm volatile("red.relaxed.gpu.global.add.u32 [%0], 1;" :: "l"(p) : "memory"); }
__device__ __forceinline__ void raw_load(const void* map, int y, int z, uint32_t dst, uint32_t bar) {
    asm volatile("cp.async.bulk.tensor.3d.shared::cluster.global.tile.mbarrier::complete_tx::bytes [%0], [%1, {0, %2, %3}], [%4];"
                 :: "r"(dst), "l"(map), "r"(y), "r"(z), "r"(bar) : "memory");
}
__device__ __forceinline__ void tile_load(Scratch* sc, uint32_t dst, int tile, uint32_t bar) {
    asm volatile("cp.async.bulk.shared::cluster.global.mbarrier::complete_tx::bytes [%0], [%1], %2, [%3];"
                 :: "r"(dst), "l"((const char*)sc->s8 + tile * 8192), "r"(8192), "r"(bar) : "memory");
}
__device__ __forceinline__ void tile_store(const void* map, int x, int y, uint32_t src) {
    asm volatile("cp.async.bulk.tensor.2d.global.shared::cta.tile.bulk_group [%0, {%1, %2}], [%3];"
                 :: "l"(map), "r"(x), "r"(y), "r"(src) : "memory");
}
__device__ __forceinline__ void st_async(uint32_t a, uint32_t v, uint32_t bar) {
    asm volatile("st.async.weak.shared::cluster.mbarrier::complete_tx::bytes.b32 [%0], %1, [%2];" :: "r"(a), "r"(v), "r"(bar) : "memory");
}
__device__ __forceinline__ void red_async(uint32_t a, int v, uint32_t bar) {
    asm volatile("red.async.relaxed.cluster.shared::cluster.mbarrier::complete_tx::bytes.add.s32 [%0], %1, [%2];" :: "r"(a), "r"(v), "r"(bar) : "memory");
}
__device__ __forceinline__ void red_shared(uint32_t a, int v) { asm volatile("red.shared.add.s32 [%0], %1;" :: "r"(a), "r"(v) : "memory"); }
__device__ __forceinline__ int sum4(unsigned v, int c) { return __dp4a((int)v, 0x01010101, c); }

constexpr uint32_t DESC_A_HI = 0x80000000u | (512 >> 4);
constexpr uint32_t DESC_B_HI = 512 >> 4;
template <int NR> __device__ __forceinline__ void wgmma_n160(int (&d)[NR], uint32_t alo, uint32_t blo, int scale_d) {
    asm volatile("{\n.reg .pred p;\n.reg .b64 da, db;\nsetp.ne.b32 p, %82, 0;\n"
        "mov.b64 da, {%80, %83};\nmov.b64 db, {%81, %84};\n"
        "wgmma.mma_async.sync.aligned.m64n160k32.s32.s8.s8 "
        "{%0, %1, %2, %3, %4, %5, %6, %7, %8, %9, %10, %11, %12, %13, %14, %15, "
        "%16, %17, %18, %19, %20, %21, %22, %23, %24, %25, %26, %27, %28, %29, %30, %31, "
        "%32, %33, %34, %35, %36, %37, %38, %39, %40, %41, %42, %43, %44, %45, %46, %47, "
        "%48, %49, %50, %51, %52, %53, %54, %55, %56, %57, %58, %59, %60, %61, %62, %63, "
        "%64, %65, %66, %67, %68, %69, %70, %71, %72, %73, %74, %75, %76, %77, %78, %79}, "
        "da, db, p;\n}\n"
        : "+r"(d[0]), "+r"(d[1]), "+r"(d[2]), "+r"(d[3]), "+r"(d[4]), "+r"(d[5]), "+r"(d[6]), "+r"(d[7]),
          "+r"(d[8]), "+r"(d[9]), "+r"(d[10]), "+r"(d[11]), "+r"(d[12]), "+r"(d[13]), "+r"(d[14]), "+r"(d[15]),
          "+r"(d[16]), "+r"(d[17]), "+r"(d[18]), "+r"(d[19]), "+r"(d[20]), "+r"(d[21]), "+r"(d[22]), "+r"(d[23]),
          "+r"(d[24]), "+r"(d[25]), "+r"(d[26]), "+r"(d[27]), "+r"(d[28]), "+r"(d[29]), "+r"(d[30]), "+r"(d[31]),
          "+r"(d[32]), "+r"(d[33]), "+r"(d[34]), "+r"(d[35]), "+r"(d[36]), "+r"(d[37]), "+r"(d[38]), "+r"(d[39]),
          "+r"(d[40]), "+r"(d[41]), "+r"(d[42]), "+r"(d[43]), "+r"(d[44]), "+r"(d[45]), "+r"(d[46]), "+r"(d[47]),
          "+r"(d[48]), "+r"(d[49]), "+r"(d[50]), "+r"(d[51]), "+r"(d[52]), "+r"(d[53]), "+r"(d[54]), "+r"(d[55]),
          "+r"(d[56]), "+r"(d[57]), "+r"(d[58]), "+r"(d[59]), "+r"(d[60]), "+r"(d[61]), "+r"(d[62]), "+r"(d[63]),
          "+r"(d[64]), "+r"(d[65]), "+r"(d[66]), "+r"(d[67]), "+r"(d[68]), "+r"(d[69]), "+r"(d[70]), "+r"(d[71]),
          "+r"(d[72]), "+r"(d[73]), "+r"(d[74]), "+r"(d[75]), "+r"(d[76]), "+r"(d[77]), "+r"(d[78]), "+r"(d[79])
        : "r"(alo), "r"(blo), "r"(scale_d), "r"(DESC_A_HI), "r"(DESC_B_HI));
}
template <int NR> __device__ __forceinline__ void wgmma_t128(int (&d)[NR], uint32_t alo, uint32_t blo, int scale_d) {
    asm volatile("{\n.reg .pred p;\n.reg .b64 da, db;\nsetp.ne.b32 p, %66, 0;\n"
        "mov.b64 da, {%64, %67};\nmov.b64 db, {%65, %68};\n"
        "wgmma.mma_async.sync.aligned.m64n128k32.s32.s8.s8 "
        "{%0, %1, %2, %3, %4, %5, %6, %7, %8, %9, %10, %11, %12, %13, %14, %15, "
        "%16, %17, %18, %19, %20, %21, %22, %23, %24, %25, %26, %27, %28, %29, %30, %31, "
        "%32, %33, %34, %35, %36, %37, %38, %39, %40, %41, %42, %43, %44, %45, %46, %47, "
        "%48, %49, %50, %51, %52, %53, %54, %55, %56, %57, %58, %59, %60, %61, %62, %63}, "
        "da, db, p;\n}\n"
        : "+r"(d[0]), "+r"(d[1]), "+r"(d[2]), "+r"(d[3]), "+r"(d[4]), "+r"(d[5]), "+r"(d[6]), "+r"(d[7]),
          "+r"(d[8]), "+r"(d[9]), "+r"(d[10]), "+r"(d[11]), "+r"(d[12]), "+r"(d[13]), "+r"(d[14]), "+r"(d[15]),
          "+r"(d[16]), "+r"(d[17]), "+r"(d[18]), "+r"(d[19]), "+r"(d[20]), "+r"(d[21]), "+r"(d[22]), "+r"(d[23]),
          "+r"(d[24]), "+r"(d[25]), "+r"(d[26]), "+r"(d[27]), "+r"(d[28]), "+r"(d[29]), "+r"(d[30]), "+r"(d[31]),
          "+r"(d[32]), "+r"(d[33]), "+r"(d[34]), "+r"(d[35]), "+r"(d[36]), "+r"(d[37]), "+r"(d[38]), "+r"(d[39]),
          "+r"(d[40]), "+r"(d[41]), "+r"(d[42]), "+r"(d[43]), "+r"(d[44]), "+r"(d[45]), "+r"(d[46]), "+r"(d[47]),
          "+r"(d[48]), "+r"(d[49]), "+r"(d[50]), "+r"(d[51]), "+r"(d[52]), "+r"(d[53]), "+r"(d[54]), "+r"(d[55]),
          "+r"(d[56]), "+r"(d[57]), "+r"(d[58]), "+r"(d[59]), "+r"(d[60]), "+r"(d[61]), "+r"(d[62]), "+r"(d[63])
        : "r"(alo), "r"(blo), "r"(scale_d), "r"(DESC_B_HI), "r"(DESC_A_HI));
}


__device__ __forceinline__ void wg_fence() { asm volatile("wgmma.fence.sync.aligned;" ::: "memory"); }
__device__ __forceinline__ void wg_commit() { asm volatile("wgmma.commit_group.sync.aligned;" ::: "memory"); }
template <int N> __device__ __forceinline__ void wg_wait() { asm volatile("wgmma.wait_group.sync.aligned %0;" :: "n"(N) : "memory"); }

__host__ __device__ constexpr int unit_of(int X1, int piece, int slab) {
    return piece < 2 ? (slab < X1 ? 2 * slab + piece : (piece ? 16 : X1) + slab) : 32 + (piece - 2) * 8 + (slab >> 1);
}
__host__ __device__ constexpr int col_of(int G) { return G == 4 ? 256 : (G > 4 && G < 9) ? 32 * G - 32 : 32 * G; }
struct BJob { int u, slab, G, pos; };
__host__ __device__ constexpr BJob decode_b(int X1, int q) {
    BJob j = {};
    if (q < 160) {
        j.u = q / 5; j.pos = q - j.u * 5;
        const int piece = j.u < 2 * X1 ? (j.u & 1) : (j.u >= X1 + 16);
        j.slab = j.u < 2 * X1 ? (j.u >> 1) : j.u - (piece ? 16 : X1);
        j.G = piece * 5 + j.pos;
    } else {
        q -= 160;
        j.u = 32 + (q >> 2); j.pos = q & 3;
        j.slab = (q >> 1) & 15;
        j.G = 10 + (q >> 5) * 2 + (q & 1);
    }
    return j;
}
__host__ __device__ constexpr int fb_of(int X1, int u) {
    return u < 2 * X1 ? (u & 1) * 32 + (u >> 1) : u < X1 + 16 ? u - X1 : u < 32 ? 16 + u : u < 40 ? u - 16 : u < 48 ? u + 8 : u - 24;
}
__host__ __device__ constexpr uint64_t slot_table(int X1, int piece) {
    uint64_t t = 0;
    for (int s = 0; s < 16; s++) t |= (uint64_t)(unit_of(X1, piece, s) % NSLOT) << (4 * s);
    return t;
}
template <bool k2> __device__ __forceinline__ int stage_w(int t) { return (k2 && t < 9) ? SM_A + (7 + t) * 8192 : SM_STG + (t % 3) * 8192; }
template <bool k2> __host__ __device__ constexpr int ford(int g, int m) {
    return k2 ? g * 5 + m : g ? (m ? 4 + m : 2) : (m < 2 ? m : m < 4 ? m + 1 : 9);
}
template <bool k2> __host__ __device__ constexpr int turn(int n) { return (n + (!k2 && n >= 5)) % 3; }
template <bool k2> __host__ __device__ constexpr uint64_t ford_table() {
    uint64_t t = 0;
    for (int g = 0; g < 2; g++) for (int m = 0; m < 5; m++) t |= (uint64_t)(g * 8 + m) << (4 * ford<k2>(g, m));
    return t;
}
struct Maps { CUtensorMap m[4]; };

__device__ __forceinline__ uint32_t bf2_mul(uint32_t a, uint32_t b) { asm("mul.rn.bf16x2 %0, %0, %1;" : "+r"(a) : "r"(b)); return a; }
__device__ __forceinline__ uint32_t epi(int a, int b, uint32_t zc, uint32_t sx, uint32_t sw, uint32_t bi) {
    uint32_t v;
    float fa = __int2float_rn(a), fb = __int2float_rn(b);
    asm("cvt.rn.bf16x2.f32 %0, %1, %2;" : "=r"(v) : "f"(fb), "f"(fa));
    if (CFG_EPI == 3) {
        asm("fma.rn.bf16x2 %0, %0, %1, %2;" : "+r"(v) : "r"(sw), "r"(zc));
        return v;
    }
    asm("sub.rn.bf16x2 %0, %0, %1;" : "+r"(v) : "r"(zc));
    if (CFG_EPI == 0) {
        v = bf2_mul(bf2_mul(v, sx), sw);
        asm("add.rn.bf16x2 %0, %0, %1;" : "+r"(v) : "r"(bi));
    } else {
        asm("fma.rn.bf16x2 %0, %0, %1, %2;" : "+r"(v) : "r"(sw), "r"(bi));
    }
    return v;
}
__device__ __forceinline__ uint32_t zero_term(int lo, int hi, float zx) {
    uint32_t z;
    asm("cvt.rn.bf16x2.f32 %0, %1, %2;" : "=r"(z) : "f"(__bfloat162float(__float2bfloat16_rn((float)hi)) * zx),
                                                    "f"(__bfloat162float(__float2bfloat16_rn((float)lo)) * zx));
    return z;
}
__device__ __forceinline__ uint32_t fold(uint32_t z, uint32_t sw, uint32_t bi) {
    if (CFG_EPI == 3) asm("fma.rn.bf16x2 %0, %1, %2, %3;" : "=r"(z) : "r"(z ^ 0x80008000u), "r"(sw), "r"(bi));
    return z;
}
__device__ __forceinline__ float ld_zx(const int* zero_x) { return __bfloat162float(__float2bfloat16_rn((float)__ldg(zero_x))); }
struct Par { uint4 zc, sw, bi; };
__device__ __forceinline__ Par ld_par(uint32_t p) { return {lds128(p), lds128(p + TN * 2), CFG_EPI == 3 ? uint4{} : lds128(p + TN * 4)}; }
__device__ __forceinline__ uint4 epi_row(const int (&a)[WA / 2], int o, const Par& p, uint32_t sx2) {
    uint4 r;
    r.x = epi(a[o + 0], a[o + 4], p.zc.x, sx2, p.sw.x, p.bi.x);
    r.y = epi(a[o + 8], a[o + 12], p.zc.y, sx2, p.sw.y, p.bi.y);
    r.z = epi(a[o + 1], a[o + 5], p.zc.z, sx2, p.sw.z, p.bi.z);
    r.w = epi(a[o + 9], a[o + 13], p.zc.w, sx2, p.sw.w, p.bi.w);
    return r;
}
__device__ __forceinline__ void scale_bias(const __nv_bfloat16* scale_x, const __nv_bfloat16* scale_w, const __nv_bfloat16* bias, uint32_t sb, int lane) {
    const uint32_t sx2 = (uint32_t)__ldg((const unsigned short*)scale_x) * 0x10001u;
#pragma unroll
    for (int i = lane; i < TN / 4; i += 32) {
        const bool hi = i >= TN / 8;
        uint4 v = __ldg((const uint4*)(hi ? bias : scale_w) + (hi ? i - TN / 8 : i));
        if (CFG_EPI && !hi) v = {bf2_mul(v.x, sx2), bf2_mul(v.y, sx2), bf2_mul(v.z, sx2), bf2_mul(v.w, sx2)};
        sts128(sb + SM_PAR + TN * 2 + i * 16, v);
    }
    __syncwarp();
    if (elect_one()) mbar_arrive(sb + SM_BAR + B_SW * 8);
}
template <bool k2> __device__ __forceinline__ void release(uint32_t go, int u, int lane) {
    const int v = u + NSLOT;
    if (k2) {
        const int q = v + lane;
        if (lane < (v < 48 ? 1 : 0)) mbar_arrive_cluster(mapa(go + (q >> 1) * 8, q & 1));
    } else {
        const int q = 5 * v - (v > 34 ? 3 : 0) + lane;
        if (lane < (v > 38 ? 0 : v == 34 ? 2 : 5)) mbar_arrive_cluster(mapa(go + (q >> 4) * 8, q & 15));
    }
}
__device__ __forceinline__ unsigned read_back(const uint4* d, int lane) { return ld_flag((const unsigned*)(d - lane + ((lane + 10) & 15) * 8 + 6)); }
__device__ __forceinline__ void publish(unsigned rb, unsigned mine, unsigned* flag) {
    if (__shfl_sync(~0u, rb ^ mine, 6)) asm volatile("fence.acq_rel.gpu;" ::: "memory");
    if (elect_one()) flag_add(flag);
}
#define CV_B(m, f)                                                                                                      \
    {                                                                                                                   \
        uint4 v0 = lds128(rdB + m * 512), v1 = lds128(rdB + m * 512 + 128);                                             \
        uint4 v2 = lds128(rdB + m * 512 + 256), v3 = lds128(rdB + m * 512 + 384);                                       \
        o[0].f = pack4(v0.x, v1.x, v2.x, v3.x); o[1].f = pack4(v0.y, v1.y, v2.y, v3.y);                                 \
        o[2].f = pack4(v0.z, v1.z, v2.z, v3.z); o[3].f = pack4(v0.w, v1.w, v2.w, v3.w);                                 \
    }

__device__ __forceinline__ void last_columns(Scratch* sc, const Maps& maps, const __nv_bfloat16* scale_x, const int* zero_x, const __nv_bfloat16* scale_w,
                                             const __nv_bfloat16* bias, uint32_t sb, int warp, int lane, unsigned t0) {
    constexpr int C_FULL = 0, C_EMPTY = 32, C_RAW = 64, C_GO = 80, C_PEER = 81, D3 = CFG_D3;
    const uint32_t bars = sb + SM_BAR;
    const int j = blockIdx.x & 3;
    while ((int)(t0 + CFG_T3 - clk()) > 0) ;
    const int s0 = (j & 1) * 8 + (warp >> 1) * 2;
    if (warp < 8) {
        if (elect_one()) {
#pragma unroll
            for (int i = 0; i < 2; i++) {
                const uint32_t bar = bars + (C_RAW + warp * 2 + i) * 8;
                mbar_init(bar, 1); mbar_expect_tx(bar, 8192);
                raw_load(maps.m + 1, (s0 + (i ^ (j >> 1))) * 64, N_ / 32 - 2 + (warp & 1), sb + SM_A + (warp * 2 + i) * 8192, bar);
            }
#pragma unroll
            for (int i = 0; i < 4; i++) { mbar_init(bars + (C_FULL + warp * 4 + i) * 8, 1); mbar_expect_tx(bars + (C_FULL + warp * 4 + i) * 8, 16384); }
#pragma unroll
            for (int i = 0; i < 4; i++) mbar_init(bars + (C_EMPTY + warp * 4 + i) * 8, 4);
            if (warp == 0) {
                mbar_init(bars + C_GO * 8, 8);
                mbar_init(bars + C_PEER * 8, 1); mbar_expect_tx(bars + C_PEER * 8, 32768 + 4096);
            }
        }
        if (warp < 2) sts32(sb + SM_PAR + threadIdx.x * 4, 0);
        fence_init();
    }
    __syncthreads();
    cluster_arrive();
    cluster_wait();
    if (warp >= 8) {
        asm volatile("setmaxnreg.dec.sync.aligned.u32 40;");
        if (warp < 12) {
            const unsigned ep = (ld_flag(epoch(sc, j * 4, 8)) + 1) * 4;
            const int mb = j * 4 + warp - 8, wg = (warp >> 1) & 1;
            unsigned rdy = 0;
            mbar_wait(bars + (wg ? C_EMPTY : C_GO) * 8);
#pragma unroll 1
            for (int s = 0; s < 16; s++) {
                for (int it = 0; !((rdy >> s) & 1); it++) {
                    rdy = __ballot_sync(~0u, (int)(ld_flag(sc->flag + mb * 32 + (lane & 15)) - ep) >= 0);
                    if (it > (1 << 22)) __trap();
                }
                if (s >= D3) mbar_wait(bars + (C_EMPTY + (s - (s < CFG_S3 ? D3 : CFG_D4)) * 2 + wg) * 8);
                if (elect_one()) tile_load(sc, sb + SM_A + ((s & 3) * 4 + warp - 8) * 8192, mb * 16 + s, bars + (C_FULL + s * 2 + wg) * 8);
            }
        }
    } else {
        asm volatile("setmaxnreg.inc.sync.aligned.u32 200;");
        const int wg = warp >> 2, w = warp & 3;
        const int c0 = (w >> 1) * 32 + (lane >> 2) * 4 + (w & 1) * 2, r0 = (lane & 3) * 2;
        const uint32_t sx2 = (uint32_t)__ldg((const unsigned short*)scale_x) * 0x10001u;
        uint32_t sw = __ldg((const unsigned*)(scale_w + N_ - WB + c0));
        const uint32_t bi = __ldg((const unsigned*)(bias + N_ - WB + c0));
        const float zxf = ld_zx(zero_x);
        int cs[4] = {0, 0, 0, 0};
        const uint32_t peer = mapa(sb, (j & 1) ^ 1);
#pragma unroll 1
        for (int i = 0; i < 2; i++) {
            const uint32_t rdB = sb + SM_A + (warp * 2 + i) * 8192 + (lane >> 3) * 2048 + (lane & 7) * 16;
            const uint32_t wr = SM_RING + (s0 + (i ^ (j >> 1))) * 4096 + (warp & 1) * 2048 + lane * 16;
            mbar_wait(bars + (C_RAW + warp * 2 + i) * 8);
            uint4 o[4];
            CV_B(0, x) CV_B(1, y) CV_B(2, z) CV_B(3, w)
#pragma unroll
            for (int k = 0; k < 4; k++) {
                sts128(sb + wr + k * 512, o[k]);
                asm volatile("st.async.weak.shared::cluster.mbarrier::complete_tx::bytes.v4.b32 [%0], {%1,%2,%3,%4}, [%5];"
                             :: "r"(peer + wr + k * 512), "r"(o[k].x), "r"(o[k].y), "r"(o[k].z), "r"(o[k].w), "r"(peer + SM_BAR + C_PEER * 8) : "memory");
                cs[k] = sum4(o[k].x, sum4(o[k].y, sum4(o[k].z, sum4(o[k].w, cs[k]))));
            }
        }
        __syncwarp();
        if (elect_one()) mbar_arrive(bars + C_GO * 8);
#pragma unroll
        for (int k = 0; k < 4; k++) {
            const uint32_t ca = SM_PAR + ((warp & 1) * 32 + (lane & 7) * 4 + k) * 4;
            red_shared(sb + ca, cs[k]);
            red_async(peer + ca, cs[k], peer + SM_BAR + C_PEER * 8);
        }
        mbar_wait(bars + C_PEER * 8);
        asm volatile("fence.proxy.async.shared::cta;" ::: "memory");
        asm volatile("bar.sync 1, 256;" ::: "memory");
        if (CFG_EPI) sw = bf2_mul(sw, sx2);
        const uint32_t zc = fold(zero_term(lds32(sb + SM_PAR + c0 * 4), lds32(sb + SM_PAR + c0 * 4 + 4), zxf), sw, bi);
        const uint32_t sd = (sb & 0x3FFFF) >> 4;
        int t[2][64];
        wg_fence();
#pragma unroll 1
        for (int s = 0; s < 16; s++) {
            const uint32_t db = ((sd + (SM_RING >> 4)) | (8 << 16)) + s * 256, da = ((sd + (SM_A >> 4)) | (1 << 16)) + ((s & 3) * 4 + wg * 2) * 512;
            mbar_wait(bars + (C_FULL + s * 2 + wg) * 8);
            wgmma_t128(t[0], db, da, s);
            wgmma_t128(t[1], db, da + 512, s);
            wgmma_t128(t[0], db + 16, da + 2, 1);
            wgmma_t128(t[1], db + 16, da + 514, 1);
            wg_commit();
            wg_wait<0>();
            if (elect_one()) mbar_arrive(bars + (C_EMPTY + s * 2 + wg) * 8);
        }
        asm volatile("bar.sync %0, 128;" :: "r"(3 + wg) : "memory");
        const uint32_t st0 = sb + SM_A + wg * 16384 + r0 * 128 + (((c0 >> 3) ^ r0) << 4) + (c0 & 7) * 2;
#pragma unroll
        for (int h = 0; h < 4; h++) {
            const uint32_t off = (h >> 1) * 32768 + (h & 1) * 8192;
#pragma unroll
            for (int q = 0; q < 8; q++) {
                const int o = (h & 1) * 32 + q * 4;
                sts32(st0 + off + q * 1024, epi(t[h >> 1][o], t[h >> 1][o + 2], zc, sx2, sw, bi));
                sts32((st0 ^ (5 * 128 + 5 * 16)) + off + q * 1024, epi(t[h >> 1][o + 1], t[h >> 1][o + 3], zc, sx2, sw, bi));
            }
            asm volatile("fence.proxy.async.shared::cta;" ::: "memory");
            asm volatile("bar.sync %0, 128;" :: "r"(3 + wg) : "memory");
            if (w == 0 && elect_one()) tile_store(maps.m + 2, N_ - WB, j * 512 + wg * 256 + h * 64, sb + SM_A + wg * 16384 + off);
        }
        if (w == 0) {
            asm volatile("cp.async.bulk.commit_group;" ::: "memory");
            asm volatile("cp.async.bulk.wait_group.read 0;" ::: "memory");
        }
        asm volatile("bar.sync 1, 256;" ::: "memory");
        if (threadIdx.x == 0) flag_add(epoch(sc, j * 4, 8));
    }
}

template <bool k2>
__global__ void __cluster_dims__(k2 ? 2 : CS, 1, 1) __launch_bounds__(512, 1)
w8a8_kernel(Scratch* sc, const char* __restrict__ qx, const char* __restrict__ qw, const __nv_bfloat16* __restrict__ scale_x, const int* __restrict__ zero_x,
            const __nv_bfloat16* __restrict__ scale_w, const __nv_bfloat16* __restrict__ bias, const __grid_constant__ Maps maps) {
    extern __shared__ __align__(1024) unsigned char smem_raw[];
    constexpr int NBJ = k2 ? 12 : 14, NF = NBJ, NU = k2 ? 40 : 48;
    constexpr int X1 = k2 ? CFG_X2 : CFG_X1;
    const int b = blockIdx.x + (k2 ? NCTA : 0), r = b & 15, c = k2 ? NCL : b >> 4;
    const unsigned tc = clk();
    if (!k2) {
        const int a = (r * NCL + c) ^ REV;
        const unsigned off = ((a & 63) * 32 + (threadIdx.x >> 1)) * (K_ * 4) + (a >> 6) * 256 + (threadIdx.x & 1) * 128;
        asm volatile("{\n.reg .pred p;\n.reg .b64 a;\nsetp.lt.u32 p, %2, 64;\n@!p bra PF_DONE;\ncvt.u64.u32 a, %1;\nadd.u64 a, a, %0;\nprefetch.global.L2 [a];\nPF_DONE:\n}"
                     :: "l"(qx), "r"(off), "r"(threadIdx.x));
    }
    const uint32_t sb = (uint32_t)__cvta_generic_to_shared(smem_raw);
    const uint32_t bars = sb + SM_BAR;
    const unsigned tw = __shfl_sync(~0u, (tc & ~15u) | threadIdx.x >> 5, 0), t0 = tw + (k2 ? 0 : T0);
    const int warp = tw & 15, lane = threadIdx.x & 31;

    if (!k2 && warp == 12) {
        const int a = r * NCL + c;
        if (elect_one()) {
            mbar_init(bars + (B_RAWA + 3) * 8, 1);
            mbar_expect_tx(bars + (B_RAWA + 3) * 8, 8192);
            raw_load(maps.m, (a >> 6) * 2, ((a ^ REV) & 63) * 32, sb + SM_A + (a < NAJ % NCTA ? 15 : 13) * 8192, bars + (B_RAWA + 3) * 8);
        }
        __syncwarp();
    }
    if (!k2 && (warp >> 1) == 1 && r < CFG_PG) {
        const int a = (NCTA + r * NCL + c) ^ REV;
        const char* p = qx + ((a & 63) * 32 + (warp & 1) * 16 + (lane >> 1)) * (K_ * 4) + (a >> 6) * 256 + (lane & 1) * 128;
        while ((int)(t0 + (16 + r) * P1 - clk()) > 0) ;
        asm volatile("prefetch.global.L2 [%0];" :: "l"(p));
    }
    if (warp == 9 && elect_one()) asm volatile("prefetch.tensormap [%0];" :: "l"(maps.m + 1) : "memory");
    if (k2 && blockIdx.x >= 16) {
        last_columns(sc, maps, scale_x, zero_x, scale_w, bias, sb, warp, lane, t0);
        return;
    }
    if (warp >= 12) {
        const int isw = k2 || warp == 14, t = k2 ? warp - 12 : isw ? 0 : (warp - 11) >> 1;
        const uint32_t bar = bars + ((isw ? B_RAWB : B_RAWA) + 3 + t) * 8;
        if ((k2 || warp != 12) && elect_one()) { mbar_init(bar, 1); mbar_expect_tx(bar, 8192); }
        __syncwarp();
        cluster_arrive();
        const int x = t * 16 + r, a = (x * NCL + c) ^ REV, sx = (x * 26) >> 8;
        static_assert(X1 >= 7, "");
        if ((k2 || warp != 12) && elect_one()) {
            const unsigned te = t0 + (k2 ? sched2(x) : (isw ? time_w(x) : time_x(x)) * P1);
            while ((int)(te - clk()) > 0) ;
            raw_load(maps.m + isw, isw ? sx * 64 : (a >> 6) * 2,
                     isw ? c * (TN / 32) + (int)((0x9765483210ull >> ((x - sx * 10) * 4)) & 15) : (a & 63) * 32,
                     sb + (k2 ? SM_A + 7 * 8192 : isw ? SM_STG : SM_A + 13 * 8192) + (t - (!isw && r * NCL + c < NAJ % NCTA)) * 8192, bar);
        }
        __syncwarp();
        if (!k2 && warp == 15) cluster_wait();
    }
    if (warp < 8) {
        const uint32_t p = bars + warp * 104;
        if (elect_one()) {
#pragma unroll
            for (int i = 0; i < 13; i++) mbar_init(p + i * 8, (!k2 && ((warp == 6 && i == 12) || (warp == 7 && i < 2))) ? 2 : 1);
            static_assert(B_FREE == 90 && B_GO == 104, "");
        }
        __syncwarp();
        const int i = warp * 13 + lane;
        if (lane < 13 && i < B_SW) mbar_expect_tx(p + lane * 8, i >= B_PAR ? (i < B_PAR + 2 ? WA * 2 : WB * 2) : (i & 16) || i >= 48 ? 8192 : WA * 64);
        fence_init();
    }
    if (warp < 8 || warp == 10) cluster_arrive();
    if (!k2 && warp == 10 && lane < CFG_PF7) {
        const int n = b * CFG_PF7 + lane, row = n / 10;
        asm volatile("prefetch.global.L2 [%0];" :: "l"(qw + row * (N_ * 4) + NCL * TN * 4 + (n - row * 10) * 128));
    }

    if (warp < 8) {
        asm volatile("setmaxnreg.inc.sync.aligned.u32 200;");
        const int wg = warp >> 2;
        const uint32_t sd = (sb & 0x3FFFF) >> 4;
        const uint32_t sx2 = (uint32_t)__ldg((const unsigned short*)scale_x) * 0x10001u;
        const uint32_t par = sb + SM_PAR + (lane & 3) * 16 + wg * 256;
        const uint32_t go = bars + B_GO * 8;
        const int w = warp & 3, pq = (lane >> 2) ^ (lane & 4);
        uint32_t so = (w * 16 + pq) * 128 + (((lane & 3) ^ pq) << 4);
        const int c0 = (w >> 1) * 32 + (lane >> 2) * 4 + (w & 1) * 2, r0 = (lane & 3) * 2;
        uint32_t pp = sb + SM_PAR + (2 * WA + wg * WB + c0) * 2, st0 = r0 * 128 + (((c0 >> 3) ^ r0) << 4) + (c0 & 7) * 2;
        uint32_t rq = k2 ? mapa(go + 19 * 8, 1) : mapa(go + (12 + (lane >> 4)) * 8, lane & 15);
        int rk = k2 ? (lane ? 99 : 1) : (lane >> 2) + 1;
        asm volatile("" : "+r"(so), "+r"(pp), "+r"(st0), "+r"(rq), "+r"(rk));
        cluster_wait();
        int a0[WA / 2], a1[WA / 2];
        uint32_t barB = bars + (B_FULLB + wg * 32) * 8;
        wg_fence();
        {
            uint64_t tbl = wg ? slot_table(X1, 1) : slot_table(X1, 0);
            uint32_t da = (sd + (SM_A >> 4)) | (1 << 16);
            int up = 99;
            bool rdy = false;
#pragma unroll 1
            for (int s = 0; s < 16; s++) {
                const uint32_t db = ((sd + (SM_RING >> 4)) | (8 << 16)) + ((uint32_t)tbl & 15) * (SLOT >> 4);
                const bool hold = wg && s == X1;
                if (hold || (!rdy && !mbar_test2(bars + (B_FULLA + s) * 8, barB))) {
                    wg_wait<0>();
                    release<k2>(go, up, lane); up = 99;
                    mbar_wait2(bars + (B_FULLA + s) * 8, barB);
                    if (hold) asm volatile("bar.sync 7, 256;" ::: "memory");
                }
                wgmma_n160(a0, da, db, s);
                wgmma_n160(a1, da + 256, db, s);
                wg_commit();
                if (!wg && s == 15) asm volatile("bar.arrive 7, 256;" ::: "memory");
                wg_wait<1>();
                release<k2>(go, up, lane);
                wgmma_n160(a0, da + 2, db + 16, 1);
                wgmma_n160(a1, da + 258, db + 16, 1);
                wg_commit();
                up = s < X1 ? 2 * s + wg : (wg ? 16 : X1) + s;
                tbl >>= 4; da += 512; barB += 8;
                rdy = mbar_test2(bars + (B_FULLA + s + 1) * 8, barB);
                if (s < 15) wg_wait<1>();
            }
        }
        mbar_wait2(bars + (B_PAR + wg) * 8, bars + B_SW * 8);
        Par P = ld_par(par);
        wg_wait<0>();
        release<k2>(go, wg ? 31 : X1 + 15, lane);
        bool ready = mbar_test(barB);
#define FILL_BEGIN(n0, n1) mbar_wait(bars + (B_FREE + (wg ? n1 : n0)) * 8);                                             \
                           const uint32_t buf = sb + SM_STG + (wg ? (turn<k2>(n1) + NBJ) % 3 : (turn<k2>(n0) + NBJ) % 3) * 8192;
#define FILL_END(n0, n1) __syncwarp();                                                                                  \
                         if (elect_one()) mbar_arrive(bars + (B_FILL + (wg ? turn<k2>(n1) : turn<k2>(n0))) * 8);
#define FILL_PAIR(a, J, PN, m)                                                                                          \
        {                                                                                                               \
            const uint4 v0 = epi_row(a, J * 16, P, sx2);                                                                \
            const Par Q = ld_par(par + J * 64 + 64);                                                                    \
            const uint4 v1 = epi_row(a, J * 16 + 2, P, sx2);                                                            \
            FILL_BEGIN(ford<k2>(0, m), ford<k2>(1, m))                                                                          \
            sts128(buf + so, v0); sts128(buf + so + 1024, v1);                                                          \
            if ((PN) >= 0) P = ld_par(par + (PN));                                                                      \
            sts128(buf + (so ^ 64), epi_row(a, J * 16 + 16, Q, sx2));                                                   \
            sts128(buf + (so ^ 64) + 1024, epi_row(a, J * 16 + 18, Q, sx2));                                            \
            FILL_END(ford<k2>(0, m), ford<k2>(1, m))                                                                            \
        }
#define NARROW(p)                                                                                                       \
        {                                                                                                               \
            if (!ready) mbar_wait(barB);                                                                                \
            wg_fence();                                                                                                 \
            _Pragma("unroll 1") for (int i = 0; i < 8; i++) {                                                           \
                const uint32_t db = ((sd + (SM_RING >> 4)) | (8 << 16)) + (k2 ? (i > 2 ? i - 3 : i + 4) * (SLOT >> 4) : ((i + 5) & 7) * 512); \
                _Pragma("unroll") for (int kk = 0; kk < 4; kk++)                                                        \
                    wgmma_t128(t, db + (kk >> 1) * 256 + (kk & 1) * 16,                                                 \
                               ((sd + (SM_A >> 4)) | (1 << 16)) + i * 1024 + (kk >> 1) * 512 + (kk & 1) * 2, kk ? 1 : i); \
                wg_commit();                                                                                            \
                barB += 8;                                                                                              \
                mbar_wait(i < 7 ? barB : bars + (B_PAR + p) * 8);                                                       \
                wg_wait<1>();                                                                                           \
                if (p == 2 && rk == i) mbar_arrive_cluster(rq);                                                         \
            }                                                                                                           \
            if (p == 2 && !k2) P = ld_par(par + 512);                                                                   \
            else { zc = lds32(pp); sw = lds32(pp + TN * 2); bi = CFG_EPI == 3 ? 0 : lds32(pp + TN * 4); }               \
            wg_wait<0>();                                                                                               \
            if (p == 2 && rk == 8) mbar_arrive_cluster(rq);                                                             \
        }
        FILL_PAIR(a0, 0, 128, 0) FILL_PAIR(a0, 2, 0, 1)
        int t[64];
        uint32_t zc, sw, bi;
        FILL_PAIR(a1, 0, 128, 2) FILL_PAIR(a1, 2, k2 ? 512 - wg * 192 : -1, 3)
        if (!k2) { if (wg == 0) NARROW(2) else P = ld_par(par + 320); }
        {
            const uint4 v0 = epi_row(a0, 64, P, sx2), v1 = epi_row(a0, 66, P, sx2);
            FILL_BEGIN(ford<k2>(0, 4), ford<k2>(1, 4))
            const uint32_t s4 = buf + ((so >> 1) & ~63u) + (lane & 3) * 16;
            sts128(s4, v0); sts128(s4 + 512, v1);
            sts128(s4 + 4096, epi_row(a1, 64, P, sx2)); sts128(s4 + 4608, epi_row(a1, 66, P, sx2));
            FILL_END(ford<k2>(0, 4), ford<k2>(1, 4))
        }
        if (!(k2 && wg)) {
            if (k2) NARROW(2) else if (wg) NARROW(3) else { zc = lds32(pp); sw = lds32(pp + TN * 2); bi = CFG_EPI == 3 ? 0 : lds32(pp + TN * 4); }
#define FILL_T(h)                                                                                                       \
            {                                                                                                           \
                FILL_BEGIN((10 + h), (12 + h))                                                                          \
                _Pragma("unroll") for (int j = 0; j < 8; j++) {                                                         \
                    const int o = h * 32 + j * 4;                                                                       \
                    sts32(buf + st0 + j * 1024, epi(t[o], t[o + 2], zc, sx2, sw, bi));                                  \
                    sts32(buf + (st0 ^ (5 * 128 + 5 * 16)) + j * 1024, epi(t[o + 1], t[o + 3], zc, sx2, sw, bi));       \
                }                                                                                                       \
                FILL_END((10 + h), (12 + h))                                                                            \
            }
            FILL_T(0) FILL_T(1)
        }
        if (threadIdx.x == 0) flag_add(epoch(sc, r, c));
    } else {
        const int g = r * NCL + c, na = k2 ? 0 : NAJ / NCTA + (g < NAJ % NCTA);
        int cw = NF;
        if (warp >= 12) {
            asm volatile("setmaxnreg.dec.sync.aligned.u32 80;");
            if (warp < 14) {
                const int c4 = (lane ^ (lane >> 3)) & 3, ln = ((lane >> 2) ^ (lane & 4)) * 2 + (c4 >> 1);
                const uint32_t rd0 = sb + SM_A + 13 * 8192 + ln * 128 + ((((c4 & 1) << 2) ^ (ln & 7)) << 4);
#pragma unroll 1
                for (int t = warp - 12, sl = na == 9 ? t : 2 - 2 * t; t < na; t += 2, sl = sl ? sl - 1 : 2) {
                    const uint32_t rdA = rd0 + sl * 8192;
                    const int a = (t * NCTA + g) ^ REV, f = (a & 60) * 4 + (a >> 6);
                    uint4* const d = sc->s8 + (f * 4 + (a & 3)) * 128 + lane;
                    uint4 o[4];
                    mbar_wait(bars + (B_RAWA + 3 + t) * 8);
#pragma unroll
                    for (int i = 0; i < 4; i++) {
                        uint4 v0 = lds128(rdA + i * 2048), v1 = lds128((rdA ^ 16) + i * 2048);
                        uint4 v2 = lds128((rdA ^ 32) + i * 2048), v3 = lds128((rdA ^ 48) + i * 2048);
                        o[i].x = pack4(v0.x, v0.y, v0.z, v0.w); o[i].y = pack4(v1.x, v1.y, v1.z, v1.w);
                        o[i].z = pack4(v2.x, v2.y, v2.z, v2.w); o[i].w = pack4(v3.x, v3.y, v3.z, v3.w);
                    }
#pragma unroll
                    for (int i = 0; i < 4; i++) stg128(d + i * 32, o[i]);
                    asm volatile("fence.proxy.async.global;" ::: "memory");
                    __syncwarp();
                    const unsigned rb = read_back(d, lane);
                    if (t < 2) cluster_wait();
                    if (elect_one()) mbar_arrive(bars + ((t < na - 3 ? B_RAWA : B_AFREE + 13) + sl) * 8);
                    publish(rb, o[0].x, sc->flag + (a & 60) * 8 + (a >> 6));
                }
                cw = warp - 12;
            }
            if (!k2) {
                const int hw = warp & 1;
                const uint32_t rd0 = sb + SM_STG + hw * 4096 + (lane >> 3) * 1024 + (lane & 7) * 16;
                const int myG = decode_b(X1, (lane & 15) * 16 + r).G;
#pragma unroll 1
                for (int t = warp < 14 ? TA : 0; t < NBJ; t += warp < 14 ? NBJ : t == TA - 1 ? 2 : 1) {
                    const int sl = t % 3;
                    const uint32_t rdB = rd0 + sl * 8192;
                    char* const d = (char*)sc->s8 + (1024 + c * 256 + t * 16 + r) * 2048 + hw * 256 + (lane >> 4) * 128 + (lane & 7) * 16 + (lane & 8);
                    uint2 o[4];
                    mbar_wait(bars + (B_RAWB + 3 + t) * 8);
                    CV_B(0, x) CV_B(1, y)
#pragma unroll
                    for (int i = 0; i < 4; i++) asm volatile("st.global.v2.b32 [%0], {%1,%2};" :: "l"(d + i * 512), "r"(o[i].x), "r"(o[i].y) : "memory");
                    if (t == 0 && warp == 14) cluster_wait();
                    if (elect_one()) mbar_arrive(bars + (t >= NBJ - 3 ? B_FREE + t - (NBJ - 3) : B_RAWB + sl) * 8);
                    asm volatile("fence.proxy.async.global;" ::: "memory");
                    __syncwarp();
                    if (elect_one()) mbar_arrive(bars + (B_GO + t) * 8);
                    int cs[4];
#pragma unroll
                    for (int i = 0; i < 4; i++) cs[i] = sum4(o[i].x, sum4(o[i].y, 0));
                    const int p01 = cs[0] + cs[1] * 65536, p23 = cs[2] + cs[3] * 65536;
                    const bool h = lane & 16;
                    int x = (h ? p23 : p01) + __shfl_xor_sync(~0u, h ? p01 : p23, 16);
                    x += __shfl_xor_sync(~0u, x, 8);
                    const int lo = (int)(short)x, v = (lane & 8) ? (x - lo) >> 16 : lo;
                    const int G = __shfl_sync(~0u, myG, t);
                    if (G != r) {
                        red_async(mapa(sb + SM_CS + lane * 4, G), v, mapa(bars + B_CS * 8, G));
                    } else {
                        red_shared(sb + SM_CS + lane * 4, v);
                        __syncwarp();
                        if (elect_one()) mbar_arrive(bars + B_CS * 8);
                    }
                }
            } else {
                const uint32_t rd0 = sb + (lane >> 3) * 2048 + (lane & 7) * 16;
                const BJob mb = decode_b(X1, (lane & 15) * 16 + r);
                const int myG = mb.G | mb.u << 8;
#pragma unroll 1
                for (int t = warp - 12; t < NBJ; t += 4) {
                    const uint32_t rdB = rd0 + stage_w<k2>(t);
                    uint4* const d = sc->s8 + (1024 + c * 256 + t * 16 + r) * 128 + lane;
                    uint4 o[4];
                    mbar_wait(bars + (B_RAWB + 3 + t) * 8);
                    CV_B(0, x) CV_B(1, y) CV_B(2, z) CV_B(3, w)
#pragma unroll
                    for (int i = 0; i < 4; i++) stg128(d + i * 32, o[i]);
                    if (t < 4) cluster_wait();
                    if (elect_one()) mbar_arrive(bars + (B_FREE + t - (NBJ - 3)) * 8);
                    asm volatile("fence.proxy.async.global;" ::: "memory");
                    __syncwarp();
                    const unsigned rb = read_back(d, lane), ep = ld_flag(epoch(sc, r, c));
                    int cs[4];
#pragma unroll
                    for (int i = 0; i < 4; i++) cs[i] = sum4(o[i].x, sum4(o[i].y, sum4(o[i].z, sum4(o[i].w, 0))));
                    const bool h = lane & 16, odd = lane & 8;
                    int x = (h ? cs[2] : cs[0]) + __shfl_xor_sync(~0u, h ? cs[0] : cs[2], 16);
                    int y = (h ? cs[3] : cs[1]) + __shfl_xor_sync(~0u, h ? cs[1] : cs[3], 16);
                    const int v = (odd ? y : x) + __shfl_xor_sync(~0u, odd ? x : y, 8);
                    const int gu = __shfl_sync(~0u, myG, t);
                    publish(rb, o[0].x, sc->flag + F_W + (gu >> 8));
                    const int old = atomicAdd(sc->cs[ep & 1] + col_of(gu & 255) + (lane & 7) * 4 + (lane >> 3), v);
                    if (old == 0x7FFFFFFF) sc->sink[0] = old;
                    __syncwarp();
                    if (elect_one()) flag_add(sc->flag + F_CS + (gu & 255) / 5);
                }
            }
        } else {
            asm volatile("setmaxnreg.dec.sync.aligned.u32 32;");
            if (warp == 11) {
                if (elect_one()) {
#pragma unroll
                    for (int i = 0; i < (k2 ? NU / 2 : NBJ); i++)
                        mbar_init(bars + (B_GO + i) * 8, k2 ? (i * 2 + (r & 1) >= NSLOT ? 9 : 1) : (i * 16 + r >= NSLOT * 5 ? 2 + 4 * CS : 2));
#pragma unroll
                    for (int i = 0; i < 3; i++) mbar_init(bars + (B_FILL + i) * 8, 4);
                }
                const int u2 = lane * 2 + (r & 1), q = k2 ? (u2 < 32 ? 5 * u2 : 4 * u2 + 32) : (lane & 15) * 16 + r;
                const BJob bj = decode_b(X1, q);
                unsigned seen = 0;
                if (!k2) {
                    const int nself = __popc(__ballot_sync(~0u, lane < NBJ && bj.G == r));
                    sts32(sb + SM_CS + lane * 4, 0);
                    if (lane == 0) {
                        mbar_init(bars + B_CS * 8, 1 + 2 * nself);
                        mbar_expect_tx(bars + B_CS * 8, (16 - nself) * 256);
                    }
                    seen = lds32(sb + SM_CS + lane * 4);
                }
                fence_init();
                asm volatile("barrier.cluster.arrive.relaxed.aligned;" :: "r"(seen) : "memory");
                const char* src = (const char*)sc->s8 + (1024 + c * 256 + q) * 2048;
                const uint32_t dst = sb + SM_RING + ((!k2 && q >= 160) ? ((q + 20) & 31) * 2048 : (bj.u % NSLOT) * SLOT + bj.pos * 2048);
                const uint32_t fb = bars + (B_FULLB + fb_of(X1, bj.u)) * 8;
                cluster_wait();
                if (!k2) scale_bias(scale_x, scale_w + c * TN, bias + c * TN, sb, lane);
#pragma unroll 1
                for (int i = 0; i < (k2 ? NU / 2 : NBJ); i++) {
                    mbar_wait(bars + (B_GO + i) * 8);
                    if (lane == i) {
                        asm volatile("cp.async.bulk.shared::cluster.global.mbarrier::complete_tx::bytes.multicast::cluster [%0], [%1], %2, [%3], %4;"
                                     :: "r"(dst), "l"(src), "r"(k2 ? (u2 < 32 ? SLOT : 8192) : 2048), "r"(fb), "h"((uint16_t)(k2 ? 3 : 0xFFFF)) : "memory");
                    }
                    __syncwarp();
                }
            } else if (warp == 10) {
                const unsigned ep = (__shfl_sync(~0u, ld_flag(sc->flag + r * 32 + (lane < 16 ? lane : 16 + c)), 16) + 1) * 4;
                const unsigned* f = sc->flag + r * 32 + (lane & 15);
                bool dn = lane >= 16;
                const bool fr = lane < (k2 ? 7 : 13);
                cluster_wait();
                for (int it = 0;; it++) {
                    const unsigned v = ld_flag(f);
                    if (!dn && (int)(v - ep) >= 0 && (fr || mbar_test(bars + (B_AFREE + lane) * 8))) {
                        dn = true;
                        tile_load(sc, sb + SM_A + lane * 8192, r * 16 + lane, bars + (B_FULLA + lane) * 8);
                    }
                    if (__all_sync(~0u, dn)) break;
                    if (it > (1 << 22)) __trap();
                }
            } else {
                const bool isw = warp == 9;
                const uint32_t rb = bars + (isw ? B_RAWB : B_RAWA) * 8;
                if (elect_one()) {
#pragma unroll
                    for (int i = 0; i < 13; i++) if (i < 3 || i >= (k2 ? 7 : 6)) mbar_init(rb + i * 8, (i < 3 && isw && !k2) ? 2 : 1);
                    if (isw) {
#pragma unroll
                        for (int i = 13; i < 17; i++) mbar_init(rb + i * 8, 1);
                        if (!k2) { mbar_init(rb + 4 * 8, 1); mbar_init(rb + 5 * 8, 1); }
                    }
                }
                __syncwarp();
                const int nj = isw ? NBJ : na, j0 = k2 ? 4 : isw ? 1 : 3;
                if (lane >= j0 && lane < nj) mbar_expect_tx(rb + (3 + lane) * 8, 8192);
                fence_init();
                cluster_arrive();
                const unsigned e0 = k2 ? ld_flag(epoch(sc, r, c)) : 0;
                const int k = lane / 3, x = lane * 16 + r;
                int sl = lane - k * 3, y, z, T;
                if (isw) {
                    const BJob bj = decode_b(X1, x & 255);
                    y = bj.slab * 64; z = (c * TN + col_of(bj.G)) >> 5; T = time_w(x);
                } else {
                    const int a = (lane * NCTA + g) ^ REV;
                    y = (a >> 6) * 2; z = (a & 63) * 32; T = time_x(x);
                    if (na == 10) sl = sl ? sl - 1 : 2;
                }
                const unsigned te = t0 + (k2 ? sched2(x) : sched(T));
                const uint32_t sd = sb + (isw ? stage_w<k2>(lane) : SM_A + (13 + sl) * 8192);
#pragma unroll 1
                for (int t = j0; t < nj; t++) {
                    if (lane == t) {
                        if (t >= 3 && !k2) mbar_wait(rb + sl * 8, (k & 1) ^ 1);
                        while ((int)(te - clk()) > 0) ;
                        raw_load(maps.m + isw, y, z, sd, rb + (3 + t) * 8);
                    }
                    __syncwarp();
                }
                cluster_wait();
                if (elect_one()) asm volatile("prefetch.tensormap [%0];" :: "l"(maps.m + 2 + isw) : "memory");
                if (!isw) cw = 2;
                if (k2) {
                    if (!isw) {
                        if (lane < TN / 16) sc->cs[(e0 & 1) ^ 1][r * (TN / 16) + lane] = 0;
                        const int u = lane * 2 + (r & 1);
                        const unsigned tg = (e0 + 1) * (u < 32 ? 5 : 4);
                        bool dn = u >= NU;
                        for (int it = 0;; it++) {
                            if (!dn && (int)(ld_flag(sc->flag + F_W + u) - tg) >= 0) {
                                dn = true;
                                mbar_arrive(bars + (B_GO + lane) * 8);
                            }
                            if (__all_sync(~0u, dn)) break;
                            if (it > (1 << 22)) __trap();
                        }
                    } else {
                        const float zxf = ld_zx(zero_x);
                        scale_bias(scale_x, scale_w + c * TN, bias + c * TN, sb, lane);
#pragma unroll 1
                        for (int h = 0; h < 3; h++) {
                            for (int it = 0; (int)(ld_flag(sc->flag + F_CS + h) - (e0 + 1) * (h < 2 ? 80 : 32)) < 0; it++) if (it > (1 << 22)) __trap();
                            int2 v[3];
                            int i[3];
#pragma unroll
                            for (int j = 0; j < 3; j++) {
                                i[j] = (j < 2 ? h * 64 + j * 32 : 128 + h * 16) + lane;
                                v[j] = __ldcg((const int2*)sc->cs[e0 & 1] + i[j]);
                            }
#pragma unroll
                            for (int j = 0; j < 3; j++) {
                                const uint32_t pa = sb + SM_PAR + i[j] * 4;
                                const uint32_t z = fold(zero_term(v[j].x, v[j].y, zxf), lds32(pa + TN * 2), lds32(pa + TN * 4));
                                if (h < 2 ? (j < 2 || lane < 16) : j == 2) st_async(pa, z, bars + (B_PAR + h) * 8);
                            }
                        }
                    }
                }
            }
        }
        if (!k2 && r < NBJ && warp == (r < 10 ? 8 : 10)) {
            const float zxf = ld_zx(zero_x);
            const int w = lane & 15;
            uint32_t sw = 0, bi = 0;
            if (CFG_EPI == 3) { mbar_wait(bars + B_SW * 8); sw = lds32(sb + SM_PAR + TN * 2 + col_of(r) * 2 + w * 4); bi = lds32(sb + SM_PAR + TN * 4 + col_of(r) * 2 + w * 4); }
            mbar_wait(bars + B_CS * 8);
            const uint32_t ca = sb + SM_CS + ((w >> 1) + (w & 1) * 16) * 4;
            const uint32_t z = fold(zero_term(lds32(ca), lds32(ca + 32), zxf), sw, bi);
            const int piece = r < 10 ? (r >= 5) : (r - 6) >> 1;
#pragma unroll 1
            for (int i = lane >> 4; i < CS; i += 2) st_async(mapa(sb + SM_PAR + col_of(r) * 2 + w * 4, i), z, mapa(bars + (B_PAR + piece) * 8, i));
        }
#pragma unroll 1
        for (int n = cw, nn, k = 0; n < NF; n = nn, k ^= 1) {
            nn = n + 3;
            if (!k2 && n < 5 && nn >= 5) nn += nn == 5 ? 2 : -1;
            const int gm = (int)(ford_table<k2>() >> (4 * n)), g = (gm >> 3) & 1, m = gm & 7;
            const int x = n >= 10 ? (n >> 1) * 64 : m == 4 ? 256 + g * 32 : g * 128 + (m & 1) * 64;
            const int y = n >= 10 ? (n & 1) * 64 : (m & 2) * 32;
            mbar_wait(bars + (B_FILL + cw) * 8, k);
            asm volatile("fence.proxy.async.shared::cta;" ::: "memory");
            if (elect_one()) tile_store(maps.m + (n < 10 && m == 4 ? 3 : 2), c * TN + x, r * 128 + y, sb + SM_STG + ((cw + NBJ) % 3) * 8192);
            asm volatile("cp.async.bulk.commit_group;" ::: "memory");
            asm volatile("cp.async.bulk.wait_group.read 0;" ::: "memory");
            __syncwarp();
            if (nn < NF && elect_one()) mbar_arrive(bars + (B_FREE + nn) * 8);
        }
    }
}

__global__ void __launch_bounds__(256)
w8a8_plain(const int* __restrict__ qx, const int* __restrict__ qw, const __nv_bfloat16* __restrict__ scale_x, const int* __restrict__ zero_x,
           const __nv_bfloat16* __restrict__ scale_w, const __nv_bfloat16* __restrict__ bias, __nv_bfloat16* __restrict__ out) {
    __shared__ int xs[16][K_ / 4];
    const int n = (blockIdx.x * 256 + threadIdx.x) * 2, m0 = blockIdx.y * 16;
    for (int i = threadIdx.x; i < 16 * K_ / 4; i += 256) {
        const uint4 v = ((const uint4*)qx)[m0 * (K_ / 4) + i];
        xs[i / (K_ / 4)][i % (K_ / 4)] = pack4(v.x, v.y, v.z, v.w);
    }
    __syncthreads();
    int acc[16][2] = {}, cs[2] = {};
    for (int k = 0; k < K_ / 4; k++) {
        uint2 v[4];
#pragma unroll
        for (int i = 0; i < 4; i++) v[i] = *(const uint2*)(qw + (k * 4 + i) * N_ + n);
        const unsigned w0 = pack4(v[0].x, v[1].x, v[2].x, v[3].x), w1 = pack4(v[0].y, v[1].y, v[2].y, v[3].y);
        cs[0] = sum4(w0, cs[0]); cs[1] = sum4(w1, cs[1]);
#pragma unroll
        for (int i = 0; i < 16; i++) { acc[i][0] = __dp4a(xs[i][k], (int)w0, acc[i][0]); acc[i][1] = __dp4a(xs[i][k], (int)w1, acc[i][1]); }
    }
    const uint32_t sx2 = (uint32_t)*(const unsigned short*)scale_x * 0x10001u, bi = *(const unsigned*)(bias + n);
    uint32_t sw = *(const unsigned*)(scale_w + n);
    if (CFG_EPI) sw = bf2_mul(sw, sx2);
    const uint32_t zc = fold(zero_term(cs[0], cs[1], ld_zx(zero_x)), sw, bi);
#pragma unroll
    for (int i = 0; i < 16; i++) *(unsigned*)(out + (m0 + i) * N_ + n) = epi(acc[i][0], acc[i][1], zc, sx2, sw, bi);
}

}

typedef CUresult (*EncodeFn)(CUtensorMap*, CUtensorMapDataType, cuuint32_t, void*, const cuuint64_t*, const cuuint64_t*,
                             const cuuint32_t*, const cuuint32_t*, CUtensorMapInterleave, CUtensorMapSwizzle,
                             CUtensorMapL2promotion, CUtensorMapFloatOOBfill);

extern "C" void kernel_launch(void* const* d_in, const int* in_sizes, int n_in, void* d_out, int out_size) {
    using namespace w8;
    static EncodeFn encode = nullptr;
    static cudaStream_t side;
    static cudaEvent_t started, joined;
    static int clusters = -1;
    static Scratch* sc;
    cudaLaunchConfig_t cfg = {};
    cfg.gridDim = dim3(NCTA); cfg.blockDim = dim3(512); cfg.dynamicSmemBytes = SM_TOTAL; cfg.stream = cudaStreamPerThread;
    if (clusters < 0) {
        void* fn = nullptr;
        cudaDriverEntryPointQueryResult qr;
        cudaGetDriverEntryPoint("cuTensorMapEncodeTiled", &fn, cudaEnableDefault, &qr);
        encode = (EncodeFn)fn;
        cudaGetSymbolAddress((void**)&sc, g_scratch);
        cudaStreamCreateWithFlags(&side, cudaStreamNonBlocking);
        cudaEventCreateWithFlags(&started, cudaEventDisableTiming);
        cudaEventCreateWithFlags(&joined, cudaEventDisableTiming);
        cudaFuncSetAttribute(w8a8_kernel<false>, cudaFuncAttributeMaxDynamicSharedMemorySize, SM_TOTAL);
        cudaFuncSetAttribute(w8a8_kernel<true>, cudaFuncAttributeMaxDynamicSharedMemorySize, SM_TOTAL);
        cudaFuncSetAttribute(w8a8_kernel<false>, cudaFuncAttributeNonPortableClusterSizeAllowed, 1);
        if (cudaOccupancyMaxActiveClusters(&clusters, w8a8_kernel<false>, &cfg) != cudaSuccess) { clusters = 0; cudaGetLastError(); }
    }
    const __nv_bfloat16 *sx = (const __nv_bfloat16*)d_in[2], *sw = (const __nv_bfloat16*)d_in[4], *bias = (const __nv_bfloat16*)d_in[5];
    const int* zx = (const int*)d_in[3];
    if (clusters < NCL) {
        w8a8_plain<<<dim3(N_ / 512, M_ / 16), 256, 0, cudaStreamPerThread>>>((const int*)d_in[0], (const int*)d_in[1], sx, zx, sw, bias, (__nv_bfloat16*)d_out);
        return;
    }
    Maps maps;
    const cuuint32_t es[3] = {1, 1, 1};
    {
        const cuuint64_t dim[3] = {32, K_ / 32, M_}, str[2] = {128, K_ * 4};
        const cuuint32_t box[3] = {32, 2, 32};
        encode(&maps.m[0], CU_TENSOR_MAP_DATA_TYPE_INT32, 3, d_in[0], dim, str, box, es, CU_TENSOR_MAP_INTERLEAVE_NONE,
               CU_TENSOR_MAP_SWIZZLE_128B, CU_TENSOR_MAP_L2_PROMOTION_NONE, CU_TENSOR_MAP_FLOAT_OOB_FILL_NONE);
    }
    {
        const cuuint64_t dim[3] = {32, K_, N_ / 32}, str[2] = {N_ * 4, 128};
        const cuuint32_t box[3] = {32, 64, 1};
        encode(&maps.m[1], CU_TENSOR_MAP_DATA_TYPE_INT32, 3, d_in[1], dim, str, box, es, CU_TENSOR_MAP_INTERLEAVE_NONE,
               CU_TENSOR_MAP_SWIZZLE_NONE, CU_TENSOR_MAP_L2_PROMOTION_NONE, CU_TENSOR_MAP_FLOAT_OOB_FILL_NONE);
    }
    for (int i = 0; i < 2; i++) {
        const cuuint64_t dim[2] = {N_, M_}, str[1] = {N_ * 2};
        const cuuint32_t box[2] = {i ? 32u : 64u, i ? 128u : 64u};
        encode(&maps.m[2 + i], CU_TENSOR_MAP_DATA_TYPE_BFLOAT16, 2, d_out, dim, str, box, es, CU_TENSOR_MAP_INTERLEAVE_NONE,
               i ? CU_TENSOR_MAP_SWIZZLE_NONE : CU_TENSOR_MAP_SWIZZLE_128B, CU_TENSOR_MAP_L2_PROMOTION_NONE, CU_TENSOR_MAP_FLOAT_OOB_FILL_NONE);
    }
    cudaLaunchAttribute at;
    at.id = cudaLaunchAttributeProgrammaticEvent;
    at.val.programmaticEvent.event = started; at.val.programmaticEvent.flags = 0; at.val.programmaticEvent.triggerAtBlockStart = 1;
    cfg.attrs = &at; cfg.numAttrs = 1;
    cudaLaunchKernelEx(&cfg, w8a8_kernel<false>, sc, (const char*)d_in[0], (const char*)d_in[1], sx, zx, sw, bias, maps);
    cudaStreamWaitEvent(side, started, 0);
    cfg.gridDim = dim3(20); cfg.stream = side; cfg.numAttrs = 0;
    cudaLaunchKernelEx(&cfg, w8a8_kernel<true>, sc, (const char*)d_in[0], (const char*)d_in[1], sx, zx, sw, bias, maps);
    cudaEventRecord(joined, side);
    cudaStreamWaitEvent(cudaStreamPerThread, joined, 0);
}
```

```cpp
#include <cuda_runtime.h>
#include <cuda.h>
#include <cuda_bf16.h>
#include <stdint.h>
#include <stddef.h>

#define CFG_X1 13
#define CFG_P1 46
#define CFG_P2 39
#define CFG_PT 100
#define CFG_L0 34
#define CFG_RA 33
#define CFG_T0 -550
#define CFG_Q0 14
#define CFG_Q2 69
#define CFG_Q3 30
#define CFG_T3 400
#define CFG_D3 2
#define CFG_PF7 18
#define CFG_TA 10
#define CFG_EPI 3
#define CFG_X2 11
#define CFG_S3 12
#define CFG_D4 4
#define CFG_PG 8

namespace w8 {

constexpr int M_ = 2048, K_ = 1024, N_ = 3584;
constexpr int CS = 16, NCL = 7, NCTA = CS * NCL;
constexpr int WA = 160, WB = 64, TN = 2 * WA + 2 * WB;
constexpr int NSLOT = 7, SLOT = WA * 64;
constexpr int NAJ = 1024;
constexpr int REV = 60;
constexpr int TA = CFG_TA;

constexpr int L0 = CFG_L0, RA = CFG_RA, RB64 = 64 * RA / (RA - 16);
constexpr int P1 = CFG_P1, P2 = CFG_P2, PT = CFG_PT, T0 = CFG_T0;
__device__ __forceinline__ int time_x(int x) { return max(x, L0 + (((x - L0) * RA) >> 4)); }
__device__ __forceinline__ int time_w(int q) { return min(L0 + ((q * RB64) >> 6), NAJ / NCL + q); }
__device__ __forceinline__ unsigned sched(int T) { return T * P2 + min(T, PT) * (P1 - P2); }
__device__ __forceinline__ int sched2(int q) { return (min(q, 160) - CFG_Q0) * CFG_Q2 + max(q - 160, 0) * CFG_Q3; }

constexpr int SM_A = 0;
constexpr int SM_RING = 131072;
constexpr int SM_STG = SM_RING + NSLOT * SLOT;
constexpr int SM_PAR = SM_STG + 3 * 8192;
constexpr int SM_CS = SM_PAR + 3 * TN * 2;
constexpr int SM_BAR = SM_CS + 128;
constexpr int B_FULLB = 0, B_FULLA = 56, B_PAR = 72, B_SW = 77, B_AFREE = 74  , B_FREE = 90,
              B_GO = 104, B_FILL = 128, B_CS = 131, B_RAWA = 132, B_RAWB = 145, B_END = 163;
constexpr int SM_TOTAL = SM_BAR + B_END * 8;
static_assert(SM_TOTAL <= 232448, "");

constexpr int F_W = 512, F_CS = 576;
struct Scratch {
    unsigned flag[768];
    int cs[2][TN];
    int sink[384];
    uint4 s8[(1024 + 8 * 256) * 128];
};
static_assert(offsetof(Scratch, s8) == 8192, "");
__device__ __align__(8192) Scratch g_scratch;
__device__ __forceinline__ unsigned* epoch(Scratch* sc, int r, int c) { return sc->flag + r * 32 + 16 + c; }

__device__ __forceinline__ void mbar_init(uint32_t bar, uint32_t cnt) {
    asm volatile("mbarrier.init.shared::cta.b64 [%0], %1;" :: "r"(bar), "r"(cnt) : "memory");
}
__device__ __forceinline__ void mbar_expect_tx(uint32_t bar, uint32_t bytes) {
    asm volatile("mbarrier.arrive.expect_tx.shared::cta.b64 _, [%0], %1;" :: "r"(bar), "r"(bytes) : "memory");
}
__device__ __forceinline__ void mbar_arrive(uint32_t bar) {
    asm volatile("mbarrier.arrive.shared::cta.b64 _, [%0];" :: "r"(bar) : "memory");
}
__device__ __forceinline__ void mbar_arrive_cluster(uint32_t bar) {
    asm volatile("mbarrier.arrive.shared::cluster.b64 _, [%0];" :: "r"(bar) : "memory");
}
__device__ __forceinline__ void mbar_wait(uint32_t bar, uint32_t parity = 0) {
    asm volatile("{\n.reg .pred p;\n.reg .u32 c;\n"
                 "mbarrier.try_wait.parity.shared::cta.b64 p, [%0], %1;\n"
                 "@p bra WAIT_DONE;\n"
                 "mov.u32 c, 0;\n"
                 "WAIT_LOOP:\n"
                 "mbarrier.try_wait.parity.shared::cta.b64 p, [%0], %1;\n"
                 "@p bra WAIT_DONE;\n"
                 "add.u32 c, c, 1;\nsetp.lt.u32 p, c, 0x100000;\n"
                 "@p bra WAIT_LOOP;\n"
                 "trap;\n"
                 "WAIT_DONE:\n}" :: "r"(bar), "r"(parity) : "memory");
}
__device__ __forceinline__ void mbar_wait2(uint32_t bar0, uint32_t bar1) {
    asm volatile("{\n.reg .pred p, q;\n.reg .u32 c;\nmov.u32 c, 0;\n"
                 "WAIT_LOOP:\n"
                 "mbarrier.try_wait.parity.shared::cta.b64 p, [%0], 0;\n"
                 "mbarrier.try_wait.parity.shared::cta.b64 q, [%1], 0;\n"
                 "and.pred p, p, q;\n"
                 "@p bra WAIT_DONE;\n"
                 "add.u32 c, c, 1;\nsetp.lt.u32 p, c, 0x100000;\n"
                 "@p bra WAIT_LOOP;\n"
                 "trap;\n"
                 "WAIT_DONE:\n}" :: "r"(bar0), "r"(bar1) : "memory");
}
__device__ __forceinline__ bool mbar_test(uint32_t bar) {
    uint32_t ok;
    asm volatile("{\n.reg .pred p;\nmbarrier.test_wait.parity.shared::cta.b64 p, [%1], 0;\nselp.u32 %0, 1, 0, p;\n}" : "=r"(ok) : "r"(bar) : "memory");
    return ok;
}
__device__ __forceinline__ bool mbar_test2(uint32_t bar0, uint32_t bar1) {
    uint32_t ok;
    asm volatile("{\n.reg .pred p, q;\nmbarrier.test_wait.parity.shared::cta.b64 p, [%1], 0;\n"
                 "mbarrier.test_wait.parity.shared::cta.b64 q, [%2], 0;\nand.pred p, p, q;\nselp.u32 %0, 1, 0, p;\n}"
                 : "=r"(ok) : "r"(bar0), "r"(bar1) : "memory");
    return ok;
}
__device__ __forceinline__ bool elect_one() {
    uint32_t ok;
    asm volatile("{\n.reg .pred p;\nelect.sync _|p, 0xffffffff;\nselp.u32 %0, 1, 0, p;\n}" : "=r"(ok));
    return ok;
}
__device__ __forceinline__ unsigned ld_flag(const unsigned* p) {
    unsigned v;
    asm volatile("ld.relaxed.gpu.global.u32 %0, [%1];" : "=r"(v) : "l"(p) : "memory");
    return v;
}
__device__ __forceinline__ uint4 lds128(uint32_t a) {
    uint4 v;
    asm volatile("ld.shared.v4.b32 {%0,%1,%2,%3}, [%4];" : "=r"(v.x), "=r"(v.y), "=r"(v.z), "=r"(v.w) : "r"(a) : "memory");
    return v;
}
__device__ __forceinline__ void sts128(uint32_t a, uint4 v) {
    asm volatile("st.shared.v4.b32 [%0], {%1,%2,%3,%4};" :: "r"(a), "r"(v.x), "r"(v.y), "r"(v.z), "r"(v.w) : "memory");
}
__device__ __forceinline__ uint32_t lds32(uint32_t a) {
    uint32_t v;
    asm volatile("ld.shared.b32 %0, [%1];" : "=r"(v) : "r"(a) : "memory");
    return v;
}
__device__ __forceinline__ void sts32(uint32_t a, uint32_t v) {
    asm volatile("st.shared.b32 [%0], %1;" :: "r"(a), "r"(v) : "memory");
}
__device__ __forceinline__ void stg128(void* p, uint4 v) {
    asm volatile("st.global.v4.b32 [%0], {%1,%2,%3,%4};" :: "l"(p), "r"(v.x), "r"(v.y), "r"(v.z), "r"(v.w) : "memory");
}
__device__ __forceinline__ unsigned pack4(unsigned a, unsigned b, unsigned c, unsigned d) {
    unsigned lo, r;
    asm("cvt.pack.sat.s8.s32.b32 %0, %1, %2, 0;" : "=r"(lo) : "r"(d), "r"(c));
    asm("cvt.pack.sat.s8.s32.b32 %0, %1, %2, %3;" : "=r"(r) : "r"(b), "r"(a), "r"(lo));
    return r;
}
__device__ __forceinline__ uint32_t mapa(uint32_t a, uint32_t r) {
    uint32_t o;
    asm("mapa.shared::cluster.u32 %0, %1, %2;" : "=r"(o) : "r"(a), "r"(r));
    return o;
}
__device__ __forceinline__ unsigned clk() {
    unsigned t;
    asm volatile("mov.u32 %0, %clock;" : "=r"(t));
    return t;
}
__device__ __forceinline__ void cluster_arrive() { asm volatile("barrier.cluster.arrive.relaxed.aligned;" ::: "memory"); }
__device__ __forceinline__ void cluster_wait() { asm volatile("barrier.cluster.wait.aligned;" ::: "memory"); }
__device__ __forceinline__ void fence_init() { asm volatile("fence.mbarrier_init.release.cluster;" ::: "memory"); }
__device__ __forceinline__ void flag_add(unsigned* p) { asm volatile("red.relaxed.gpu.global.add.u32 [%0], 1;" :: "l"(p) : "memory"); }
__device__ __forceinline__ void raw_load(const void* map, int y, int z, uint32_t dst, uint32_t bar) {
    asm volatile("cp.async.bulk.tensor.3d.shared::cluster.global.tile.mbarrier::complete_tx::bytes [%0], [%1, {0, %2, %3}], [%4];"
                 :: "r"(dst), "l"(map), "r"(y), "r"(z), "r"(bar) : "memory");
}
__device__ __forceinline__ void tile_load(Scratch* sc, uint32_t dst, int tile, uint32_t bar) {
    asm volatile("cp.async.bulk.shared::cluster.global.mbarrier::complete_tx::bytes [%0], [%1], %2, [%3];"
                 :: "r"(dst), "l"((const char*)sc->s8 + tile * 8192), "r"(8192), "r"(bar) : "memory");
}
__device__ __forceinline__ void tile_store(const void* map, int x, int y, uint32_t src) {
    asm volatile("cp.async.bulk.tensor.2d.global.shared::cta.tile.bulk_group [%0, {%1, %2}], [%3];"
                 :: "l"(map), "r"(x), "r"(y), "r"(src) : "memory");
}
__device__ __forceinline__ void st_async(uint32_t a, uint32_t v, uint32_t bar) {
    asm volatile("st.async.weak.shared::cluster.mbarrier::complete_tx::bytes.b32 [%0], %1, [%2];" :: "r"(a), "r"(v), "r"(bar) : "memory");
}
__device__ __forceinline__ void red_async(uint32_t a, int v, uint32_t bar) {
    asm volatile("red.async.relaxed.cluster.shared::cluster.mbarrier::complete_tx::bytes.add.s32 [%0], %1, [%2];" :: "r"(a), "r"(v), "r"(bar) : "memory");
}
__device__ __forceinline__ void red_shared(uint32_t a, int v) { asm volatile("red.shared.add.s32 [%0], %1;" :: "r"(a), "r"(v) : "memory"); }
__device__ __forceinline__ int sum4(unsigned v, int c) { return __dp4a((int)v, 0x01010101, c); }

constexpr uint32_t DESC_A_HI = 0x80000000u | (512 >> 4);
constexpr uint32_t DESC_B_HI = 512 >> 4;
template <int NR> __device__ __forceinline__ void wgmma_n160(int (&d)[NR], uint32_t alo, uint32_t blo, int scale_d) {
    asm volatile("{\n.reg .pred p;\n.reg .b64 da, db;\nsetp.ne.b32 p, %82, 0;\n"
        "mov.b64 da, {%80, %83};\nmov.b64 db, {%81, %84};\n"
        "wgmma.mma_async.sync.aligned.m64n160k32.s32.s8.s8 "
        "{%0, %1, %2, %3, %4, %5, %6, %7, %8, %9, %10, %11, %12, %13, %14, %15, "
        "%16, %17, %18, %19, %20, %21, %22, %23, %24, %25, %26, %27, %28, %29, %30, %31, "
        "%32, %33, %34, %35, %36, %37, %38, %39, %40, %41, %42, %43, %44, %45, %46, %47, "
        "%48, %49, %50, %51, %52, %53, %54, %55, %56, %57, %58, %59, %60, %61, %62, %63, "
        "%64, %65, %66, %67, %68, %69, %70, %71, %72, %73, %74, %75, %76, %77, %78, %79}, "
        "da, db, p;\n}\n"
        : "+r"(d[0]), "+r"(d[1]), "+r"(d[2]), "+r"(d[3]), "+r"(d[4]), "+r"(d[5]), "+r"(d[6]), "+r"(d[7]),
          "+r"(d[8]), "+r"(d[9]), "+r"(d[10]), "+r"(d[11]), "+r"(d[12]), "+r"(d[13]), "+r"(d[14]), "+r"(d[15]),
          "+r"(d[16]), "+r"(d[17]), "+r"(d[18]), "+r"(d[19]), "+r"(d[20]), "+r"(d[21]), "+r"(d[22]), "+r"(d[23]),
          "+r"(d[24]), "+r"(d[25]), "+r"(d[26]), "+r"(d[27]), "+r"(d[28]), "+r"(d[29]), "+r"(d[30]), "+r"(d[31]),
          "+r"(d[32]), "+r"(d[33]), "+r"(d[34]), "+r"(d[35]), "+r"(d[36]), "+r"(d[37]), "+r"(d[38]), "+r"(d[39]),
          "+r"(d[40]), "+r"(d[41]), "+r"(d[42]), "+r"(d[43]), "+r"(d[44]), "+r"(d[45]), "+r"(d[46]), "+r"(d[47]),
          "+r"(d[48]), "+r"(d[49]), "+r"(d[50]), "+r"(d[51]), "+r"(d[52]), "+r"(d[53]), "+r"(d[54]), "+r"(d[55]),
          "+r"(d[56]), "+r"(d[57]), "+r"(d[58]), "+r"(d[59]), "+r"(d[60]), "+r"(d[61]), "+r"(d[62]), "+r"(d[63]),
          "+r"(d[64]), "+r"(d[65]), "+r"(d[66]), "+r"(d[67]), "+r"(d[68]), "+r"(d[69]), "+r"(d[70]), "+r"(d[71]),
          "+r"(d[72]), "+r"(d[73]), "+r"(d[74]), "+r"(d[75]), "+r"(d[76]), "+r"(d[77]), "+r"(d[78]), "+r"(d[79])
        : "r"(alo), "r"(blo), "r"(scale_d), "r"(DESC_A_HI), "r"(DESC_B_HI));
}
template <int NR> __device__ __forceinline__ void wgmma_t128(int (&d)[NR], uint32_t alo, uint32_t blo, int scale_d) {
    asm volatile("{\n.reg .pred p;\n.reg .b64 da, db;\nsetp.ne.b32 p, %66, 0;\n"
        "mov.b64 da, {%64, %67};\nmov.b64 db, {%65, %68};\n"
        "wgmma.mma_async.sync.aligned.m64n128k32.s32.s8.s8 "
        "{%0, %1, %2, %3, %4, %5, %6, %7, %8, %9, %10, %11, %12, %13, %14, %15, "
        "%16, %17, %18, %19, %20, %21, %22, %23, %24, %25, %26, %27, %28, %29, %30, %31, "
        "%32, %33, %34, %35, %36, %37, %38, %39, %40, %41, %42, %43, %44, %45, %46, %47, "
        "%48, %49, %50, %51, %52, %53, %54, %55, %56, %57, %58, %59, %60, %61, %62, %63}, "
        "da, db, p;\n}\n"
        : "+r"(d[0]), "+r"(d[1]), "+r"(d[2]), "+r"(d[3]), "+r"(d[4]), "+r"(d[5]), "+r"(d[6]), "+r"(d[7]),
          "+r"(d[8]), "+r"(d[9]), "+r"(d[10]), "+r"(d[11]), "+r"(d[12]), "+r"(d[13]), "+r"(d[14]), "+r"(d[15]),
          "+r"(d[16]), "+r"(d[17]), "+r"(d[18]), "+r"(d[19]), "+r"(d[20]), "+r"(d[21]), "+r"(d[22]), "+r"(d[23]),
          "+r"(d[24]), "+r"(d[25]), "+r"(d[26]), "+r"(d[27]), "+r"(d[28]), "+r"(d[29]), "+r"(d[30]), "+r"(d[31]),
          "+r"(d[32]), "+r"(d[33]), "+r"(d[34]), "+r"(d[35]), "+r"(d[36]), "+r"(d[37]), "+r"(d[38]), "+r"(d[39]),
          "+r"(d[40]), "+r"(d[41]), "+r"(d[42]), "+r"(d[43]), "+r"(d[44]), "+r"(d[45]), "+r"(d[46]), "+r"(d[47]),
          "+r"(d[48]), "+r"(d[49]), "+r"(d[50]), "+r"(d[51]), "+r"(d[52]), "+r"(d[53]), "+r"(d[54]), "+r"(d[55]),
          "+r"(d[56]), "+r"(d[57]), "+r"(d[58]), "+r"(d[59]), "+r"(d[60]), "+r"(d[61]), "+r"(d[62]), "+r"(d[63])
        : "r"(alo), "r"(blo), "r"(scale_d), "r"(DESC_B_HI), "r"(DESC_A_HI));
}


__device__ __forceinline__ void wg_fence() { asm volatile("wgmma.fence.sync.aligned;" ::: "memory"); }
__device__ __forceinline__ void wg_commit() { asm volatile("wgmma.commit_group.sync.aligned;" ::: "memory"); }
template <int N> __device__ __forceinline__ void wg_wait() { asm volatile("wgmma.wait_group.sync.aligned %0;" :: "n"(N) : "memory"); }

__host__ __device__ constexpr int unit_of(int X1, int piece, int slab) {
    return piece < 2 ? (slab < X1 ? 2 * slab + piece : (piece ? 16 : X1) + slab) : 32 + (piece - 2) * 8 + (slab >> 1);
}
__host__ __device__ constexpr int col_of(int G) { return G == 4 ? 256 : (G > 4 && G < 9) ? 32 * G - 32 : 32 * G; }
struct BJob { int u, slab, G, pos; };
__host__ __device__ constexpr BJob decode_b(int X1, int q) {
    BJob j = {};
    if (q < 160) {
        j.u = q / 5; j.pos = q - j.u * 5;
        const int piece = j.u < 2 * X1 ? (j.u & 1) : (j.u >= X1 + 16);
        j.slab = j.u < 2 * X1 ? (j.u >> 1) : j.u - (piece ? 16 : X1);
        j.G = piece * 5 + j.pos;
    } else {
        q -= 160;
        j.u = 32 + (q >> 2); j.pos = q & 3;
        j.slab = (q >> 1) & 15;
        j.G = 10 + (q >> 5) * 2 + (q & 1);
    }
    return j;
}
__host__ __device__ constexpr int fb_of(int X1, int u) {
    return u < 2 * X1 ? (u & 1) * 32 + (u >> 1) : u < X1 + 16 ? u - X1 : u < 32 ? 16 + u : u < 40 ? u - 16 : u < 48 ? u + 8 : u - 24;
}
__host__ __device__ constexpr uint64_t slot_table(int X1, int piece) {
    uint64_t t = 0;
    for (int s = 0; s < 16; s++) t |= (uint64_t)(unit_of(X1, piece, s) % NSLOT) << (4 * s);
    return t;
}
template <bool k2> __device__ __forceinline__ int stage_w(int t) { return (k2 && t < 9) ? SM_A + (7 + t) * 8192 : SM_STG + (t % 3) * 8192; }
template <bool k2> __host__ __device__ constexpr int ford(int g, int m) {
    return k2 ? g * 5 + m : g ? (m ? 4 + m : 2) : (m < 2 ? m : m < 4 ? m + 1 : 9);
}
template <bool k2> __host__ __device__ constexpr int turn(int n) { return (n + (!k2 && n >= 5)) % 3; }
template <bool k2> __host__ __device__ constexpr uint64_t ford_table() {
    uint64_t t = 0;
    for (int g = 0; g < 2; g++) for (int m = 0; m < 5; m++) t |= (uint64_t)(g * 8 + m) << (4 * ford<k2>(g, m));
    return t;
}
struct Maps { CUtensorMap m[4]; };

__device__ __forceinline__ uint32_t bf2_mul(uint32_t a, uint32_t b) { asm("mul.rn.bf16x2 %0, %0, %1;" : "+r"(a) : "r"(b)); return a; }
__device__ __forceinline__ uint32_t epi(int a, int b, uint32_t zc, uint32_t sx, uint32_t sw, uint32_t bi) {
    uint32_t v;
    float fa = __int2float_rn(a), fb = __int2float_rn(b);
    asm("cvt.rn.bf16x2.f32 %0, %1, %2;" : "=r"(v) : "f"(fb), "f"(fa));
    if (CFG_EPI == 3) {
        asm("fma.rn.bf16x2 %0, %0, %1, %2;" : "+r"(v) : "r"(sw), "r"(zc));
        return v;
    }
    asm("sub.rn.bf16x2 %0, %0, %1;" : "+r"(v) : "r"(zc));
    if (CFG_EPI == 0) {
        v = bf2_mul(bf2_mul(v, sx), sw);
        asm("add.rn.bf16x2 %0, %0, %1;" : "+r"(v) : "r"(bi));
    } else {
        asm("fma.rn.bf16x2 %0, %0, %1, %2;" : "+r"(v) : "r"(sw), "r"(bi));
    }
    return v;
}
__device__ __forceinline__ uint32_t zero_term(int lo, int hi, float zx) {
    uint32_t z;
    asm("cvt.rn.bf16x2.f32 %0, %1, %2;" : "=r"(z) : "f"(__bfloat162float(__float2bfloat16_rn((float)hi)) * zx),
                                                    "f"(__bfloat162float(__float2bfloat16_rn((float)lo)) * zx));
    return z;
}
__device__ __forceinline__ uint32_t fold(uint32_t z, uint32_t sw, uint32_t bi) {
    if (CFG_EPI == 3) asm("fma.rn.bf16x2 %0, %1, %2, %3;" : "=r"(z) : "r"(z ^ 0x80008000u), "r"(sw), "r"(bi));
    return z;
}
__device__ __forceinline__ float ld_zx(const int* zero_x) { return __bfloat162float(__float2bfloat16_rn((float)__ldg(zero_x))); }
struct Par { uint4 zc, sw, bi; };
__device__ __forceinline__ Par ld_par(uint32_t p) { return {lds128(p), lds128(p + TN * 2), CFG_EPI == 3 ? uint4{} : lds128(p + TN * 4)}; }
__device__ __forceinline__ uint4 epi_row(const int (&a)[WA / 2], int o, const Par& p, uint32_t sx2) {
    uint4 r;
    r.x = epi(a[o + 0], a[o + 4], p.zc.x, sx2, p.sw.x, p.bi.x);
    r.y = epi(a[o + 8], a[o + 12], p.zc.y, sx2, p.sw.y, p.bi.y);
    r.z = epi(a[o + 1], a[o + 5], p.zc.z, sx2, p.sw.z, p.bi.z);
    r.w = epi(a[o + 9], a[o + 13], p.zc.w, sx2, p.sw.w, p.bi.w);
    return r;
}
__device__ __forceinline__ void scale_bias(const __nv_bfloat16* scale_x, const __nv_bfloat16* scale_w, const __nv_bfloat16* bias, uint32_t sb, int lane) {
    const uint32_t sx2 = (uint32_t)__ldg((const unsigned short*)scale_x) * 0x10001u;
#pragma unroll
    for (int i = lane; i < TN / 4; i += 32) {
        const bool hi = i >= TN / 8;
        uint4 v = __ldg((const uint4*)(hi ? bias : scale_w) + (hi ? i - TN / 8 : i));
        if (CFG_EPI && !hi) v = {bf2_mul(v.x, sx2), bf2_mul(v.y, sx2), bf2_mul(v.z, sx2), bf2_mul(v.w, sx2)};
        sts128(sb + SM_PAR + TN * 2 + i * 16, v);
    }
    __syncwarp();
    if (elect_one()) mbar_arrive(sb + SM_BAR + B_SW * 8);
}
template <bool k2> __device__ __forceinline__ void release(uint32_t go, int u, int lane) {
    const int v = u + NSLOT;
    if (k2) {
        const int q = v + lane;
        if (lane < (v < 48 ? 1 : 0)) mbar_arrive_cluster(mapa(go + (q >> 1) * 8, q & 1));
    } else {
        const int q = 5 * v - (v > 34 ? 3 : 0) + lane;
        if (lane < (v > 38 ? 0 : v == 34 ? 2 : 5)) mbar_arrive_cluster(mapa(go + (q >> 4) * 8, q & 15));
    }
}
__device__ __forceinline__ unsigned read_back(const uint4* d, int lane) { return ld_flag((const unsigned*)(d - lane + ((lane + 10) & 15) * 8 + 6)); }
__device__ __forceinline__ void publish(unsigned rb, unsigned mine, unsigned* flag) {
    if (__shfl_sync(~0u, rb ^ mine, 6)) asm volatile("fence.acq_rel.gpu;" ::: "memory");
    if (elect_one()) flag_add(flag);
}
#define CV_B(m, f)                                                                                                      \
    {                                                                                                                   \
        uint4 v0 = lds128(rdB + m * 512), v1 = lds128(rdB + m * 512 + 128);                                             \
        uint4 v2 = lds128(rdB + m * 512 + 256), v3 = lds128(rdB + m * 512 + 384);                                       \
        o[0].f = pack4(v0.x, v1.x, v2.x, v3.x); o[1].f = pack4(v0.y, v1.y, v2.y, v3.y);                                 \
        o[2].f = pack4(v0.z, v1.z, v2.z, v3.z); o[3].f = pack4(v0.w, v1.w, v2.w, v3.w);                                 \
    }

__device__ __forceinline__ void last_columns(Scratch* sc, const Maps& maps, const __nv_bfloat16* scale_x, const int* zero_x, const __nv_bfloat16* scale_w,
                                             const __nv_bfloat16* bias, uint32_t sb, int warp, int lane, unsigned t0) {
    constexpr int C_FULL = 0, C_EMPTY = 32, C_RAW = 64, C_GO = 80, C_PEER = 81, D3 = CFG_D3;
    const uint32_t bars = sb + SM_BAR;
    const int j = blockIdx.x & 3;
    while ((int)(t0 + CFG_T3 - clk()) > 0) ;
    const int s0 = (j & 1) * 8 + (warp >> 1) * 2;
    if (warp < 8) {
        if (elect_one()) {
#pragma unroll
            for (int i = 0; i < 2; i++) {
                const uint32_t bar = bars + (C_RAW + warp * 2 + i) * 8;
                mbar_init(bar, 1); mbar_expect_tx(bar, 8192);
                raw_load(maps.m + 1, (s0 + (i ^ (j >> 1))) * 64, N_ / 32 - 2 + (warp & 1), sb + SM_A + (warp * 2 + i) * 8192, bar);
            }
#pragma unroll
            for (int i = 0; i < 4; i++) { mbar_init(bars + (C_FULL + warp * 4 + i) * 8, 1); mbar_expect_tx(bars + (C_FULL + warp * 4 + i) * 8, 16384); }
#pragma unroll
            for (int i = 0; i < 4; i++) mbar_init(bars + (C_EMPTY + warp * 4 + i) * 8, 4);
            if (warp == 0) {
                mbar_init(bars + C_GO * 8, 8);
                mbar_init(bars + C_PEER * 8, 1); mbar_expect_tx(bars + C_PEER * 8, 32768 + 4096);
            }
        }
        if (warp < 2) sts32(sb + SM_PAR + threadIdx.x * 4, 0);
        fence_init();
    }
    __syncthreads();
    cluster_arrive();
    cluster_wait();
    if (warp >= 8) {
        asm volatile("setmaxnreg.dec.sync.aligned.u32 40;");
        if (warp < 12) {
            const unsigned ep = (ld_flag(epoch(sc, j * 4, 8)) + 1) * 4;
            const int mb = j * 4 + warp - 8, wg = (warp >> 1) & 1;
            unsigned rdy = 0;
            mbar_wait(bars + (wg ? C_EMPTY : C_GO) * 8);
#pragma unroll 1
            for (int s = 0; s < 16; s++) {
                for (int it = 0; !((rdy >> s) & 1); it++) {
                    rdy = __ballot_sync(~0u, (int)(ld_flag(sc->flag + mb * 32 + (lane & 15)) - ep) >= 0);
                    if (it > (1 << 22)) __trap();
                }
                if (s >= D3) mbar_wait(bars + (C_EMPTY + (s - (s < CFG_S3 ? D3 : CFG_D4)) * 2 + wg) * 8);
                if (elect_one()) tile_load(sc, sb + SM_A + ((s & 3) * 4 + warp - 8) * 8192, mb * 16 + s, bars + (C_FULL + s * 2 + wg) * 8);
            }
        }
    } else {
        asm volatile("setmaxnreg.inc.sync.aligned.u32 200;");
        const int wg = warp >> 2, w = warp & 3;
        const int c0 = (w >> 1) * 32 + (lane >> 2) * 4 + (w & 1) * 2, r0 = (lane & 3) * 2;
        const uint32_t sx2 = (uint32_t)__ldg((const unsigned short*)scale_x) * 0x10001u;
        uint32_t sw = __ldg((const unsigned*)(scale_w + N_ - WB + c0));
        const uint32_t bi = __ldg((const unsigned*)(bias + N_ - WB + c0));
        const float zxf = ld_zx(zero_x);
        int cs[4] = {0, 0, 0, 0};
        const uint32_t peer = mapa(sb, (j & 1) ^ 1);
#pragma unroll 1
        for (int i = 0; i < 2; i++) {
            const uint32_t rdB = sb + SM_A + (warp * 2 + i) * 8192 + (lane >> 3) * 2048 + (lane & 7) * 16;
            const uint32_t wr = SM_RING + (s0 + (i ^ (j >> 1))) * 4096 + (warp & 1) * 2048 + lane * 16;
            mbar_wait(bars + (C_RAW + warp * 2 + i) * 8);
            uint4 o[4];
            CV_B(0, x) CV_B(1, y) CV_B(2, z) CV_B(3, w)
#pragma unroll
            for (int k = 0; k < 4; k++) {
                sts128(sb + wr + k * 512, o[k]);
                asm volatile("st.async.weak.shared::cluster.mbarrier::complete_tx::bytes.v4.b32 [%0], {%1,%2,%3,%4}, [%5];"
                             :: "r"(peer + wr + k * 512), "r"(o[k].x), "r"(o[k].y), "r"(o[k].z), "r"(o[k].w), "r"(peer + SM_BAR + C_PEER * 8) : "memory");
                cs[k] = sum4(o[k].x, sum4(o[k].y, sum4(o[k].z, sum4(o[k].w, cs[k]))));
            }
        }
        __syncwarp();
        if (elect_one()) mbar_arrive(bars + C_GO * 8);
#pragma unroll
        for (int k = 0; k < 4; k++) {
            const uint32_t ca = SM_PAR + ((warp & 1) * 32 + (lane & 7) * 4 + k) * 4;
            red_shared(sb + ca, cs[k]);
            red_async(peer + ca, cs[k], peer + SM_BAR + C_PEER * 8);
        }
        mbar_wait(bars + C_PEER * 8);
        asm volatile("fence.proxy.async.shared::cta;" ::: "memory");
        asm volatile("bar.sync 1, 256;" ::: "memory");
        if (CFG_EPI) sw = bf2_mul(sw, sx2);
        const uint32_t zc = fold(zero_term(lds32(sb + SM_PAR + c0 * 4), lds32(sb + SM_PAR + c0 * 4 + 4), zxf), sw, bi);
        const uint32_t sd = (sb & 0x3FFFF) >> 4;
        int t[2][64];
        wg_fence();
#pragma unroll 1
        for (int s = 0; s < 16; s++) {
            const uint32_t db = ((sd + (SM_RING >> 4)) | (8 << 16)) + s * 256, da = ((sd + (SM_A >> 4)) | (1 << 16)) + ((s & 3) * 4 + wg * 2) * 512;
            mbar_wait(bars + (C_FULL + s * 2 + wg) * 8);
            wgmma_t128(t[0], db, da, s);
            wgmma_t128(t[1], db, da + 512, s);
            wgmma_t128(t[0], db + 16, da + 2, 1);
            wgmma_t128(t[1], db + 16, da + 514, 1);
            wg_commit();
            wg_wait<0>();
            if (elect_one()) mbar_arrive(bars + (C_EMPTY + s * 2 + wg) * 8);
        }
        asm volatile("bar.sync %0, 128;" :: "r"(3 + wg) : "memory");
        const uint32_t st0 = sb + SM_A + wg * 16384 + r0 * 128 + (((c0 >> 3) ^ r0) << 4) + (c0 & 7) * 2;
#pragma unroll
        for (int h = 0; h < 4; h++) {
            const uint32_t off = (h >> 1) * 32768 + (h & 1) * 8192;
#pragma unroll
            for (int q = 0; q < 8; q++) {
                const int o = (h & 1) * 32 + q * 4;
                sts32(st0 + off + q * 1024, epi(t[h >> 1][o], t[h >> 1][o + 2], zc, sx2, sw, bi));
                sts32((st0 ^ (5 * 128 + 5 * 16)) + off + q * 1024, epi(t[h >> 1][o + 1], t[h >> 1][o + 3], zc, sx2, sw, bi));
            }
            asm volatile("fence.proxy.async.shared::cta;" ::: "memory");
            asm volatile("bar.sync %0, 128;" :: "r"(3 + wg) : "memory");
            if (w == 0 && elect_one()) tile_store(maps.m + 2, N_ - WB, j * 512 + wg * 256 + h * 64, sb + SM_A + wg * 16384 + off);
        }
        if (w == 0) {
            asm volatile("cp.async.bulk.commit_group;" ::: "memory");
            asm volatile("cp.async.bulk.wait_group.read 0;" ::: "memory");
        }
        asm volatile("bar.sync 1, 256;" ::: "memory");
        if (threadIdx.x == 0) flag_add(epoch(sc, j * 4, 8));
    }
}

template <bool k2>
__global__ void __cluster_dims__(k2 ? 2 : CS, 1, 1) __launch_bounds__(512, 1)
w8a8_kernel(Scratch* sc, const char* __restrict__ qx, const char* __restrict__ qw, const __nv_bfloat16* __restrict__ scale_x, const int* __restrict__ zero_x,
            const __nv_bfloat16* __restrict__ scale_w, const __nv_bfloat16* __restrict__ bias, const __grid_constant__ Maps maps) {
    extern __shared__ __align__(1024) unsigned char smem_raw[];
    constexpr int NBJ = k2 ? 12 : 14, NF = NBJ, NU = k2 ? 40 : 48;
    constexpr int X1 = k2 ? CFG_X2 : CFG_X1;
    const int b = blockIdx.x + (k2 ? NCTA : 0), r = b & 15, c = k2 ? NCL : b >> 4;
    const unsigned tc = clk();
    if (!k2) {
        const int a = (r * NCL + c) ^ REV;
        const unsigned off = ((a & 63) * 32 + (threadIdx.x >> 1)) * (K_ * 4) + (a >> 6) * 256 + (threadIdx.x & 1) * 128;
        asm volatile("{\n.reg .pred p;\n.reg .b64 a;\nsetp.lt.u32 p, %2, 64;\n@!p bra PF_DONE;\ncvt.u64.u32 a, %1;\nadd.u64 a, a, %0;\nprefetch.global.L2 [a];\nPF_DONE:\n}"
                     :: "l"(qx), "r"(off), "r"(threadIdx.x));
    }
    const uint32_t sb = (uint32_t)__cvta_generic_to_shared(smem_raw);
    const uint32_t bars = sb + SM_BAR;
    const unsigned tw = __shfl_sync(~0u, (tc & ~15u) | threadIdx.x >> 5, 0), t0 = tw + (k2 ? 0 : T0);
    const int warp = tw & 15, lane = threadIdx.x & 31;

    if (!k2 && warp == 12) {
        const int a = r * NCL + c;
        if (elect_one()) {
            mbar_init(bars + (B_RAWA + 3) * 8, 1);
            mbar_expect_tx(bars + (B_RAWA + 3) * 8, 8192);
            raw_load(maps.m, (a >> 6) * 2, ((a ^ REV) & 63) * 32, sb + SM_A + (a < NAJ % NCTA ? 15 : 13) * 8192, bars + (B_RAWA + 3) * 8);
        }
        __syncwarp();
    }
    if (!k2 && (warp >> 1) == 1 && r < CFG_PG) {
        const int a = (NCTA + r * NCL + c) ^ REV;
        const char* p = qx + ((a & 63) * 32 + (warp & 1) * 16 + (lane >> 1)) * (K_ * 4) + (a >> 6) * 256 + (lane & 1) * 128;
        while ((int)(t0 + (16 + r) * P1 - clk()) > 0) ;
        asm volatile("prefetch.global.L2 [%0];" :: "l"(p));
    }
    if (warp == 9 && elect_one()) asm volatile("prefetch.tensormap [%0];" :: "l"(maps.m + 1) : "memory");
    if (k2 && blockIdx.x >= 16) {
        last_columns(sc, maps, scale_x, zero_x, scale_w, bias, sb, warp, lane, t0);
        return;
    }
    if (warp >= 12) {
        const int isw = k2 || warp == 14, t = k2 ? warp - 12 : isw ? 0 : (warp - 11) >> 1;
        const uint32_t bar = bars + ((isw ? B_RAWB : B_RAWA) + 3 + t) * 8;
        if ((k2 || warp != 12) && elect_one()) { mbar_init(bar, 1); mbar_expect_tx(bar, 8192); }
        __syncwarp();
        cluster_arrive();
        const int x = t * 16 + r, a = (x * NCL + c) ^ REV, sx = (x * 26) >> 8;
        static_assert(X1 >= 7, "");
        if ((k2 || warp != 12) && elect_one()) {
            const unsigned te = t0 + (k2 ? sched2(x) : (isw ? time_w(x) : time_x(x)) * P1);
            while ((int)(te - clk()) > 0) ;
            raw_load(maps.m + isw, isw ? sx * 64 : (a >> 6) * 2,
                     isw ? c * (TN / 32) + (int)((0x9765483210ull >> ((x - sx * 10) * 4)) & 15) : (a & 63) * 32,
                     sb + (k2 ? SM_A + 7 * 8192 : isw ? SM_STG : SM_A + 13 * 8192) + (t - (!isw && r * NCL + c < NAJ % NCTA)) * 8192, bar);
        }
        __syncwarp();
        if (!k2 && warp == 15) cluster_wait();
    }
    if (warp < 8) {
        const uint32_t p = bars + warp * 104;
        if (elect_one()) {
#pragma unroll
            for (int i = 0; i < 13; i++) mbar_init(p + i * 8, (!k2 && ((warp == 6 && i == 12) || (warp == 7 && i < 2))) ? 2 : 1);
            static_assert(B_FREE == 90 && B_GO == 104, "");
        }
        __syncwarp();
        const int i = warp * 13 + lane;
        if (lane < 13 && i < B_SW) mbar_expect_tx(p + lane * 8, i >= B_PAR ? (i < B_PAR + 2 ? WA * 2 : WB * 2) : (i & 16) || i >= 48 ? 8192 : WA * 64);
        fence_init();
    }
    if (warp < 8 || warp == 10) cluster_arrive();
    if (!k2 && warp == 10 && lane < CFG_PF7) {
        const int n = b * CFG_PF7 + lane, row = n / 10;
        asm volatile("prefetch.global.L2 [%0];" :: "l"(qw + row * (N_ * 4) + NCL * TN * 4 + (n - row * 10) * 128));
    }

    if (warp < 8) {
        asm volatile("setmaxnreg.inc.sync.aligned.u32 200;");
        const int wg = warp >> 2;
        const uint32_t sd = (sb & 0x3FFFF) >> 4;
        const uint32_t sx2 = (uint32_t)__ldg((const unsigned short*)scale_x) * 0x10001u;
        const uint32_t par = sb + SM_PAR + (lane & 3) * 16 + wg * 256;
        const uint32_t go = bars + B_GO * 8;
        const int w = warp & 3, pq = (lane >> 2) ^ (lane & 4);
        uint32_t so = (w * 16 + pq) * 128 + (((lane & 3) ^ pq) << 4);
        const int c0 = (w >> 1) * 32 + (lane >> 2) * 4 + (w & 1) * 2, r0 = (lane & 3) * 2;
        uint32_t pp = sb + SM_PAR + (2 * WA + wg * WB + c0) * 2, st0 = r0 * 128 + (((c0 >> 3) ^ r0) << 4) + (c0 & 7) * 2;
        uint32_t rq = k2 ? mapa(go + 19 * 8, 1) : mapa(go + (12 + (lane >> 4)) * 8, lane & 15);
        int rk = k2 ? (lane ? 99 : 1) : (lane >> 2) + 1;
        asm volatile("" : "+r"(so), "+r"(pp), "+r"(st0), "+r"(rq), "+r"(rk));
        cluster_wait();
        int a0[WA / 2], a1[WA / 2];
        uint32_t barB = bars + (B_FULLB + wg * 32) * 8;
        wg_fence();
        {
            uint64_t tbl = wg ? slot_table(X1, 1) : slot_table(X1, 0);
            uint32_t da = (sd + (SM_A >> 4)) | (1 << 16);
            int up = 99;
            bool rdy = false;
#pragma unroll 1
            for (int s = 0; s < 16; s++) {
                const uint32_t db = ((sd + (SM_RING >> 4)) | (8 << 16)) + ((uint32_t)tbl & 15) * (SLOT >> 4);
                const bool hold = wg && s == X1;
                if (hold || (!rdy && !mbar_test2(bars + (B_FULLA + s) * 8, barB))) {
                    wg_wait<0>();
                    release<k2>(go, up, lane); up = 99;
                    mbar_wait2(bars + (B_FULLA + s) * 8, barB);
                    if (hold) asm volatile("bar.sync 7, 256;" ::: "memory");
                }
                wgmma_n160(a0, da, db, s);
                wgmma_n160(a1, da + 256, db, s);
                wg_commit();
                if (!wg && s == 15) asm volatile("bar.arrive 7, 256;" ::: "memory");
                wg_wait<1>();
                release<k2>(go, up, lane);
                wgmma_n160(a0, da + 2, db + 16, 1);
                wgmma_n160(a1, da + 258, db + 16, 1);
                wg_commit();
                up = s < X1 ? 2 * s + wg : (wg ? 16 : X1) + s;
                tbl >>= 4; da += 512; barB += 8;
                rdy = mbar_test2(bars + (B_FULLA + s + 1) * 8, barB);
                if (s < 15) wg_wait<1>();
            }
        }
        mbar_wait2(bars + (B_PAR + wg) * 8, bars + B_SW * 8);
        const Par P0 = ld_par(par), P1 = ld_par(par + 64);
        wg_wait<0>();
        release<k2>(go, wg ? 31 : X1 + 15, lane);
        bool ready = mbar_test(barB);
#define FILL_BEGIN(n0, n1) mbar_wait(bars + (B_FREE + (wg ? n1 : n0)) * 8);                                             \
                           const uint32_t buf = sb + SM_STG + (wg ? (turn<k2>(n1) + NBJ) % 3 : (turn<k2>(n0) + NBJ) % 3) * 8192;
#define FILL_END(n0, n1) __syncwarp();                                                                                  \
                         if (elect_one()) mbar_arrive(bars + (B_FILL + (wg ? turn<k2>(n1) : turn<k2>(n0))) * 8);
#define FILL_PAIR(a, J, P, Q, m, MID)                                                                                   \
        {                                                                                                               \
            const uint4 v0 = epi_row(a, J * 16, P, sx2), v1 = epi_row(a, J * 16 + 2, P, sx2);                           \
            FILL_BEGIN(ford<k2>(0, m), ford<k2>(1, m))                                                                  \
            sts128(buf + so, v0); sts128(buf + so + 1024, v1);                                                          \
            MID                                                                                                         \
            sts128(buf + (so ^ 64), epi_row(a, J * 16 + 16, Q, sx2));                                                   \
            sts128(buf + (so ^ 64) + 1024, epi_row(a, J * 16 + 18, Q, sx2));                                            \
            FILL_END(ford<k2>(0, m), ford<k2>(1, m))                                                                    \
        }
#define NARROW(p)                                                                                                       \
        {                                                                                                               \
            if (!ready) mbar_wait(barB);                                                                                \
            wg_fence();                                                                                                 \
            _Pragma("unroll 1") for (int i = 0; i < 8; i++) {                                                           \
                const uint32_t db = ((sd + (SM_RING >> 4)) | (8 << 16)) + (k2 ? (i > 2 ? i - 3 : i + 4) * (SLOT >> 4) : ((i + 5) & 7) * 512); \
                _Pragma("unroll") for (int kk = 0; kk < 4; kk++)                                                        \
                    wgmma_t128(t, db + (kk >> 1) * 256 + (kk & 1) * 16,                                                 \
                               ((sd + (SM_A >> 4)) | (1 << 16)) + i * 1024 + (kk >> 1) * 512 + (kk & 1) * 2, kk ? 1 : i); \
                wg_commit();                                                                                            \
                barB += 8;                                                                                              \
                mbar_wait(i < 7 ? barB : bars + (B_PAR + p) * 8);                                                       \
                wg_wait<1>();                                                                                           \
                if (p == 2 && rk == i) mbar_arrive_cluster(rq);                                                         \
            }                                                                                                           \
            if (p == 3 || k2) { zc = lds32(pp); sw = lds32(pp + TN * 2); bi = CFG_EPI == 3 ? 0 : lds32(pp + TN * 4); }               \
            wg_wait<0>();                                                                                               \
            if (p == 2 && rk == 8) mbar_arrive_cluster(rq);                                                             \
        }
        Par P2, P3, P;
        FILL_PAIR(a0, 0, P0, P1, 0, P2 = ld_par(par + 128);)
        FILL_PAIR(a1, 0, P0, P1, 1, P3 = ld_par(par + 192);)
        FILL_PAIR(a0, 2, P2, P3, 2, P = ld_par(par + 512 - wg * 192);)
        FILL_PAIR(a1, 2, P2, P3, 3, )
        int t[64];
        uint32_t zc, sw, bi;
        if (!k2 && wg == 0) NARROW(2)
        {
            const uint4 v0 = epi_row(a0, 64, P, sx2), v1 = epi_row(a0, 66, P, sx2);
            FILL_BEGIN(ford<k2>(0, 4), ford<k2>(1, 4))
            const uint32_t s4 = buf + ((so >> 1) & ~63u) + (lane & 3) * 16;
            sts128(s4, v0); sts128(s4 + 512, v1);
            sts128(s4 + 4096, epi_row(a1, 64, P, sx2)); sts128(s4 + 4608, epi_row(a1, 66, P, sx2));
            FILL_END(ford<k2>(0, 4), ford<k2>(1, 4))
        }
        if (!(k2 && wg)) {
            if (k2) NARROW(2) else if (wg) NARROW(3) else { zc = lds32(pp); sw = lds32(pp + TN * 2); bi = CFG_EPI == 3 ? 0 : lds32(pp + TN * 4); }
#define FILL_T(h)                                                                                                       \
            {                                                                                                           \
                FILL_BEGIN((10 + h), (12 + h))                                                                          \
                _Pragma("unroll") for (int j = 0; j < 8; j++) {                                                         \
                    const int o = h * 32 + j * 4;                                                                       \
                    sts32(buf + st0 + j * 1024, epi(t[o], t[o + 2], zc, sx2, sw, bi));                                  \
                    sts32(buf + (st0 ^ (5 * 128 + 5 * 16)) + j * 1024, epi(t[o + 1], t[o + 3], zc, sx2, sw, bi));       \
                }                                                                                                       \
                FILL_END((10 + h), (12 + h))                                                                            \
            }
            FILL_T(0) FILL_T(1)
        }
        if (threadIdx.x == 0) flag_add(epoch(sc, r, c));
    } else {
        const int g = r * NCL + c, na = k2 ? 0 : NAJ / NCTA + (g < NAJ % NCTA);
        int cw = NF;
        if (warp >= 12) {
            asm volatile("setmaxnreg.dec.sync.aligned.u32 80;");
            if (warp < 14) {
                const int c4 = (lane ^ (lane >> 3)) & 3, ln = ((lane >> 2) ^ (lane & 4)) * 2 + (c4 >> 1);
                const uint32_t rd0 = sb + SM_A + 13 * 8192 + ln * 128 + ((((c4 & 1) << 2) ^ (ln & 7)) << 4);
#pragma unroll 1
                for (int t = warp - 12, sl = na == 9 ? t : 2 - 2 * t; t < na; t += 2, sl = sl ? sl - 1 : 2) {
                    const uint32_t rdA = rd0 + sl * 8192;
                    const int a = (t * NCTA + g) ^ REV, f = (a & 60) * 4 + (a >> 6);
                    uint4* const d = sc->s8 + (f * 4 + (a & 3)) * 128 + lane;
                    uint4 o[4];
                    mbar_wait(bars + (B_RAWA + 3 + t) * 8);
#pragma unroll
                    for (int i = 0; i < 4; i++) {
                        uint4 v0 = lds128(rdA + i * 2048), v1 = lds128((rdA ^ 16) + i * 2048);
                        uint4 v2 = lds128((rdA ^ 32) + i * 2048), v3 = lds128((rdA ^ 48) + i * 2048);
                        o[i].x = pack4(v0.x, v0.y, v0.z, v0.w); o[i].y = pack4(v1.x, v1.y, v1.z, v1.w);
                        o[i].z = pack4(v2.x, v2.y, v2.z, v2.w); o[i].w = pack4(v3.x, v3.y, v3.z, v3.w);
                    }
#pragma unroll
                    for (int i = 0; i < 4; i++) stg128(d + i * 32, o[i]);
                    asm volatile("fence.proxy.async.global;" ::: "memory");
                    __syncwarp();
                    const unsigned rb = read_back(d, lane);
                    if (t < 2) cluster_wait();
                    if (elect_one()) mbar_arrive(bars + ((t < na - 3 ? B_RAWA : B_AFREE + 13) + sl) * 8);
                    publish(rb, o[0].x, sc->flag + (a & 60) * 8 + (a >> 6));
                }
                cw = warp - 12;
            }
            if (!k2) {
                const int hw = warp & 1;
                const uint32_t rd0 = sb + SM_STG + hw * 4096 + (lane >> 3) * 1024 + (lane & 7) * 16;
                const int myG = decode_b(X1, (lane & 15) * 16 + r).G;
#pragma unroll 1
                for (int t = warp < 14 ? TA : 0; t < NBJ; t += warp < 14 ? NBJ : t == TA - 1 ? 2 : 1) {
                    const int sl = t % 3;
                    const uint32_t rdB = rd0 + sl * 8192;
                    char* const d = (char*)sc->s8 + (1024 + c * 256 + t * 16 + r) * 2048 + hw * 256 + (lane >> 4) * 128 + (lane & 7) * 16 + (lane & 8);
                    uint2 o[4];
                    mbar_wait(bars + (B_RAWB + 3 + t) * 8);
                    CV_B(0, x) CV_B(1, y)
#pragma unroll
                    for (int i = 0; i < 4; i++) asm volatile("st.global.v2.b32 [%0], {%1,%2};" :: "l"(d + i * 512), "r"(o[i].x), "r"(o[i].y) : "memory");
                    if (t == 0 && warp == 14) cluster_wait();
                    if (elect_one()) mbar_arrive(bars + (t >= NBJ - 3 ? B_FREE + t - (NBJ - 3) : B_RAWB + sl) * 8);
                    asm volatile("fence.proxy.async.global;" ::: "memory");
                    __syncwarp();
                    if (elect_one()) mbar_arrive(bars + (B_GO + t) * 8);
                    int cs[4];
#pragma unroll
                    for (int i = 0; i < 4; i++) cs[i] = sum4(o[i].x, sum4(o[i].y, 0));
                    const int p01 = cs[0] + cs[1] * 65536, p23 = cs[2] + cs[3] * 65536;
                    const bool h = lane & 16;
                    int x = (h ? p23 : p01) + __shfl_xor_sync(~0u, h ? p01 : p23, 16);
                    x += __shfl_xor_sync(~0u, x, 8);
                    const int lo = (int)(short)x, v = (lane & 8) ? (x - lo) >> 16 : lo;
                    const int G = __shfl_sync(~0u, myG, t);
                    if (G != r) {
                        red_async(mapa(sb + SM_CS + lane * 4, G), v, mapa(bars + B_CS * 8, G));
                    } else {
                        red_shared(sb + SM_CS + lane * 4, v);
                        __syncwarp();
                        if (elect_one()) mbar_arrive(bars + B_CS * 8);
                    }
                }
            } else {
                const uint32_t rd0 = sb + (lane >> 3) * 2048 + (lane & 7) * 16;
                const BJob mb = decode_b(X1, (lane & 15) * 16 + r);
                const int myG = mb.G | mb.u << 8;
#pragma unroll 1
                for (int t = warp - 12; t < NBJ; t += 4) {
                    const uint32_t rdB = rd0 + stage_w<k2>(t);
                    uint4* const d = sc->s8 + (1024 + c * 256 + t * 16 + r) * 128 + lane;
                    uint4 o[4];
                    mbar_wait(bars + (B_RAWB + 3 + t) * 8);
                    CV_B(0, x) CV_B(1, y) CV_B(2, z) CV_B(3, w)
#pragma unroll
                    for (int i = 0; i < 4; i++) stg128(d + i * 32, o[i]);
                    if (t < 4) cluster_wait();
                    if (elect_one()) mbar_arrive(bars + (B_FREE + t - (NBJ - 3)) * 8);
                    asm volatile("fence.proxy.async.global;" ::: "memory");
                    __syncwarp();
                    const unsigned rb = read_back(d, lane), ep = ld_flag(epoch(sc, r, c));
                    int cs[4];
#pragma unroll
                    for (int i = 0; i < 4; i++) cs[i] = sum4(o[i].x, sum4(o[i].y, sum4(o[i].z, sum4(o[i].w, 0))));
                    const bool h = lane & 16, odd = lane & 8;
                    int x = (h ? cs[2] : cs[0]) + __shfl_xor_sync(~0u, h ? cs[0] : cs[2], 16);
                    int y = (h ? cs[3] : cs[1]) + __shfl_xor_sync(~0u, h ? cs[1] : cs[3], 16);
                    const int v = (odd ? y : x) + __shfl_xor_sync(~0u, odd ? x : y, 8);
                    const int gu = __shfl_sync(~0u, myG, t);
                    publish(rb, o[0].x, sc->flag + F_W + (gu >> 8));
                    const int old = atomicAdd(sc->cs[ep & 1] + col_of(gu & 255) + (lane & 7) * 4 + (lane >> 3), v);
                    if (old == 0x7FFFFFFF) sc->sink[0] = old;
                    __syncwarp();
                    if (elect_one()) flag_add(sc->flag + F_CS + (gu & 255) / 5);
                }
            }
        } else {
            asm volatile("setmaxnreg.dec.sync.aligned.u32 32;");
            if (warp == 11) {
                if (elect_one()) {
#pragma unroll
                    for (int i = 0; i < (k2 ? NU / 2 : NBJ); i++)
                        mbar_init(bars + (B_GO + i) * 8, k2 ? (i * 2 + (r & 1) >= NSLOT ? 9 : 1) : (i * 16 + r >= NSLOT * 5 ? 2 + 4 * CS : 2));
#pragma unroll
                    for (int i = 0; i < 3; i++) mbar_init(bars + (B_FILL + i) * 8, 4);
                }
                const int u2 = lane * 2 + (r & 1), q = k2 ? (u2 < 32 ? 5 * u2 : 4 * u2 + 32) : (lane & 15) * 16 + r;
                const BJob bj = decode_b(X1, q);
                unsigned seen = 0;
                if (!k2) {
                    const int nself = __popc(__ballot_sync(~0u, lane < NBJ && bj.G == r));
                    sts32(sb + SM_CS + lane * 4, 0);
                    if (lane == 0) {
                        mbar_init(bars + B_CS * 8, 1 + 2 * nself);
                        mbar_expect_tx(bars + B_CS * 8, (16 - nself) * 256);
                    }
                    seen = lds32(sb + SM_CS + lane * 4);
                }
                fence_init();
                asm volatile("barrier.cluster.arrive.relaxed.aligned;" :: "r"(seen) : "memory");
                const char* src = (const char*)sc->s8 + (1024 + c * 256 + q) * 2048;
                const uint32_t dst = sb + SM_RING + ((!k2 && q >= 160) ? ((q + 20) & 31) * 2048 : (bj.u % NSLOT) * SLOT + bj.pos * 2048);
                const uint32_t fb = bars + (B_FULLB + fb_of(X1, bj.u)) * 8;
                cluster_wait();
                if (!k2) scale_bias(scale_x, scale_w + c * TN, bias + c * TN, sb, lane);
#pragma unroll 1
                for (int i = 0; i < (k2 ? NU / 2 : NBJ); i++) {
                    mbar_wait(bars + (B_GO + i) * 8);
                    if (lane == i) {
                        asm volatile("cp.async.bulk.shared::cluster.global.mbarrier::complete_tx::bytes.multicast::cluster [%0], [%1], %2, [%3], %4;"
                                     :: "r"(dst), "l"(src), "r"(k2 ? (u2 < 32 ? SLOT : 8192) : 2048), "r"(fb), "h"((uint16_t)(k2 ? 3 : 0xFFFF)) : "memory");
                    }
                    __syncwarp();
                }
            } else if (warp == 10) {
                const unsigned ep = (__shfl_sync(~0u, ld_flag(sc->flag + r * 32 + (lane < 16 ? lane : 16 + c)), 16) + 1) * 4;
                const unsigned* f = sc->flag + r * 32 + (lane & 15);
                bool dn = lane >= 16;
                const bool fr = lane < (k2 ? 7 : 13);
                cluster_wait();
                for (int it = 0;; it++) {
                    const unsigned v = ld_flag(f);
                    if (!dn && (int)(v - ep) >= 0 && (fr || mbar_test(bars + (B_AFREE + lane) * 8))) {
                        dn = true;
                        tile_load(sc, sb + SM_A + lane * 8192, r * 16 + lane, bars + (B_FULLA + lane) * 8);
                    }
                    if (__all_sync(~0u, dn)) break;
                    if (it > (1 << 22)) __trap();
                }
            } else {
                const bool isw = warp == 9;
                const uint32_t rb = bars + (isw ? B_RAWB : B_RAWA) * 8;
                if (elect_one()) {
#pragma unroll
                    for (int i = 0; i < 13; i++) if (i < 3 || i >= (k2 ? 7 : 6)) mbar_init(rb + i * 8, (i < 3 && isw && !k2) ? 2 : 1);
                    if (isw) {
#pragma unroll
                        for (int i = 13; i < 17; i++) mbar_init(rb + i * 8, 1);
                        if (!k2) { mbar_init(rb + 4 * 8, 1); mbar_init(rb + 5 * 8, 1); }
                    }
                }
                __syncwarp();
                const int nj = isw ? NBJ : na, j0 = k2 ? 4 : isw ? 1 : 3;
                if (lane >= j0 && lane < nj) mbar_expect_tx(rb + (3 + lane) * 8, 8192);
                fence_init();
                cluster_arrive();
                const unsigned e0 = k2 ? ld_flag(epoch(sc, r, c)) : 0;
                const int k = lane / 3, x = lane * 16 + r;
                int sl = lane - k * 3, y, z, T;
                if (isw) {
                    const BJob bj = decode_b(X1, x & 255);
                    y = bj.slab * 64; z = (c * TN + col_of(bj.G)) >> 5; T = time_w(x);
                } else {
                    const int a = (lane * NCTA + g) ^ REV;
                    y = (a >> 6) * 2; z = (a & 63) * 32; T = time_x(x);
                    if (na == 10) sl = sl ? sl - 1 : 2;
                }
                const unsigned te = t0 + (k2 ? sched2(x) : sched(T));
                const uint32_t sd = sb + (isw ? stage_w<k2>(lane) : SM_A + (13 + sl) * 8192);
#pragma unroll 1
                for (int t = j0; t < nj; t++) {
                    if (lane == t) {
                        if (t >= 3 && !k2) mbar_wait(rb + sl * 8, (k & 1) ^ 1);
                        while ((int)(te - clk()) > 0) ;
                        raw_load(maps.m + isw, y, z, sd, rb + (3 + t) * 8);
                    }
                    __syncwarp();
                }
                cluster_wait();
                if (elect_one()) asm volatile("prefetch.tensormap [%0];" :: "l"(maps.m + 2 + isw) : "memory");
                if (!isw) cw = 2;
                if (k2) {
                    if (!isw) {
                        if (lane < TN / 16) sc->cs[(e0 & 1) ^ 1][r * (TN / 16) + lane] = 0;
                        const int u = lane * 2 + (r & 1);
                        const unsigned tg = (e0 + 1) * (u < 32 ? 5 : 4);
                        bool dn = u >= NU;
                        for (int it = 0;; it++) {
                            if (!dn && (int)(ld_flag(sc->flag + F_W + u) - tg) >= 0) {
                                dn = true;
                                mbar_arrive(bars + (B_GO + lane) * 8);
                            }
                            if (__all_sync(~0u, dn)) break;
                            if (it > (1 << 22)) __trap();
                        }
                    } else {
                        const float zxf = ld_zx(zero_x);
                        scale_bias(scale_x, scale_w + c * TN, bias + c * TN, sb, lane);
#pragma unroll 1
                        for (int h = 0; h < 3; h++) {
                            for (int it = 0; (int)(ld_flag(sc->flag + F_CS + h) - (e0 + 1) * (h < 2 ? 80 : 32)) < 0; it++) if (it > (1 << 22)) __trap();
                            int2 v[3];
                            int i[3];
#pragma unroll
                            for (int j = 0; j < 3; j++) {
                                i[j] = (j < 2 ? h * 64 + j * 32 : 128 + h * 16) + lane;
                                v[j] = __ldcg((const int2*)sc->cs[e0 & 1] + i[j]);
                            }
#pragma unroll
                            for (int j = 0; j < 3; j++) {
                                const uint32_t pa = sb + SM_PAR + i[j] * 4;
                                const uint32_t z = fold(zero_term(v[j].x, v[j].y, zxf), lds32(pa + TN * 2), lds32(pa + TN * 4));
                                if (h < 2 ? (j < 2 || lane < 16) : j == 2) st_async(pa, z, bars + (B_PAR + h) * 8);
                            }
                        }
                    }
                }
            }
        }
        if (!k2 && r < NBJ && warp == (r < 10 ? 8 : 10)) {
            const float zxf = ld_zx(zero_x);
            const int w = lane & 15;
            uint32_t sw = 0, bi = 0;
            if (CFG_EPI == 3) { mbar_wait(bars + B_SW * 8); sw = lds32(sb + SM_PAR + TN * 2 + col_of(r) * 2 + w * 4); bi = lds32(sb + SM_PAR + TN * 4 + col_of(r) * 2 + w * 4); }
            mbar_wait(bars + B_CS * 8);
            const uint32_t ca = sb + SM_CS + ((w >> 1) + (w & 1) * 16) * 4;
            const uint32_t z = fold(zero_term(lds32(ca), lds32(ca + 32), zxf), sw, bi);
            const int piece = r < 10 ? (r >= 5) : (r - 6) >> 1;
#pragma unroll 1
            for (int i = lane >> 4; i < CS; i += 2) st_async(mapa(sb + SM_PAR + col_of(r) * 2 + w * 4, i), z, mapa(bars + (B_PAR + piece) * 8, i));
        }
#pragma unroll 1
        for (int n = cw, nn, k = 0; n < NF; n = nn, k ^= 1) {
            nn = n + 3;
            if (!k2 && n < 5 && nn >= 5) nn += nn == 5 ? 2 : -1;
            const int gm = (int)(ford_table<k2>() >> (4 * n)), g = (gm >> 3) & 1, m = gm & 7;
            const int x = n >= 10 ? (n >> 1) * 64 : m == 4 ? 256 + g * 32 : g * 128 + (m & 2) * 32;
            const int y = n >= 10 ? (n & 1) * 64 : (m & 1) * 64;
            mbar_wait(bars + (B_FILL + cw) * 8, k);
            asm volatile("fence.proxy.async.shared::cta;" ::: "memory");
            if (elect_one()) tile_store(maps.m + (n < 10 && m == 4 ? 3 : 2), c * TN + x, r * 128 + y, sb + SM_STG + ((cw + NBJ) % 3) * 8192);
            asm volatile("cp.async.bulk.commit_group;" ::: "memory");
            asm volatile("cp.async.bulk.wait_group.read 0;" ::: "memory");
            __syncwarp();
            if (nn < NF && elect_one()) mbar_arrive(bars + (B_FREE + nn) * 8);
        }
    }
}

__global__ void __launch_bounds__(256)
w8a8_plain(const int* __restrict__ qx, const int* __restrict__ qw, const __nv_bfloat16* __restrict__ scale_x, const int* __restrict__ zero_x,
           const __nv_bfloat16* __restrict__ scale_w, const __nv_bfloat16* __restrict__ bias, __nv_bfloat16* __restrict__ out) {
    __shared__ int xs[16][K_ / 4];
    const int n = (blockIdx.x * 256 + threadIdx.x) * 2, m0 = blockIdx.y * 16;
    for (int i = threadIdx.x; i < 16 * K_ / 4; i += 256) {
        const uint4 v = ((const uint4*)qx)[m0 * (K_ / 4) + i];
        xs[i / (K_ / 4)][i % (K_ / 4)] = pack4(v.x, v.y, v.z, v.w);
    }
    __syncthreads();
    int acc[16][2] = {}, cs[2] = {};
    for (int k = 0; k < K_ / 4; k++) {
        uint2 v[4];
#pragma unroll
        for (int i = 0; i < 4; i++) v[i] = *(const uint2*)(qw + (k * 4 + i) * N_ + n);
        const unsigned w0 = pack4(v[0].x, v[1].x, v[2].x, v[3].x), w1 = pack4(v[0].y, v[1].y, v[2].y, v[3].y);
        cs[0] = sum4(w0, cs[0]); cs[1] = sum4(w1, cs[1]);
#pragma unroll
        for (int i = 0; i < 16; i++) { acc[i][0] = __dp4a(xs[i][k], (int)w0, acc[i][0]); acc[i][1] = __dp4a(xs[i][k], (int)w1, acc[i][1]); }
    }
    const uint32_t sx2 = (uint32_t)*(const unsigned short*)scale_x * 0x10001u, bi = *(const unsigned*)(bias + n);
    uint32_t sw = *(const unsigned*)(scale_w + n);
    if (CFG_EPI) sw = bf2_mul(sw, sx2);
    const uint32_t zc = fold(zero_term(cs[0], cs[1], ld_zx(zero_x)), sw, bi);
#pragma unroll
    for (int i = 0; i < 16; i++) *(unsigned*)(out + (m0 + i) * N_ + n) = epi(acc[i][0], acc[i][1], zc, sx2, sw, bi);
}

}

typedef CUresult (*EncodeFn)(CUtensorMap*, CUtensorMapDataType, cuuint32_t, void*, const cuuint64_t*, const cuuint64_t*,
                             const cuuint32_t*, const cuuint32_t*, CUtensorMapInterleave, CUtensorMapSwizzle,
                             CUtensorMapL2promotion, CUtensorMapFloatOOBfill);

extern "C" void kernel_launch(void* const* d_in, const int* in_sizes, int n_in, void* d_out, int out_size) {
    using namespace w8;
    static EncodeFn encode = nullptr;
    static cudaStream_t side;
    static cudaEvent_t started, joined;
    static int clusters = -1;
    static Scratch* sc;
    cudaLaunchConfig_t cfg = {};
    cfg.gridDim = dim3(NCTA); cfg.blockDim = dim3(512); cfg.dynamicSmemBytes = SM_TOTAL; cfg.stream = cudaStreamPerThread;
    if (clusters < 0) {
        void* fn = nullptr;
        cudaDriverEntryPointQueryResult qr;
        cudaGetDriverEntryPoint("cuTensorMapEncodeTiled", &fn, cudaEnableDefault, &qr);
        encode = (EncodeFn)fn;
        cudaGetSymbolAddress((void**)&sc, g_scratch);
        cudaStreamCreateWithFlags(&side, cudaStreamNonBlocking);
        cudaEventCreateWithFlags(&started, cudaEventDisableTiming);
        cudaEventCreateWithFlags(&joined, cudaEventDisableTiming);
        cudaFuncSetAttribute(w8a8_kernel<false>, cudaFuncAttributeMaxDynamicSharedMemorySize, SM_TOTAL);
        cudaFuncSetAttribute(w8a8_kernel<true>, cudaFuncAttributeMaxDynamicSharedMemorySize, SM_TOTAL);
        cudaFuncSetAttribute(w8a8_kernel<false>, cudaFuncAttributeNonPortableClusterSizeAllowed, 1);
        if (cudaOccupancyMaxActiveClusters(&clusters, w8a8_kernel<false>, &cfg) != cudaSuccess) { clusters = 0; cudaGetLastError(); }
    }
    const __nv_bfloat16 *sx = (const __nv_bfloat16*)d_in[2], *sw = (const __nv_bfloat16*)d_in[4], *bias = (const __nv_bfloat16*)d_in[5];
    const int* zx = (const int*)d_in[3];
    if (clusters < NCL) {
        w8a8_plain<<<dim3(N_ / 512, M_ / 16), 256, 0, cudaStreamPerThread>>>((const int*)d_in[0], (const int*)d_in[1], sx, zx, sw, bias, (__nv_bfloat16*)d_out);
        return;
    }
    Maps maps;
    const cuuint32_t es[3] = {1, 1, 1};
    {
        const cuuint64_t dim[3] = {32, K_ / 32, M_}, str[2] = {128, K_ * 4};
        const cuuint32_t box[3] = {32, 2, 32};
        encode(&maps.m[0], CU_TENSOR_MAP_DATA_TYPE_INT32, 3, d_in[0], dim, str, box, es, CU_TENSOR_MAP_INTERLEAVE_NONE,
               CU_TENSOR_MAP_SWIZZLE_128B, CU_TENSOR_MAP_L2_PROMOTION_NONE, CU_TENSOR_MAP_FLOAT_OOB_FILL_NONE);
    }
    {
        const cuuint64_t dim[3] = {32, K_, N_ / 32}, str[2] = {N_ * 4, 128};
        const cuuint32_t box[3] = {32, 64, 1};
        encode(&maps.m[1], CU_TENSOR_MAP_DATA_TYPE_INT32, 3, d_in[1], dim, str, box, es, CU_TENSOR_MAP_INTERLEAVE_NONE,
               CU_TENSOR_MAP_SWIZZLE_NONE, CU_TENSOR_MAP_L2_PROMOTION_NONE, CU_TENSOR_MAP_FLOAT_OOB_FILL_NONE);
    }
    for (int i = 0; i < 2; i++) {
        const cuuint64_t dim[2] = {N_, M_}, str[1] = {N_ * 2};
        const cuuint32_t box[2] = {i ? 32u : 64u, i ? 128u : 64u};
        encode(&maps.m[2 + i], CU_TENSOR_MAP_DATA_TYPE_BFLOAT16, 2, d_out, dim, str, box, es, CU_TENSOR_MAP_INTERLEAVE_NONE,
               i ? CU_TENSOR_MAP_SWIZZLE_NONE : CU_TENSOR_MAP_SWIZZLE_128B, CU_TENSOR_MAP_L2_PROMOTION_NONE, CU_TENSOR_MAP_FLOAT_OOB_FILL_NONE);
    }
    cudaLaunchAttribute at;
    at.id = cudaLaunchAttributeProgrammaticEvent;
    at.val.programmaticEvent.event = started; at.val.programmaticEvent.flags = 0; at.val.programmaticEvent.triggerAtBlockStart = 1;
    cfg.attrs = &at; cfg.numAttrs = 1;
    cudaLaunchKernelEx(&cfg, w8a8_kernel<false>, sc, (const char*)d_in[0], (const char*)d_in[1], sx, zx, sw, bias, maps);
    cudaStreamWaitEvent(side, started, 0);
    cfg.gridDim = dim3(20); cfg.stream = side; cfg.numAttrs = 0;
    cudaLaunchKernelEx(&cfg, w8a8_kernel<true>, sc, (const char*)d_in[0], (const char*)d_in[1], sx, zx, sw, bias, maps);
    cudaEventRecord(joined, side);
    cudaStreamWaitEvent(cudaStreamPerThread, joined, 0);
}
```

```cpp
#include <cuda_runtime.h>
#include <cuda.h>
#include <cuda_bf16.h>
#include <stdint.h>
#include <stddef.h>

#define CFG_X1 13
#define CFG_P1 46
#define CFG_P2 39
#define CFG_PT 100
#define CFG_L0 34
#define CFG_RA 33
#define CFG_T0 -550
#define CFG_Q0 14
#define CFG_Q2 69
#define CFG_Q3 30
#define CFG_T3 400
#define CFG_D3 2
#define CFG_PF7 18
#define CFG_TA 10
#define CFG_EPI 3
#define CFG_X2 11
#define CFG_S3 12
#define CFG_D4 4
#define CFG_PG 8

namespace w8 {

constexpr int M_ = 2048, K_ = 1024, N_ = 3584;
constexpr int CS = 16, NCL = 7, NCTA = CS * NCL;
constexpr int WA = 160, WB = 64, TN = 2 * WA + 2 * WB;
constexpr int NSLOT = 7, SLOT = WA * 64;
constexpr int NAJ = 1024;
constexpr int REV = 60;
constexpr int TA = CFG_TA;

constexpr int L0 = CFG_L0, RA = CFG_RA, RB64 = 64 * RA / (RA - 16);
constexpr int P1 = CFG_P1, P2 = CFG_P2, PT = CFG_PT, T0 = CFG_T0;
__device__ __forceinline__ int time_x(int x) { return max(x, L0 + (((x - L0) * RA) >> 4)); }
__device__ __forceinline__ int time_w(int q) { return min(L0 + ((q * RB64) >> 6), NAJ / NCL + q); }
__device__ __forceinline__ unsigned sched(int T) { return T * P2 + min(T, PT) * (P1 - P2); }
__device__ __forceinline__ int sched2(int q) { return (min(q, 160) - CFG_Q0) * CFG_Q2 + max(q - 160, 0) * CFG_Q3; }

constexpr int SM_A = 0;
constexpr int SM_RING = 131072;
constexpr int SM_STG = SM_RING + NSLOT * SLOT;
constexpr int SM_PAR = SM_STG + 3 * 8192;
constexpr int SM_CS = SM_PAR + 3 * TN * 2;
constexpr int SM_BAR = SM_CS + 128;
constexpr int B_FULLB = 0, B_FULLA = 56, B_PAR = 72, B_SW = 77, B_AFREE = 74  , B_FREE = 90,
              B_FILL = 128, B_CS = 131, B_RAWA = 132, B_RAWB = 145, B_GO = 164  , B_END = 204;
constexpr int SM_TOTAL = SM_BAR + B_END * 8;
static_assert(SM_TOTAL <= 232448, "");

constexpr int F_W = 512, F_CS = 576;
struct Scratch {
    unsigned flag[768];
    int cs[2][TN];
    int sink[384];
    uint4 s8[(1024 + 8 * 256) * 128];
};
static_assert(offsetof(Scratch, s8) == 8192, "");
__device__ __align__(8192) Scratch g_scratch;
__device__ __forceinline__ unsigned* epoch(Scratch* sc, int r, int c) { return sc->flag + r * 32 + 16 + c; }

__device__ __forceinline__ void mbar_init(uint32_t bar, uint32_t cnt) {
    asm volatile("mbarrier.init.shared::cta.b64 [%0], %1;" :: "r"(bar), "r"(cnt) : "memory");
}
__device__ __forceinline__ void mbar_expect_tx(uint32_t bar, uint32_t bytes) {
    asm volatile("mbarrier.arrive.expect_tx.shared::cta.b64 _, [%0], %1;" :: "r"(bar), "r"(bytes) : "memory");
}
__device__ __forceinline__ void mbar_arrive(uint32_t bar) {
    asm volatile("mbarrier.arrive.shared::cta.b64 _, [%0];" :: "r"(bar) : "memory");
}
__device__ __forceinline__ void mbar_arrive_cluster(uint32_t bar) {
    asm volatile("mbarrier.arrive.shared::cluster.b64 _, [%0];" :: "r"(bar) : "memory");
}
__device__ __forceinline__ void mbar_wait(uint32_t bar, uint32_t parity = 0) {
    asm volatile("{\n.reg .pred p;\n.reg .u32 c;\n"
                 "mbarrier.try_wait.parity.shared::cta.b64 p, [%0], %1;\n"
                 "@p bra WAIT_DONE;\n"
                 "mov.u32 c, 0;\n"
                 "WAIT_LOOP:\n"
                 "mbarrier.try_wait.parity.shared::cta.b64 p, [%0], %1;\n"
                 "@p bra WAIT_DONE;\n"
                 "add.u32 c, c, 1;\nsetp.lt.u32 p, c, 0x100000;\n"
                 "@p bra WAIT_LOOP;\n"
                 "trap;\n"
                 "WAIT_DONE:\n}" :: "r"(bar), "r"(parity) : "memory");
}
__device__ __forceinline__ void mbar_wait2(uint32_t bar0, uint32_t bar1) {
    asm volatile("{\n.reg .pred p, q;\n.reg .u32 c;\nmov.u32 c, 0;\n"
                 "WAIT_LOOP:\n"
                 "mbarrier.try_wait.parity.shared::cta.b64 p, [%0], 0;\n"
                 "mbarrier.try_wait.parity.shared::cta.b64 q, [%1], 0;\n"
                 "and.pred p, p, q;\n"
                 "@p bra WAIT_DONE;\n"
                 "add.u32 c, c, 1;\nsetp.lt.u32 p, c, 0x100000;\n"
                 "@p bra WAIT_LOOP;\n"
                 "trap;\n"
                 "WAIT_DONE:\n}" :: "r"(bar0), "r"(bar1) : "memory");
}
__device__ __forceinline__ bool mbar_test(uint32_t bar) {
    uint32_t ok;
    asm volatile("{\n.reg .pred p;\nmbarrier.test_wait.parity.shared::cta.b64 p, [%1], 0;\nselp.u32 %0, 1, 0, p;\n}" : "=r"(ok) : "r"(bar) : "memory");
    return ok;
}
__device__ __forceinline__ bool mbar_test2(uint32_t bar0, uint32_t bar1) {
    uint32_t ok;
    asm volatile("{\n.reg .pred p, q;\nmbarrier.test_wait.parity.shared::cta.b64 p, [%1], 0;\n"
                 "mbarrier.test_wait.parity.shared::cta.b64 q, [%2], 0;\nand.pred p, p, q;\nselp.u32 %0, 1, 0, p;\n}"
                 : "=r"(ok) : "r"(bar0), "r"(bar1) : "memory");
    return ok;
}
__device__ __forceinline__ bool elect_one() {
    uint32_t ok;
    asm volatile("{\n.reg .pred p;\nelect.sync _|p, 0xffffffff;\nselp.u32 %0, 1, 0, p;\n}" : "=r"(ok));
    return ok;
}
__device__ __forceinline__ unsigned ld_flag(const unsigned* p) {
    unsigned v;
    asm volatile("ld.relaxed.gpu.global.u32 %0, [%1];" : "=r"(v) : "l"(p) : "memory");
    return v;
}
__device__ __forceinline__ uint4 lds128(uint32_t a) {
    uint4 v;
    asm volatile("ld.shared.v4.b32 {%0,%1,%2,%3}, [%4];" : "=r"(v.x), "=r"(v.y), "=r"(v.z), "=r"(v.w) : "r"(a) : "memory");
    return v;
}
__device__ __forceinline__ void sts128(uint32_t a, uint4 v) {
    asm volatile("st.shared.v4.b32 [%0], {%1,%2,%3,%4};" :: "r"(a), "r"(v.x), "r"(v.y), "r"(v.z), "r"(v.w) : "memory");
}
__device__ __forceinline__ uint32_t lds32(uint32_t a) {
    uint32_t v;
    asm volatile("ld.shared.b32 %0, [%1];" : "=r"(v) : "r"(a) : "memory");
    return v;
}
__device__ __forceinline__ void sts32(uint32_t a, uint32_t v) {
    asm volatile("st.shared.b32 [%0], %1;" :: "r"(a), "r"(v) : "memory");
}
__device__ __forceinline__ void stg128(void* p, uint4 v) {
    asm volatile("st.global.v4.b32 [%0], {%1,%2,%3,%4};" :: "l"(p), "r"(v.x), "r"(v.y), "r"(v.z), "r"(v.w) : "memory");
}
__device__ __forceinline__ unsigned pack4(unsigned a, unsigned b, unsigned c, unsigned d) {
    unsigned lo, r;
    asm("cvt.pack.sat.s8.s32.b32 %0, %1, %2, 0;" : "=r"(lo) : "r"(d), "r"(c));
    asm("cvt.pack.sat.s8.s32.b32 %0, %1, %2, %3;" : "=r"(r) : "r"(b), "r"(a), "r"(lo));
    return r;
}
__device__ __forceinline__ uint32_t mapa(uint32_t a, uint32_t r) {
    uint32_t o;
    asm("mapa.shared::cluster.u32 %0, %1, %2;" : "=r"(o) : "r"(a), "r"(r));
    return o;
}
__device__ __forceinline__ unsigned clk() {
    unsigned t;
    asm volatile("mov.u32 %0, %clock;" : "=r"(t));
    return t;
}
__device__ __forceinline__ void cluster_arrive() { asm volatile("barrier.cluster.arrive.relaxed.aligned;" ::: "memory"); }
__device__ __forceinline__ void cluster_wait() { asm volatile("barrier.cluster.wait.aligned;" ::: "memory"); }
__device__ __forceinline__ void fence_init() { asm volatile("fence.mbarrier_init.release.cluster;" ::: "memory"); }
__device__ __forceinline__ void flag_add(unsigned* p) { asm volatile("red.relaxed.gpu.global.add.u32 [%0], 1;" :: "l"(p) : "memory"); }
__device__ __forceinline__ void raw_load(const void* map, int y, int z, uint32_t dst, uint32_t bar) {
    asm volatile("cp.async.bulk.tensor.3d.shared::cluster.global.tile.mbarrier::complete_tx::bytes [%0], [%1, {0, %2, %3}], [%4];"
                 :: "r"(dst), "l"(map), "r"(y), "r"(z), "r"(bar) : "memory");
}
__device__ __forceinline__ void tile_load(Scratch* sc, uint32_t dst, int tile, uint32_t bar) {
    asm volatile("cp.async.bulk.shared::cluster.global.mbarrier::complete_tx::bytes [%0], [%1], %2, [%3];"
                 :: "r"(dst), "l"((const char*)sc->s8 + tile * 8192), "r"(8192), "r"(bar) : "memory");
}
__device__ __forceinline__ void tile_store(const void* map, int x, int y, uint32_t src) {
    asm volatile("cp.async.bulk.tensor.2d.global.shared::cta.tile.bulk_group [%0, {%1, %2}], [%3];"
                 :: "l"(map), "r"(x), "r"(y), "r"(src) : "memory");
}
__device__ __forceinline__ void st_async(uint32_t a, uint32_t v, uint32_t bar) {
    asm volatile("st.async.weak.shared::cluster.mbarrier::complete_tx::bytes.b32 [%0], %1, [%2];" :: "r"(a), "r"(v), "r"(bar) : "memory");
}
__device__ __forceinline__ void red_async(uint32_t a, int v, uint32_t bar) {
    asm volatile("red.async.relaxed.cluster.shared::cluster.mbarrier::complete_tx::bytes.add.s32 [%0], %1, [%2];" :: "r"(a), "r"(v), "r"(bar) : "memory");
}
__device__ __forceinline__ void red_shared(uint32_t a, int v) { asm volatile("red.shared.add.s32 [%0], %1;" :: "r"(a), "r"(v) : "memory"); }
__device__ __forceinline__ int sum4(unsigned v, int c) { return __dp4a((int)v, 0x01010101, c); }

constexpr uint32_t DESC_A_HI = 0x80000000u | (512 >> 4);
constexpr uint32_t DESC_B_HI = 512 >> 4;
template <int NR> __device__ __forceinline__ void wgmma_n160(int (&d)[NR], uint32_t alo, uint32_t blo, int scale_d) {
    asm volatile("{\n.reg .pred p;\n.reg .b64 da, db;\nsetp.ne.b32 p, %82, 0;\n"
        "mov.b64 da, {%80, %83};\nmov.b64 db, {%81, %84};\n"
        "wgmma.mma_async.sync.aligned.m64n160k32.s32.s8.s8 "
        "{%0, %1, %2, %3, %4, %5, %6, %7, %8, %9, %10, %11, %12, %13, %14, %15, "
        "%16, %17, %18, %19, %20, %21, %22, %23, %24, %25, %26, %27, %28, %29, %30, %31, "
        "%32, %33, %34, %35, %36, %37, %38, %39, %40, %41, %42, %43, %44, %45, %46, %47, "
        "%48, %49, %50, %51, %52, %53, %54, %55, %56, %57, %58, %59, %60, %61, %62, %63, "
        "%64, %65, %66, %67, %68, %69, %70, %71, %72, %73, %74, %75, %76, %77, %78, %79}, "
        "da, db, p;\n}\n"
        : "+r"(d[0]), "+r"(d[1]), "+r"(d[2]), "+r"(d[3]), "+r"(d[4]), "+r"(d[5]), "+r"(d[6]), "+r"(d[7]),
          "+r"(d[8]), "+r"(d[9]), "+r"(d[10]), "+r"(d[11]), "+r"(d[12]), "+r"(d[13]), "+r"(d[14]), "+r"(d[15]),
          "+r"(d[16]), "+r"(d[17]), "+r"(d[18]), "+r"(d[19]), "+r"(d[20]), "+r"(d[21]), "+r"(d[22]), "+r"(d[23]),
          "+r"(d[24]), "+r"(d[25]), "+r"(d[26]), "+r"(d[27]), "+r"(d[28]), "+r"(d[29]), "+r"(d[30]), "+r"(d[31]),
          "+r"(d[32]), "+r"(d[33]), "+r"(d[34]), "+r"(d[35]), "+r"(d[36]), "+r"(d[37]), "+r"(d[38]), "+r"(d[39]),
          "+r"(d[40]), "+r"(d[41]), "+r"(d[42]), "+r"(d[43]), "+r"(d[44]), "+r"(d[45]), "+r"(d[46]), "+r"(d[47]),
          "+r"(d[48]), "+r"(d[49]), "+r"(d[50]), "+r"(d[51]), "+r"(d[52]), "+r"(d[53]), "+r"(d[54]), "+r"(d[55]),
          "+r"(d[56]), "+r"(d[57]), "+r"(d[58]), "+r"(d[59]), "+r"(d[60]), "+r"(d[61]), "+r"(d[62]), "+r"(d[63]),
          "+r"(d[64]), "+r"(d[65]), "+r"(d[66]), "+r"(d[67]), "+r"(d[68]), "+r"(d[69]), "+r"(d[70]), "+r"(d[71]),
          "+r"(d[72]), "+r"(d[73]), "+r"(d[74]), "+r"(d[75]), "+r"(d[76]), "+r"(d[77]), "+r"(d[78]), "+r"(d[79])
        : "r"(alo), "r"(blo), "r"(scale_d), "r"(DESC_A_HI), "r"(DESC_B_HI));
}
template <int NR> __device__ __forceinline__ void wgmma_t128(int (&d)[NR], uint32_t alo, uint32_t blo, int scale_d) {
    asm volatile("{\n.reg .pred p;\n.reg .b64 da, db;\nsetp.ne.b32 p, %66, 0;\n"
        "mov.b64 da, {%64, %67};\nmov.b64 db, {%65, %68};\n"
        "wgmma.mma_async.sync.aligned.m64n128k32.s32.s8.s8 "
        "{%0, %1, %2, %3, %4, %5, %6, %7, %8, %9, %10, %11, %12, %13, %14, %15, "
        "%16, %17, %18, %19, %20, %21, %22, %23, %24, %25, %26, %27, %28, %29, %30, %31, "
        "%32, %33, %34, %35, %36, %37, %38, %39, %40, %41, %42, %43, %44, %45, %46, %47, "
        "%48, %49, %50, %51, %52, %53, %54, %55, %56, %57, %58, %59, %60, %61, %62, %63}, "
        "da, db, p;\n}\n"
        : "+r"(d[0]), "+r"(d[1]), "+r"(d[2]), "+r"(d[3]), "+r"(d[4]), "+r"(d[5]), "+r"(d[6]), "+r"(d[7]),
          "+r"(d[8]), "+r"(d[9]), "+r"(d[10]), "+r"(d[11]), "+r"(d[12]), "+r"(d[13]), "+r"(d[14]), "+r"(d[15]),
          "+r"(d[16]), "+r"(d[17]), "+r"(d[18]), "+r"(d[19]), "+r"(d[20]), "+r"(d[21]), "+r"(d[22]), "+r"(d[23]),
          "+r"(d[24]), "+r"(d[25]), "+r"(d[26]), "+r"(d[27]), "+r"(d[28]), "+r"(d[29]), "+r"(d[30]), "+r"(d[31]),
          "+r"(d[32]), "+r"(d[33]), "+r"(d[34]), "+r"(d[35]), "+r"(d[36]), "+r"(d[37]), "+r"(d[38]), "+r"(d[39]),
          "+r"(d[40]), "+r"(d[41]), "+r"(d[42]), "+r"(d[43]), "+r"(d[44]), "+r"(d[45]), "+r"(d[46]), "+r"(d[47]),
          "+r"(d[48]), "+r"(d[49]), "+r"(d[50]), "+r"(d[51]), "+r"(d[52]), "+r"(d[53]), "+r"(d[54]), "+r"(d[55]),
          "+r"(d[56]), "+r"(d[57]), "+r"(d[58]), "+r"(d[59]), "+r"(d[60]), "+r"(d[61]), "+r"(d[62]), "+r"(d[63])
        : "r"(alo), "r"(blo), "r"(scale_d), "r"(DESC_B_HI), "r"(DESC_A_HI));
}


__device__ __forceinline__ void wg_fence() { asm volatile("wgmma.fence.sync.aligned;" ::: "memory"); }
__device__ __forceinline__ void wg_commit() { asm volatile("wgmma.commit_group.sync.aligned;" ::: "memory"); }
template <int N> __device__ __forceinline__ void wg_wait() { asm volatile("wgmma.wait_group.sync.aligned %0;" :: "n"(N) : "memory"); }

__host__ __device__ constexpr int unit_of(int X1, int piece, int slab) {
    return piece < 2 ? (slab < X1 ? 2 * slab + piece : (piece ? 16 : X1) + slab) : 32 + (piece - 2) * 8 + (slab >> 1);
}
__host__ __device__ constexpr int col_of(int G) { return G == 4 ? 256 : (G > 4 && G < 9) ? 32 * G - 32 : 32 * G; }
struct BJob { int u, slab, G, pos; };
__host__ __device__ constexpr BJob decode_b(int X1, int q) {
    BJob j = {};
    if (q < 160) {
        j.u = q / 5; j.pos = q - j.u * 5;
        const int piece = j.u < 2 * X1 ? (j.u & 1) : (j.u >= X1 + 16);
        j.slab = j.u < 2 * X1 ? (j.u >> 1) : j.u - (piece ? 16 : X1);
        j.G = piece * 5 + j.pos;
    } else {
        q -= 160;
        j.u = 32 + (q >> 2); j.pos = q & 3;
        j.slab = (q >> 1) & 15;
        j.G = 10 + (q >> 5) * 2 + (q & 1);
    }
    return j;
}
__host__ __device__ constexpr int fb_of(int X1, int u) {
    return u < 2 * X1 ? (u & 1) * 32 + (u >> 1) : u < X1 + 16 ? u - X1 : u < 32 ? 16 + u : u < 40 ? u - 16 : u < 48 ? u + 8 : u - 24;
}
__host__ __device__ constexpr uint64_t slot_table(int X1, int piece) {
    uint64_t t = 0;
    for (int s = 0; s < 16; s++) t |= (uint64_t)(unit_of(X1, piece, s) % NSLOT) << (4 * s);
    return t;
}
template <bool k2> __device__ __forceinline__ int stage_w(int t) { return (k2 && t < 9) ? SM_A + (7 + t) * 8192 : SM_STG + (t % 3) * 8192; }
template <bool k2> __host__ __device__ constexpr int ford(int g, int m) {
    return k2 ? g * 5 + m : g ? (m ? 4 + m : 2) : (m < 2 ? m : m < 4 ? m + 1 : 9);
}
template <bool k2> __host__ __device__ constexpr int turn(int n) { return (n + (!k2 && n >= 5)) % 3; }
template <bool k2> __host__ __device__ constexpr uint64_t ford_table() {
    uint64_t t = 0;
    for (int g = 0; g < 2; g++) for (int m = 0; m < 5; m++) t |= (uint64_t)(g * 8 + m) << (4 * ford<k2>(g, m));
    return t;
}
struct Maps { CUtensorMap m[4]; };

__device__ __forceinline__ uint32_t bf2_mul(uint32_t a, uint32_t b) { asm("mul.rn.bf16x2 %0, %0, %1;" : "+r"(a) : "r"(b)); return a; }
__device__ __forceinline__ uint32_t epi(int a, int b, uint32_t zc, uint32_t sx, uint32_t sw, uint32_t bi) {
    uint32_t v;
    float fa = __int2float_rn(a), fb = __int2float_rn(b);
    asm("cvt.rn.bf16x2.f32 %0, %1, %2;" : "=r"(v) : "f"(fb), "f"(fa));
    if (CFG_EPI == 3) {
        asm("fma.rn.bf16x2 %0, %0, %1, %2;" : "+r"(v) : "r"(sw), "r"(zc));
        return v;
    }
    asm("sub.rn.bf16x2 %0, %0, %1;" : "+r"(v) : "r"(zc));
    if (CFG_EPI == 0) {
        v = bf2_mul(bf2_mul(v, sx), sw);
        asm("add.rn.bf16x2 %0, %0, %1;" : "+r"(v) : "r"(bi));
    } else {
        asm("fma.rn.bf16x2 %0, %0, %1, %2;" : "+r"(v) : "r"(sw), "r"(bi));
    }
    return v;
}
__device__ __forceinline__ uint32_t zero_term(int lo, int hi, float zx) {
    uint32_t z;
    asm("cvt.rn.bf16x2.f32 %0, %1, %2;" : "=r"(z) : "f"(__bfloat162float(__float2bfloat16_rn((float)hi)) * zx),
                                                    "f"(__bfloat162float(__float2bfloat16_rn((float)lo)) * zx));
    return z;
}
__device__ __forceinline__ uint32_t fold(uint32_t z, uint32_t sw, uint32_t bi) {
    if (CFG_EPI == 3) asm("fma.rn.bf16x2 %0, %1, %2, %3;" : "=r"(z) : "r"(z ^ 0x80008000u), "r"(sw), "r"(bi));
    return z;
}
__device__ __forceinline__ float ld_zx(const int* zero_x) { return __bfloat162float(__float2bfloat16_rn((float)__ldg(zero_x))); }
struct Par { uint4 zc, sw, bi; };
__device__ __forceinline__ Par ld_par(uint32_t p) { return {lds128(p), lds128(p + TN * 2), CFG_EPI == 3 ? uint4{} : lds128(p + TN * 4)}; }
__device__ __forceinline__ uint4 epi_row(const int (&a)[WA / 2], int o, const Par& p, uint32_t sx2) {
    uint4 r;
    r.x = epi(a[o + 0], a[o + 4], p.zc.x, sx2, p.sw.x, p.bi.x);
    r.y = epi(a[o + 8], a[o + 12], p.zc.y, sx2, p.sw.y, p.bi.y);
    r.z = epi(a[o + 1], a[o + 5], p.zc.z, sx2, p.sw.z, p.bi.z);
    r.w = epi(a[o + 9], a[o + 13], p.zc.w, sx2, p.sw.w, p.bi.w);
    return r;
}
__device__ __forceinline__ void scale_bias(const __nv_bfloat16* scale_x, const __nv_bfloat16* scale_w, const __nv_bfloat16* bias, uint32_t sb, int lane) {
    const uint32_t sx2 = (uint32_t)__ldg((const unsigned short*)scale_x) * 0x10001u;
#pragma unroll
    for (int i = lane; i < TN / 4; i += 32) {
        const bool hi = i >= TN / 8;
        uint4 v = __ldg((const uint4*)(hi ? bias : scale_w) + (hi ? i - TN / 8 : i));
        if (CFG_EPI && !hi) v = {bf2_mul(v.x, sx2), bf2_mul(v.y, sx2), bf2_mul(v.z, sx2), bf2_mul(v.w, sx2)};
        sts128(sb + SM_PAR + TN * 2 + i * 16, v);
    }
    __syncwarp();
    if (elect_one()) mbar_arrive(sb + SM_BAR + B_SW * 8);
}
template <bool k2> __device__ __forceinline__ int release_addr(uint32_t sb, int u, int lq) {
    const int v = u + NSLOT, q = (k2 ? (v >> 1) * 16 + (v & 1) : 5 * v - (v > 34 ? 3 : 0)) + lq;
    return mapa(sb | (q & 0x1F0), q & 15) | (q & 0x80000000);
}
__device__ __forceinline__ void release(int a) {
    asm volatile("{\n.reg .pred p;\nsetp.ge.s32 p, %0, 0;\n@p mbarrier.arrive.shared::cluster.b64 _, [%0 + %1];\n}" :: "r"(a), "n"(SM_BAR + B_GO * 8) : "memory");
}
__device__ __forceinline__ unsigned read_back(const uint4* d, int lane) { return ld_flag((const unsigned*)(d - lane + ((lane + 10) & 15) * 8 + 6)); }
__device__ __forceinline__ void publish(unsigned rb, unsigned mine, unsigned* flag) {
    if (__shfl_sync(~0u, rb ^ mine, 6)) asm volatile("fence.acq_rel.gpu;" ::: "memory");
    if (elect_one()) flag_add(flag);
}
#define CV_B(m, f)                                                                                                      \
    {                                                                                                                   \
        uint4 v0 = lds128(rdB + m * 512), v1 = lds128(rdB + m * 512 + 128);                                             \
        uint4 v2 = lds128(rdB + m * 512 + 256), v3 = lds128(rdB + m * 512 + 384);                                       \
        o[0].f = pack4(v0.x, v1.x, v2.x, v3.x); o[1].f = pack4(v0.y, v1.y, v2.y, v3.y);                                 \
        o[2].f = pack4(v0.z, v1.z, v2.z, v3.z); o[3].f = pack4(v0.w, v1.w, v2.w, v3.w);                                 \
    }

__device__ __forceinline__ void last_columns(Scratch* sc, const Maps& maps, const __nv_bfloat16* scale_x, const int* zero_x, const __nv_bfloat16* scale_w,
                                             const __nv_bfloat16* bias, uint32_t sb, int warp, int lane, unsigned t0) {
    constexpr int C_FULL = 0, C_EMPTY = 32, C_RAW = 64, C_GO = 80, C_PEER = 81, D3 = CFG_D3;
    const uint32_t bars = sb + SM_BAR;
    const int j = blockIdx.x & 3;
    while ((int)(t0 + CFG_T3 - clk()) > 0) ;
    const int s0 = (j & 1) * 8 + (warp >> 1) * 2;
    if (warp < 8) {
        if (elect_one()) {
#pragma unroll
            for (int i = 0; i < 2; i++) {
                const uint32_t bar = bars + (C_RAW + warp * 2 + i) * 8;
                mbar_init(bar, 1); mbar_expect_tx(bar, 8192);
                raw_load(maps.m + 1, (s0 + (i ^ (j >> 1))) * 64, N_ / 32 - 2 + (warp & 1), sb + SM_A + (warp * 2 + i) * 8192, bar);
            }
#pragma unroll
            for (int i = 0; i < 4; i++) { mbar_init(bars + (C_FULL + warp * 4 + i) * 8, 1); mbar_expect_tx(bars + (C_FULL + warp * 4 + i) * 8, 16384); }
#pragma unroll
            for (int i = 0; i < 4; i++) mbar_init(bars + (C_EMPTY + warp * 4 + i) * 8, 4);
            if (warp == 0) {
                mbar_init(bars + C_GO * 8, 8);
                mbar_init(bars + C_PEER * 8, 1); mbar_expect_tx(bars + C_PEER * 8, 32768 + 4096);
            }
        }
        if (warp < 2) sts32(sb + SM_PAR + threadIdx.x * 4, 0);
        fence_init();
    }
    __syncthreads();
    cluster_arrive();
    cluster_wait();
    if (warp >= 8) {
        asm volatile("setmaxnreg.dec.sync.aligned.u32 40;");
        if (warp < 12) {
            const unsigned ep = (ld_flag(epoch(sc, j * 4, 8)) + 1) * 4;
            const int mb = j * 4 + warp - 8, wg = (warp >> 1) & 1;
            unsigned rdy = 0;
            mbar_wait(bars + (wg ? C_EMPTY : C_GO) * 8);
#pragma unroll 1
            for (int s = 0; s < 16; s++) {
                for (int it = 0; !((rdy >> s) & 1); it++) {
                    rdy = __ballot_sync(~0u, (int)(ld_flag(sc->flag + mb * 32 + (lane & 15)) - ep) >= 0);
                    if (it > (1 << 22)) __trap();
                }
                if (s >= D3) mbar_wait(bars + (C_EMPTY + (s - (s < CFG_S3 ? D3 : CFG_D4)) * 2 + wg) * 8);
                if (elect_one()) tile_load(sc, sb + SM_A + ((s & 3) * 4 + warp - 8) * 8192, mb * 16 + s, bars + (C_FULL + s * 2 + wg) * 8);
            }
        }
    } else {
        asm volatile("setmaxnreg.inc.sync.aligned.u32 200;");
        const int wg = warp >> 2, w = warp & 3;
        const int c0 = (w >> 1) * 32 + (lane >> 2) * 4 + (w & 1) * 2, r0 = (lane & 3) * 2;
        const uint32_t sx2 = (uint32_t)__ldg((const unsigned short*)scale_x) * 0x10001u;
        uint32_t sw = __ldg((const unsigned*)(scale_w + N_ - WB + c0));
        const uint32_t bi = __ldg((const unsigned*)(bias + N_ - WB + c0));
        const float zxf = ld_zx(zero_x);
        int cs[4] = {0, 0, 0, 0};
        const uint32_t peer = mapa(sb, (j & 1) ^ 1);
#pragma unroll 1
        for (int i = 0; i < 2; i++) {
            const uint32_t rdB = sb + SM_A + (warp * 2 + i) * 8192 + (lane >> 3) * 2048 + (lane & 7) * 16;
            const uint32_t wr = SM_RING + (s0 + (i ^ (j >> 1))) * 4096 + (warp & 1) * 2048 + lane * 16;
            mbar_wait(bars + (C_RAW + warp * 2 + i) * 8);
            uint4 o[4];
            CV_B(0, x) CV_B(1, y) CV_B(2, z) CV_B(3, w)
#pragma unroll
            for (int k = 0; k < 4; k++) {
                sts128(sb + wr + k * 512, o[k]);
                asm volatile("st.async.weak.shared::cluster.mbarrier::complete_tx::bytes.v4.b32 [%0], {%1,%2,%3,%4}, [%5];"
                             :: "r"(peer + wr + k * 512), "r"(o[k].x), "r"(o[k].y), "r"(o[k].z), "r"(o[k].w), "r"(peer + SM_BAR + C_PEER * 8) : "memory");
                cs[k] = sum4(o[k].x, sum4(o[k].y, sum4(o[k].z, sum4(o[k].w, cs[k]))));
            }
        }
        __syncwarp();
        if (elect_one()) mbar_arrive(bars + C_GO * 8);
#pragma unroll
        for (int k = 0; k < 4; k++) {
            const uint32_t ca = SM_PAR + ((warp & 1) * 32 + (lane & 7) * 4 + k) * 4;
            red_shared(sb + ca, cs[k]);
            red_async(peer + ca, cs[k], peer + SM_BAR + C_PEER * 8);
        }
        mbar_wait(bars + C_PEER * 8);
        asm volatile("fence.proxy.async.shared::cta;" ::: "memory");
        asm volatile("bar.sync 1, 256;" ::: "memory");
        if (CFG_EPI) sw = bf2_mul(sw, sx2);
        const uint32_t zc = fold(zero_term(lds32(sb + SM_PAR + c0 * 4), lds32(sb + SM_PAR + c0 * 4 + 4), zxf), sw, bi);
        const uint32_t sd = (sb & 0x3FFFF) >> 4;
        int t[2][64];
        wg_fence();
#pragma unroll 1
        for (int s = 0; s < 16; s++) {
            const uint32_t db = ((sd + (SM_RING >> 4)) | (8 << 16)) + s * 256, da = ((sd + (SM_A >> 4)) | (1 << 16)) + ((s & 3) * 4 + wg * 2) * 512;
            mbar_wait(bars + (C_FULL + s * 2 + wg) * 8);
            wgmma_t128(t[0], db, da, s);
            wgmma_t128(t[1], db, da + 512, s);
            wgmma_t128(t[0], db + 16, da + 2, 1);
            wgmma_t128(t[1], db + 16, da + 514, 1);
            wg_commit();
            wg_wait<0>();
            if (elect_one()) mbar_arrive(bars + (C_EMPTY + s * 2 + wg) * 8);
        }
        asm volatile("bar.sync %0, 128;" :: "r"(3 + wg) : "memory");
        const uint32_t st0 = sb + SM_A + wg * 16384 + r0 * 128 + (((c0 >> 3) ^ r0) << 4) + (c0 & 7) * 2;
#pragma unroll
        for (int h = 0; h < 4; h++) {
            const uint32_t off = (h >> 1) * 32768 + (h & 1) * 8192;
#pragma unroll
            for (int q = 0; q < 8; q++) {
                const int o = (h & 1) * 32 + q * 4;
                sts32(st0 + off + q * 1024, epi(t[h >> 1][o], t[h >> 1][o + 2], zc, sx2, sw, bi));
                sts32((st0 ^ (5 * 128 + 5 * 16)) + off + q * 1024, epi(t[h >> 1][o + 1], t[h >> 1][o + 3], zc, sx2, sw, bi));
            }
            asm volatile("fence.proxy.async.shared::cta;" ::: "memory");
            asm volatile("bar.sync %0, 128;" :: "r"(3 + wg) : "memory");
            if (w == 0 && elect_one()) tile_store(maps.m + 2, N_ - WB, j * 512 + wg * 256 + h * 64, sb + SM_A + wg * 16384 + off);
        }
        if (w == 0) {
            asm volatile("cp.async.bulk.commit_group;" ::: "memory");
            asm volatile("cp.async.bulk.wait_group.read 0;" ::: "memory");
        }
        asm volatile("bar.sync 1, 256;" ::: "memory");
        if (threadIdx.x == 0) flag_add(epoch(sc, j * 4, 8));
    }
}

template <bool k2>
__global__ void __cluster_dims__(k2 ? 2 : CS, 1, 1) __launch_bounds__(512, 1)
w8a8_kernel(Scratch* sc, const char* __restrict__ qx, const char* __restrict__ qw, const __nv_bfloat16* __restrict__ scale_x, const int* __restrict__ zero_x,
            const __nv_bfloat16* __restrict__ scale_w, const __nv_bfloat16* __restrict__ bias, const __grid_constant__ Maps maps) {
    extern __shared__ __align__(1024) unsigned char smem_raw[];
    constexpr int NBJ = k2 ? 12 : 14, NF = NBJ, NU = k2 ? 40 : 48;
    constexpr int X1 = k2 ? CFG_X2 : CFG_X1;
    const int b = blockIdx.x + (k2 ? NCTA : 0), r = b & 15, c = k2 ? NCL : b >> 4;
    const unsigned tc = clk();
    if (!k2) {
        const int a = (r * NCL + c) ^ REV;
        const unsigned off = ((a & 63) * 32 + (threadIdx.x >> 1)) * (K_ * 4) + (a >> 6) * 256 + (threadIdx.x & 1) * 128;
        asm volatile("{\n.reg .pred p;\n.reg .b64 a;\nsetp.lt.u32 p, %2, 64;\n@!p bra PF_DONE;\ncvt.u64.u32 a, %1;\nadd.u64 a, a, %0;\nprefetch.global.L2 [a];\nPF_DONE:\n}"
                     :: "l"(qx), "r"(off), "r"(threadIdx.x));
    }
    const uint32_t sb = (uint32_t)__cvta_generic_to_shared(smem_raw);
    const uint32_t bars = sb + SM_BAR;
    const unsigned tw = __shfl_sync(~0u, (tc & ~15u) | threadIdx.x >> 5, 0), t0 = tw + (k2 ? 0 : T0);
    const int warp = tw & 15, lane = threadIdx.x & 31;

    if (!k2 && warp == 12) {
        const int a = r * NCL + c;
        if (elect_one()) {
            mbar_init(bars + (B_RAWA + 3) * 8, 1);
            mbar_expect_tx(bars + (B_RAWA + 3) * 8, 8192);
            raw_load(maps.m, (a >> 6) * 2, ((a ^ REV) & 63) * 32, sb + SM_A + (a < NAJ % NCTA ? 15 : 13) * 8192, bars + (B_RAWA + 3) * 8);
        }
        __syncwarp();
    }
    if (!k2 && (warp >> 1) == 1 && r < CFG_PG) {
        const int a = (NCTA + r * NCL + c) ^ REV;
        const char* p = qx + ((a & 63) * 32 + (warp & 1) * 16 + (lane >> 1)) * (K_ * 4) + (a >> 6) * 256 + (lane & 1) * 128;
        while ((int)(t0 + (16 + r) * P1 - clk()) > 0) ;
        asm volatile("prefetch.global.L2 [%0];" :: "l"(p));
    }
    if (warp == 9 && elect_one()) asm volatile("prefetch.tensormap [%0];" :: "l"(maps.m + 1) : "memory");
    if (k2 && blockIdx.x >= 16) {
        last_columns(sc, maps, scale_x, zero_x, scale_w, bias, sb, warp, lane, t0);
        return;
    }
    if (warp >= 12) {
        const int isw = k2 || warp == 14, t = k2 ? warp - 12 : isw ? 0 : (warp - 11) >> 1;
        const uint32_t bar = bars + ((isw ? B_RAWB : B_RAWA) + 3 + t) * 8;
        if ((k2 || warp != 12) && elect_one()) { mbar_init(bar, 1); mbar_expect_tx(bar, 8192); }
        __syncwarp();
        cluster_arrive();
        const int x = t * 16 + r, a = (x * NCL + c) ^ REV, sx = (x * 26) >> 8;
        static_assert(X1 >= 7, "");
        if ((k2 || warp != 12) && elect_one()) {
            const unsigned te = t0 + (k2 ? sched2(x) : (isw ? time_w(x) : time_x(x)) * P1);
            while ((int)(te - clk()) > 0) ;
            raw_load(maps.m + isw, isw ? sx * 64 : (a >> 6) * 2,
                     isw ? c * (TN / 32) + (int)((0x9765483210ull >> ((x - sx * 10) * 4)) & 15) : (a & 63) * 32,
                     sb + (k2 ? SM_A + 7 * 8192 : isw ? SM_STG : SM_A + 13 * 8192) + (t - (!isw && r * NCL + c < NAJ % NCTA)) * 8192, bar);
        }
        __syncwarp();
        if (!k2 && warp == 15) cluster_wait();
    }
    if (warp < 8) {
        const uint32_t p = bars + warp * 104;
        if (elect_one()) {
#pragma unroll
            for (int i = 0; i < 13; i++) mbar_init(p + i * 8, (!k2 && ((warp == 6 && i == 12) || (warp == 7 && i < 2))) ? 2 : 1);
            static_assert(B_FREE == 90, "");
        }
        __syncwarp();
        const int i = warp * 13 + lane;
        if (lane < 13 && i < B_SW) mbar_expect_tx(p + lane * 8, i >= B_PAR ? (i < B_PAR + 2 ? WA * 2 : WB * 2) : (i & 16) || i >= 48 ? 8192 : WA * 64);
        fence_init();
    }
    if (warp < 8 || warp == 10) cluster_arrive();
    if (!k2 && warp == 10 && lane < CFG_PF7) {
        const int n = b * CFG_PF7 + lane, row = n / 10;
        asm volatile("prefetch.global.L2 [%0];" :: "l"(qw + row * (N_ * 4) + NCL * TN * 4 + (n - row * 10) * 128));
    }

    if (warp < 8) {
        asm volatile("setmaxnreg.inc.sync.aligned.u32 200;");
        const int wg = warp >> 2;
        const uint32_t sd = (sb & 0x3FFFF) >> 4;
        const uint32_t sx2 = (uint32_t)__ldg((const unsigned short*)scale_x) * 0x10001u;
        const uint32_t par = sb + SM_PAR + (lane & 3) * 16 + wg * 256;
        const uint32_t go = bars + B_GO * 8;
        const int w = warp & 3, pq = (lane >> 2) ^ (lane & 4);
        uint32_t so = (w * 16 + pq) * 128 + (((lane & 3) ^ pq) << 4);
        const int c0 = (w >> 1) * 32 + (lane >> 2) * 4 + (w & 1) * 2, r0 = (lane & 3) * 2;
        uint32_t pp = sb + SM_PAR + (2 * WA + wg * WB + c0) * 2, st0 = r0 * 128 + (((c0 >> 3) ^ r0) << 4) + (c0 & 7) * 2;
        uint32_t rq = k2 ? mapa(go + 19 * 16, 1) : mapa(go + (12 + (lane >> 4)) * 16, lane & 15);
        int rk = k2 ? (lane ? 99 : 1) : (lane >> 2) + 1;
        asm volatile("" : "+r"(so), "+r"(pp), "+r"(st0), "+r"(rq), "+r"(rk));
        cluster_wait();
        int a0[WA / 2], a1[WA / 2];
        uint32_t barB = bars + (B_FULLB + wg * 32) * 8;
        int ra = -1;
        const int lq = lane < (k2 ? 1 : 5) ? lane : -1000;
        wg_fence();
        {
            uint64_t tbl = wg ? slot_table(X1, 1) : slot_table(X1, 0);
            uint32_t da = (sd + (SM_A >> 4)) | (1 << 16);
            bool rdy = false;
#pragma unroll 1
            for (int s = 0; s < 16; s++) {
                const uint32_t db = ((sd + (SM_RING >> 4)) | (8 << 16)) + ((uint32_t)tbl & 15) * (SLOT >> 4);
                const bool hold = wg && s == X1;
                if (hold || (!rdy && !mbar_test2(bars + (B_FULLA + s) * 8, barB))) {
                    wg_wait<0>();
                    release(ra); ra = -1;
                    mbar_wait2(bars + (B_FULLA + s) * 8, barB);
                    if (hold) asm volatile("bar.sync 7, 256;" ::: "memory");
                }
                wgmma_n160(a0, da, db, s);
                wgmma_n160(a1, da + 256, db, s);
                wg_commit();
                if (!wg && s == 15) asm volatile("bar.arrive 7, 256;" ::: "memory");
                wg_wait<1>();
                release(ra);
                wgmma_n160(a0, da + 2, db + 16, 1);
                wgmma_n160(a1, da + 258, db + 16, 1);
                wg_commit();
                ra = release_addr<k2>(sb, s < X1 ? 2 * s + wg : (wg ? 16 : X1) + s, lq);
                tbl >>= 4; da += 512; barB += 8;
                rdy = mbar_test2(bars + (B_FULLA + s + 1) * 8, barB);
                if (s < 15) wg_wait<1>();
            }
        }
        mbar_wait2(bars + (B_PAR + wg) * 8, bars + B_SW * 8);
        const Par P0 = ld_par(par), P1 = ld_par(par + 64);
        wg_wait<0>();
        release(ra);
        bool ready = mbar_test(barB);
#define FILL_BEGIN(n0, n1) mbar_wait(bars + (B_FREE + (wg ? n1 : n0)) * 8);                                             \
                           const uint32_t buf = sb + SM_STG + (wg ? (turn<k2>(n1) + NBJ) % 3 : (turn<k2>(n0) + NBJ) % 3) * 8192;
#define FILL_END(n0, n1) __syncwarp();                                                                                  \
                         if (elect_one()) mbar_arrive(bars + (B_FILL + (wg ? turn<k2>(n1) : turn<k2>(n0))) * 8);
#define FILL_PAIR(a, J, P, Q, m, MID)                                                                                   \
        {                                                                                                               \
            const uint4 v0 = epi_row(a, J * 16, P, sx2), v1 = epi_row(a, J * 16 + 2, P, sx2);                           \
            FILL_BEGIN(ford<k2>(0, m), ford<k2>(1, m))                                                                  \
            sts128(buf + so, v0); sts128(buf + so + 1024, v1);                                                          \
            MID                                                                                                         \
            sts128(buf + (so ^ 64), epi_row(a, J * 16 + 16, Q, sx2));                                                   \
            sts128(buf + (so ^ 64) + 1024, epi_row(a, J * 16 + 18, Q, sx2));                                            \
            FILL_END(ford<k2>(0, m), ford<k2>(1, m))                                                                    \
        }
#define NARROW(p)                                                                                                       \
        {                                                                                                               \
            if (!ready) mbar_wait(barB);                                                                                \
            wg_fence();                                                                                                 \
            _Pragma("unroll 1") for (int i = 0; i < 8; i++) {                                                           \
                const uint32_t db = ((sd + (SM_RING >> 4)) | (8 << 16)) + (k2 ? (i > 2 ? i - 3 : i + 4) * (SLOT >> 4) : ((i + 5) & 7) * 512); \
                _Pragma("unroll") for (int kk = 0; kk < 4; kk++)                                                        \
                    wgmma_t128(t, db + (kk >> 1) * 256 + (kk & 1) * 16,                                                 \
                               ((sd + (SM_A >> 4)) | (1 << 16)) + i * 1024 + (kk >> 1) * 512 + (kk & 1) * 2, kk ? 1 : i); \
                wg_commit();                                                                                            \
                barB += 8;                                                                                              \
                mbar_wait(i < 7 ? barB : bars + (B_PAR + p) * 8);                                                       \
                wg_wait<1>();                                                                                           \
                if (p == 2 && rk == i) mbar_arrive_cluster(rq);                                                         \
            }                                                                                                           \
            if (p == 3 || k2) { zc = lds32(pp); sw = lds32(pp + TN * 2); bi = CFG_EPI == 3 ? 0 : lds32(pp + TN * 4); }               \
            wg_wait<0>();                                                                                               \
            if (p == 2 && rk == 8) mbar_arrive_cluster(rq);                                                             \
        }
        Par P2, P3, P;
        FILL_PAIR(a0, 0, P0, P1, 0, P2 = ld_par(par + 128);)
        FILL_PAIR(a1, 0, P0, P1, 1, P3 = ld_par(par + 192);)
        FILL_PAIR(a0, 2, P2, P3, 2, P = ld_par(par + 512 - wg * 192);)
        FILL_PAIR(a1, 2, P2, P3, 3, )
        int t[64];
        uint32_t zc, sw, bi;
        if (!k2 && wg == 0) NARROW(2)
        {
            const uint4 v0 = epi_row(a0, 64, P, sx2), v1 = epi_row(a0, 66, P, sx2);
            FILL_BEGIN(ford<k2>(0, 4), ford<k2>(1, 4))
            const uint32_t s4 = buf + ((so >> 1) & ~63u) + (lane & 3) * 16;
            sts128(s4, v0); sts128(s4 + 512, v1);
            sts128(s4 + 4096, epi_row(a1, 64, P, sx2)); sts128(s4 + 4608, epi_row(a1, 66, P, sx2));
            FILL_END(ford<k2>(0, 4), ford<k2>(1, 4))
        }
        if (!(k2 && wg)) {
            if (k2) NARROW(2) else if (wg) NARROW(3) else { zc = lds32(pp); sw = lds32(pp + TN * 2); bi = CFG_EPI == 3 ? 0 : lds32(pp + TN * 4); }
#define FILL_T(h)                                                                                                       \
            {                                                                                                           \
                FILL_BEGIN((10 + h), (12 + h))                                                                          \
                _Pragma("unroll") for (int j = 0; j < 8; j++) {                                                         \
                    const int o = h * 32 + j * 4;                                                                       \
                    sts32(buf + st0 + j * 1024, epi(t[o], t[o + 2], zc, sx2, sw, bi));                                  \
                    sts32(buf + (st0 ^ (5 * 128 + 5 * 16)) + j * 1024, epi(t[o + 1], t[o + 3], zc, sx2, sw, bi));       \
                }                                                                                                       \
                FILL_END((10 + h), (12 + h))                                                                            \
            }
            FILL_T(0) FILL_T(1)
        }
        if (threadIdx.x == 0) flag_add(epoch(sc, r, c));
    } else {
        const int g = r * NCL + c, na = k2 ? 0 : NAJ / NCTA + (g < NAJ % NCTA);
        int cw = NF;
        if (warp >= 12) {
            asm volatile("setmaxnreg.dec.sync.aligned.u32 80;");
            if (warp < 14) {
                const int c4 = (lane ^ (lane >> 3)) & 3, ln = ((lane >> 2) ^ (lane & 4)) * 2 + (c4 >> 1);
                const uint32_t rd0 = sb + SM_A + 13 * 8192 + ln * 128 + ((((c4 & 1) << 2) ^ (ln & 7)) << 4);
#pragma unroll 1
                for (int t = warp - 12, sl = na == 9 ? t : 2 - 2 * t; t < na; t += 2, sl = sl ? sl - 1 : 2) {
                    const uint32_t rdA = rd0 + sl * 8192;
                    const int a = (t * NCTA + g) ^ REV, f = (a & 60) * 4 + (a >> 6);
                    uint4* const d = sc->s8 + (f * 4 + (a & 3)) * 128 + lane;
                    uint4 o[4];
                    mbar_wait(bars + (B_RAWA + 3 + t) * 8);
#pragma unroll
                    for (int i = 0; i < 4; i++) {
                        uint4 v0 = lds128(rdA + i * 2048), v1 = lds128((rdA ^ 16) + i * 2048);
                        uint4 v2 = lds128((rdA ^ 32) + i * 2048), v3 = lds128((rdA ^ 48) + i * 2048);
                        o[i].x = pack4(v0.x, v0.y, v0.z, v0.w); o[i].y = pack4(v1.x, v1.y, v1.z, v1.w);
                        o[i].z = pack4(v2.x, v2.y, v2.z, v2.w); o[i].w = pack4(v3.x, v3.y, v3.z, v3.w);
                    }
#pragma unroll
                    for (int i = 0; i < 4; i++) stg128(d + i * 32, o[i]);
                    asm volatile("fence.proxy.async.global;" ::: "memory");
                    __syncwarp();
                    const unsigned rb = read_back(d, lane);
                    if (t < 2) cluster_wait();
                    if (elect_one()) mbar_arrive(bars + ((t < na - 3 ? B_RAWA : B_AFREE + 13) + sl) * 8);
                    publish(rb, o[0].x, sc->flag + (a & 60) * 8 + (a >> 6));
                }
                cw = warp - 12;
            }
            if (!k2) {
                const int hw = warp & 1;
                const uint32_t rd0 = sb + SM_STG + hw * 4096 + (lane >> 3) * 1024 + (lane & 7) * 16;
                const int myG = decode_b(X1, (lane & 15) * 16 + r).G;
#pragma unroll 1
                for (int t = warp < 14 ? TA : 0; t < NBJ; t += warp < 14 ? NBJ : t == TA - 1 ? 2 : 1) {
                    const int sl = t % 3;
                    const uint32_t rdB = rd0 + sl * 8192;
                    char* const d = (char*)sc->s8 + (1024 + c * 256 + t * 16 + r) * 2048 + hw * 256 + (lane >> 4) * 128 + (lane & 7) * 16 + (lane & 8);
                    uint2 o[4];
                    mbar_wait(bars + (B_RAWB + 3 + t) * 8);
                    CV_B(0, x) CV_B(1, y)
#pragma unroll
                    for (int i = 0; i < 4; i++) asm volatile("st.global.v2.b32 [%0], {%1,%2};" :: "l"(d + i * 512), "r"(o[i].x), "r"(o[i].y) : "memory");
                    if (t == 0 && warp == 14) cluster_wait();
                    if (elect_one()) mbar_arrive(bars + (t >= NBJ - 3 ? B_FREE + t - (NBJ - 3) : B_RAWB + sl) * 8);
                    asm volatile("fence.proxy.async.global;" ::: "memory");
                    __syncwarp();
                    if (elect_one()) mbar_arrive(bars + (B_GO + t * 2) * 8);
                    int cs[4];
#pragma unroll
                    for (int i = 0; i < 4; i++) cs[i] = sum4(o[i].x, sum4(o[i].y, 0));
                    const int p01 = cs[0] + cs[1] * 65536, p23 = cs[2] + cs[3] * 65536;
                    const bool h = lane & 16;
                    int x = (h ? p23 : p01) + __shfl_xor_sync(~0u, h ? p01 : p23, 16);
                    x += __shfl_xor_sync(~0u, x, 8);
                    const int lo = (int)(short)x, v = (lane & 8) ? (x - lo) >> 16 : lo;
                    const int G = __shfl_sync(~0u, myG, t);
                    if (G != r) {
                        red_async(mapa(sb + SM_CS + lane * 4, G), v, mapa(bars + B_CS * 8, G));
                    } else {
                        red_shared(sb + SM_CS + lane * 4, v);
                        __syncwarp();
                        if (elect_one()) mbar_arrive(bars + B_CS * 8);
                    }
                }
            } else {
                const uint32_t rd0 = sb + (lane >> 3) * 2048 + (lane & 7) * 16;
                const BJob mb = decode_b(X1, (lane & 15) * 16 + r);
                const int myG = mb.G | mb.u << 8;
#pragma unroll 1
                for (int t = warp - 12; t < NBJ; t += 4) {
                    const uint32_t rdB = rd0 + stage_w<k2>(t);
                    uint4* const d = sc->s8 + (1024 + c * 256 + t * 16 + r) * 128 + lane;
                    uint4 o[4];
                    mbar_wait(bars + (B_RAWB + 3 + t) * 8);
                    CV_B(0, x) CV_B(1, y) CV_B(2, z) CV_B(3, w)
#pragma unroll
                    for (int i = 0; i < 4; i++) stg128(d + i * 32, o[i]);
                    if (t < 4) cluster_wait();
                    if (elect_one()) mbar_arrive(bars + (B_FREE + t - (NBJ - 3)) * 8);
                    asm volatile("fence.proxy.async.global;" ::: "memory");
                    __syncwarp();
                    const unsigned rb = read_back(d, lane), ep = ld_flag(epoch(sc, r, c));
                    int cs[4];
#pragma unroll
                    for (int i = 0; i < 4; i++) cs[i] = sum4(o[i].x, sum4(o[i].y, sum4(o[i].z, sum4(o[i].w, 0))));
                    const bool h = lane & 16, odd = lane & 8;
                    int x = (h ? cs[2] : cs[0]) + __shfl_xor_sync(~0u, h ? cs[0] : cs[2], 16);
                    int y = (h ? cs[3] : cs[1]) + __shfl_xor_sync(~0u, h ? cs[1] : cs[3], 16);
                    const int v = (odd ? y : x) + __shfl_xor_sync(~0u, odd ? x : y, 8);
                    const int gu = __shfl_sync(~0u, myG, t);
                    publish(rb, o[0].x, sc->flag + F_W + (gu >> 8));
                    const int old = atomicAdd(sc->cs[ep & 1] + col_of(gu & 255) + (lane & 7) * 4 + (lane >> 3), v);
                    if (old == 0x7FFFFFFF) sc->sink[0] = old;
                    __syncwarp();
                    if (elect_one()) flag_add(sc->flag + F_CS + (gu & 255) / 5);
                }
            }
        } else {
            asm volatile("setmaxnreg.dec.sync.aligned.u32 32;");
            if (warp == 11) {
                if (elect_one()) {
#pragma unroll
                    for (int i = 0; i < (k2 ? NU / 2 : NBJ); i++)
                        mbar_init(bars + (B_GO + i * 2) * 8, k2 ? (i * 2 + (r & 1) >= NSLOT ? 9 : 1)
                                                         : 2 + 4 * CS * ((i * 16 + r >= NSLOT * 5) + (i == 10 && r >= 12 && r < 15)));
#pragma unroll
                    for (int i = 0; i < 3; i++) mbar_init(bars + (B_FILL + i) * 8, 4);
                }
                const int u2 = lane * 2 + (r & 1), q = k2 ? (u2 < 32 ? 5 * u2 : 4 * u2 + 32) : (lane & 15) * 16 + r;
                const BJob bj = decode_b(X1, q);
                unsigned seen = 0;
                if (!k2) {
                    const int nself = __popc(__ballot_sync(~0u, lane < NBJ && bj.G == r));
                    sts32(sb + SM_CS + lane * 4, 0);
                    if (lane == 0) {
                        mbar_init(bars + B_CS * 8, 1 + 2 * nself);
                        mbar_expect_tx(bars + B_CS * 8, (16 - nself) * 256);
                    }
                    seen = lds32(sb + SM_CS + lane * 4);
                }
                fence_init();
                asm volatile("barrier.cluster.arrive.relaxed.aligned;" :: "r"(seen) : "memory");
                const char* src = (const char*)sc->s8 + (1024 + c * 256 + q) * 2048;
                const uint32_t dst = sb + SM_RING + ((!k2 && q >= 160) ? ((q + 20) & 31) * 2048 : (bj.u % NSLOT) * SLOT + bj.pos * 2048);
                const uint32_t fb = bars + (B_FULLB + fb_of(X1, bj.u)) * 8;
                cluster_wait();
                if (!k2) scale_bias(scale_x, scale_w + c * TN, bias + c * TN, sb, lane);
#pragma unroll 1
                for (int i = 0; i < (k2 ? NU / 2 : NBJ); i++) {
                    mbar_wait(bars + (B_GO + i * 2) * 8);
                    if (lane == i) {
                        asm volatile("cp.async.bulk.shared::cluster.global.mbarrier::complete_tx::bytes.multicast::cluster [%0], [%1], %2, [%3], %4;"
                                     :: "r"(dst), "l"(src), "r"(k2 ? (u2 < 32 ? SLOT : 8192) : 2048), "r"(fb), "h"((uint16_t)(k2 ? 3 : 0xFFFF)) : "memory");
                    }
                    __syncwarp();
                }
            } else if (warp == 10) {
                const unsigned ep = (__shfl_sync(~0u, ld_flag(sc->flag + r * 32 + (lane < 16 ? lane : 16 + c)), 16) + 1) * 4;
                const unsigned* f = sc->flag + r * 32 + (lane & 15);
                bool dn = lane >= 16;
                const bool fr = lane < (k2 ? 7 : 13);
                cluster_wait();
                for (int it = 0;; it++) {
                    const unsigned v = ld_flag(f);
                    if (!dn && (int)(v - ep) >= 0 && (fr || mbar_test(bars + (B_AFREE + lane) * 8))) {
                        dn = true;
                        tile_load(sc, sb + SM_A + lane * 8192, r * 16 + lane, bars + (B_FULLA + lane) * 8);
                    }
                    if (__all_sync(~0u, dn)) break;
                    if (it > (1 << 22)) __trap();
                }
            } else {
                const bool isw = warp == 9;
                const uint32_t rb = bars + (isw ? B_RAWB : B_RAWA) * 8;
                if (elect_one()) {
#pragma unroll
                    for (int i = 0; i < 13; i++) if (i < 3 || i >= (k2 ? 7 : 6)) mbar_init(rb + i * 8, (i < 3 && isw && !k2) ? 2 : 1);
                    if (isw) {
#pragma unroll
                        for (int i = 13; i < 17; i++) mbar_init(rb + i * 8, 1);
                        if (!k2) { mbar_init(rb + 4 * 8, 1); mbar_init(rb + 5 * 8, 1); }
                    }
                }
                __syncwarp();
                const int nj = isw ? NBJ : na, j0 = k2 ? 4 : isw ? 1 : 3;
                if (lane >= j0 && lane < nj) mbar_expect_tx(rb + (3 + lane) * 8, 8192);
                fence_init();
                cluster_arrive();
                const unsigned e0 = k2 ? ld_flag(epoch(sc, r, c)) : 0;
                const int k = lane / 3, x = lane * 16 + r;
                int sl = lane - k * 3, y, z, T;
                if (isw) {
                    const BJob bj = decode_b(X1, x & 255);
                    y = bj.slab * 64; z = (c * TN + col_of(bj.G)) >> 5; T = time_w(x);
                } else {
                    const int a = (lane * NCTA + g) ^ REV;
                    y = (a >> 6) * 2; z = (a & 63) * 32; T = time_x(x);
                    if (na == 10) sl = sl ? sl - 1 : 2;
                }
                const unsigned te = t0 + (k2 ? sched2(x) : sched(T));
                const uint32_t sd = sb + (isw ? stage_w<k2>(lane) : SM_A + (13 + sl) * 8192);
#pragma unroll 1
                for (int t = j0; t < nj; t++) {
                    if (lane == t) {
                        if (t >= 3 && !k2) mbar_wait(rb + sl * 8, (k & 1) ^ 1);
                        while ((int)(te - clk()) > 0) ;
                        raw_load(maps.m + isw, y, z, sd, rb + (3 + t) * 8);
                    }
                    __syncwarp();
                }
                cluster_wait();
                if (elect_one()) asm volatile("prefetch.tensormap [%0];" :: "l"(maps.m + 2 + isw) : "memory");
                if (!isw) cw = 2;
                if (k2) {
                    if (!isw) {
                        if (lane < TN / 16) sc->cs[(e0 & 1) ^ 1][r * (TN / 16) + lane] = 0;
                        const int u = lane * 2 + (r & 1);
                        const unsigned tg = (e0 + 1) * (u < 32 ? 5 : 4);
                        bool dn = u >= NU;
                        for (int it = 0;; it++) {
                            if (!dn && (int)(ld_flag(sc->flag + F_W + u) - tg) >= 0) {
                                dn = true;
                                mbar_arrive(bars + (B_GO + lane * 2) * 8);
                            }
                            if (__all_sync(~0u, dn)) break;
                            if (it > (1 << 22)) __trap();
                        }
                    } else {
                        const float zxf = ld_zx(zero_x);
                        scale_bias(scale_x, scale_w + c * TN, bias + c * TN, sb, lane);
#pragma unroll 1
                        for (int h = 0; h < 3; h++) {
                            for (int it = 0; (int)(ld_flag(sc->flag + F_CS + h) - (e0 + 1) * (h < 2 ? 80 : 32)) < 0; it++) if (it > (1 << 22)) __trap();
                            int2 v[3];
                            int i[3];
#pragma unroll
                            for (int j = 0; j < 3; j++) {
                                i[j] = (j < 2 ? h * 64 + j * 32 : 128 + h * 16) + lane;
                                v[j] = __ldcg((const int2*)sc->cs[e0 & 1] + i[j]);
                            }
#pragma unroll
                            for (int j = 0; j < 3; j++) {
                                const uint32_t pa = sb + SM_PAR + i[j] * 4;
                                const uint32_t z = fold(zero_term(v[j].x, v[j].y, zxf), lds32(pa + TN * 2), lds32(pa + TN * 4));
                                if (h < 2 ? (j < 2 || lane < 16) : j == 2) st_async(pa, z, bars + (B_PAR + h) * 8);
                            }
                        }
                    }
                }
            }
        }
        if (!k2 && r < NBJ && warp == (r < 10 ? 8 : 10)) {
            const float zxf = ld_zx(zero_x);
            const int w = lane & 15;
            uint32_t sw = 0, bi = 0;
            if (CFG_EPI == 3) { mbar_wait(bars + B_SW * 8); sw = lds32(sb + SM_PAR + TN * 2 + col_of(r) * 2 + w * 4); bi = lds32(sb + SM_PAR + TN * 4 + col_of(r) * 2 + w * 4); }
            mbar_wait(bars + B_CS * 8);
            const uint32_t ca = sb + SM_CS + ((w >> 1) + (w & 1) * 16) * 4;
            const uint32_t z = fold(zero_term(lds32(ca), lds32(ca + 32), zxf), sw, bi);
            const int piece = r < 10 ? (r >= 5) : (r - 6) >> 1;
#pragma unroll 1
            for (int i = lane >> 4; i < CS; i += 2) st_async(mapa(sb + SM_PAR + col_of(r) * 2 + w * 4, i), z, mapa(bars + (B_PAR + piece) * 8, i));
        }
#pragma unroll 1
        for (int n = cw, nn, k = 0; n < NF; n = nn, k ^= 1) {
            nn = n + 3;
            if (!k2 && n < 5 && nn >= 5) nn += nn == 5 ? 2 : -1;
            const int gm = (int)(ford_table<k2>() >> (4 * n)), g = (gm >> 3) & 1, m = gm & 7;
            const int x = n >= 10 ? (n >> 1) * 64 : m == 4 ? 256 + g * 32 : g * 128 + (m & 2) * 32;
            const int y = n >= 10 ? (n & 1) * 64 : (m & 1) * 64;
            mbar_wait(bars + (B_FILL + cw) * 8, k);
            asm volatile("fence.proxy.async.shared::cta;" ::: "memory");
            if (elect_one()) tile_store(maps.m + (n < 10 && m == 4 ? 3 : 2), c * TN + x, r * 128 + y, sb + SM_STG + ((cw + NBJ) % 3) * 8192);
            asm volatile("cp.async.bulk.commit_group;" ::: "memory");
            asm volatile("cp.async.bulk.wait_group.read 0;" ::: "memory");
            __syncwarp();
            if (nn < NF && elect_one()) mbar_arrive(bars + (B_FREE + nn) * 8);
        }
    }
}

__global__ void __launch_bounds__(256)
w8a8_plain(const int* __restrict__ qx, const int* __restrict__ qw, const __nv_bfloat16* __restrict__ scale_x, const int* __restrict__ zero_x,
           const __nv_bfloat16* __restrict__ scale_w, const __nv_bfloat16* __restrict__ bias, __nv_bfloat16* __restrict__ out) {
    __shared__ int xs[16][K_ / 4];
    const int n = (blockIdx.x * 256 + threadIdx.x) * 2, m0 = blockIdx.y * 16;
    for (int i = threadIdx.x; i < 16 * K_ / 4; i += 256) {
        const uint4 v = ((const uint4*)qx)[m0 * (K_ / 4) + i];
        xs[i / (K_ / 4)][i % (K_ / 4)] = pack4(v.x, v.y, v.z, v.w);
    }
    __syncthreads();
    int acc[16][2] = {}, cs[2] = {};
    for (int k = 0; k < K_ / 4; k++) {
        uint2 v[4];
#pragma unroll
        for (int i = 0; i < 4; i++) v[i] = *(const uint2*)(qw + (k * 4 + i) * N_ + n);
        const unsigned w0 = pack4(v[0].x, v[1].x, v[2].x, v[3].x), w1 = pack4(v[0].y, v[1].y, v[2].y, v[3].y);
        cs[0] = sum4(w0, cs[0]); cs[1] = sum4(w1, cs[1]);
#pragma unroll
        for (int i = 0; i < 16; i++) { acc[i][0] = __dp4a(xs[i][k], (int)w0, acc[i][0]); acc[i][1] = __dp4a(xs[i][k], (int)w1, acc[i][1]); }
    }
    const uint32_t sx2 = (uint32_t)*(const unsigned short*)scale_x * 0x10001u, bi = *(const unsigned*)(bias + n);
    uint32_t sw = *(const unsigned*)(scale_w + n);
    if (CFG_EPI) sw = bf2_mul(sw, sx2);
    const uint32_t zc = fold(zero_term(cs[0], cs[1], ld_zx(zero_x)), sw, bi);
#pragma unroll
    for (int i = 0; i < 16; i++) *(unsigned*)(out + (m0 + i) * N_ + n) = epi(acc[i][0], acc[i][1], zc, sx2, sw, bi);
}

}

typedef CUresult (*EncodeFn)(CUtensorMap*, CUtensorMapDataType, cuuint32_t, void*, const cuuint64_t*, const cuuint64_t*,
                             const cuuint32_t*, const cuuint32_t*, CUtensorMapInterleave, CUtensorMapSwizzle,
                             CUtensorMapL2promotion, CUtensorMapFloatOOBfill);

extern "C" void kernel_launch(void* const* d_in, const int* in_sizes, int n_in, void* d_out, int out_size) {
    using namespace w8;
    static EncodeFn encode = nullptr;
    static cudaStream_t side;
    static cudaEvent_t started, joined;
    static int clusters = -1;
    static Scratch* sc;
    cudaLaunchConfig_t cfg = {};
    cfg.gridDim = dim3(NCTA); cfg.blockDim = dim3(512); cfg.dynamicSmemBytes = SM_TOTAL; cfg.stream = cudaStreamPerThread;
    if (clusters < 0) {
        void* fn = nullptr;
        cudaDriverEntryPointQueryResult qr;
        cudaGetDriverEntryPoint("cuTensorMapEncodeTiled", &fn, cudaEnableDefault, &qr);
        encode = (EncodeFn)fn;
        cudaGetSymbolAddress((void**)&sc, g_scratch);
        cudaStreamCreateWithFlags(&side, cudaStreamNonBlocking);
        cudaEventCreateWithFlags(&started, cudaEventDisableTiming);
        cudaEventCreateWithFlags(&joined, cudaEventDisableTiming);
        cudaFuncSetAttribute(w8a8_kernel<false>, cudaFuncAttributeMaxDynamicSharedMemorySize, SM_TOTAL);
        cudaFuncSetAttribute(w8a8_kernel<true>, cudaFuncAttributeMaxDynamicSharedMemorySize, SM_TOTAL);
        cudaFuncSetAttribute(w8a8_kernel<false>, cudaFuncAttributeNonPortableClusterSizeAllowed, 1);
        if (cudaOccupancyMaxActiveClusters(&clusters, w8a8_kernel<false>, &cfg) != cudaSuccess) { clusters = 0; cudaGetLastError(); }
    }
    const __nv_bfloat16 *sx = (const __nv_bfloat16*)d_in[2], *sw = (const __nv_bfloat16*)d_in[4], *bias = (const __nv_bfloat16*)d_in[5];
    const int* zx = (const int*)d_in[3];
    if (clusters < NCL) {
        w8a8_plain<<<dim3(N_ / 512, M_ / 16), 256, 0, cudaStreamPerThread>>>((const int*)d_in[0], (const int*)d_in[1], sx, zx, sw, bias, (__nv_bfloat16*)d_out);
        return;
    }
    Maps maps;
    const cuuint32_t es[3] = {1, 1, 1};
    {
        const cuuint64_t dim[3] = {32, K_ / 32, M_}, str[2] = {128, K_ * 4};
        const cuuint32_t box[3] = {32, 2, 32};
        encode(&maps.m[0], CU_TENSOR_MAP_DATA_TYPE_INT32, 3, d_in[0], dim, str, box, es, CU_TENSOR_MAP_INTERLEAVE_NONE,
               CU_TENSOR_MAP_SWIZZLE_128B, CU_TENSOR_MAP_L2_PROMOTION_NONE, CU_TENSOR_MAP_FLOAT_OOB_FILL_NONE);
    }
    {
        const cuuint64_t dim[3] = {32, K_, N_ / 32}, str[2] = {N_ * 4, 128};
        const cuuint32_t box[3] = {32, 64, 1};
        encode(&maps.m[1], CU_TENSOR_MAP_DATA_TYPE_INT32, 3, d_in[1], dim, str, box, es, CU_TENSOR_MAP_INTERLEAVE_NONE,
               CU_TENSOR_MAP_SWIZZLE_NONE, CU_TENSOR_MAP_L2_PROMOTION_NONE, CU_TENSOR_MAP_FLOAT_OOB_FILL_NONE);
    }
    for (int i = 0; i < 2; i++) {
        const cuuint64_t dim[2] = {N_, M_}, str[1] = {N_ * 2};
        const cuuint32_t box[2] = {i ? 32u : 64u, i ? 128u : 64u};
        encode(&maps.m[2 + i], CU_TENSOR_MAP_DATA_TYPE_BFLOAT16, 2, d_out, dim, str, box, es, CU_TENSOR_MAP_INTERLEAVE_NONE,
               i ? CU_TENSOR_MAP_SWIZZLE_NONE : CU_TENSOR_MAP_SWIZZLE_128B, CU_TENSOR_MAP_L2_PROMOTION_NONE, CU_TENSOR_MAP_FLOAT_OOB_FILL_NONE);
    }
    cudaLaunchAttribute at;
    at.id = cudaLaunchAttributeProgrammaticEvent;
    at.val.programmaticEvent.event = started; at.val.programmaticEvent.flags = 0; at.val.programmaticEvent.triggerAtBlockStart = 1;
    cfg.attrs = &at; cfg.numAttrs = 1;
    cudaLaunchKernelEx(&cfg, w8a8_kernel<false>, sc, (const char*)d_in[0], (const char*)d_in[1], sx, zx, sw, bias, maps);
    cudaStreamWaitEvent(side, started, 0);
    cfg.gridDim = dim3(20); cfg.stream = side; cfg.numAttrs = 0;
    cudaLaunchKernelEx(&cfg, w8a8_kernel<true>, sc, (const char*)d_in[0], (const char*)d_in[1], sx, zx, sw, bias, maps);
    cudaEventRecord(joined, side);
    cudaStreamWaitEvent(cudaStreamPerThread, joined, 0);
}
```

```cpp
#include <cuda_runtime.h>
#include <cuda.h>
#include <cuda_bf16.h>
#include <stdint.h>
#include <stddef.h>

#define CFG_X1 13
#define CFG_P1 46
#define CFG_P2 39
#define CFG_PT 100
#define CFG_L0 34
#define CFG_RA 33
#define CFG_T0 -590
#define CFG_Q0 14
#define CFG_Q2 69
#define CFG_Q3 30
#define CFG_T3 400
#define CFG_D3 2
#define CFG_PF7 18
#define CFG_TA 10
#define CFG_EPI 3
#define CFG_X2 11
#define CFG_S3 10
#define CFG_D4 4
#define CFG_PG 8

namespace w8 {

constexpr int M_ = 2048, K_ = 1024, N_ = 3584;
constexpr int CS = 16, NCL = 7, NCTA = CS * NCL;
constexpr int WA = 160, WB = 64, TN = 2 * WA + 2 * WB;
constexpr int NSLOT = 7, SLOT = WA * 64;
constexpr int NAJ = 1024;
constexpr int REV = 60;
constexpr int TA = CFG_TA;

constexpr int L0 = CFG_L0, RA = CFG_RA, RB64 = 64 * RA / (RA - 16);
constexpr int P1 = CFG_P1, P2 = CFG_P2, PT = CFG_PT, T0 = CFG_T0;
__device__ __forceinline__ int time_x(int x) { return max(x, L0 + (((x - L0) * RA) >> 4)); }
__device__ __forceinline__ int time_w(int q) { return min(L0 + ((q * RB64) >> 6), NAJ / NCL + q); }
__device__ __forceinline__ unsigned sched(int T) { return T * P2 + min(T, PT) * (P1 - P2); }
__device__ __forceinline__ int sched2(int q) { return (min(q, 160) - CFG_Q0) * CFG_Q2 + max(q - 160, 0) * CFG_Q3; }

constexpr int SM_A = 0;
constexpr int SM_RING = 131072;
constexpr int SM_STG = SM_RING + NSLOT * SLOT;
constexpr int SM_PAR = SM_STG + 3 * 8192;
constexpr int SM_CS = SM_PAR + 3 * TN * 2;
constexpr int SM_BAR = SM_CS + 128;
constexpr int B_FULLB = 0, B_FULLA = 56, B_PAR = 72, B_SW = 77, B_AFREE = 74  , B_FREE = 90,
              B_FILL = 128, B_CS = 131, B_RAWA = 132, B_RAWB = 145, B_GO = 164  , B_END = 204;
constexpr int SM_TOTAL = SM_BAR + B_END * 8;
static_assert(SM_TOTAL <= 232448, "");

constexpr int F_W = 512, F_CS = 576;
struct Scratch {
    unsigned flag[768];
    int cs[2][TN];
    int sink[384];
    uint4 s8[(1024 + 8 * 256) * 128];
};
static_assert(offsetof(Scratch, s8) == 8192, "");
__device__ __align__(8192) Scratch g_scratch;
__device__ __forceinline__ unsigned* epoch(Scratch* sc, int r, int c) { return sc->flag + r * 32 + 16 + c; }

__device__ __forceinline__ void mbar_init(uint32_t bar, uint32_t cnt) {
    asm volatile("mbarrier.init.shared::cta.b64 [%0], %1;" :: "r"(bar), "r"(cnt) : "memory");
}
__device__ __forceinline__ void mbar_expect_tx(uint32_t bar, uint32_t bytes) {
    asm volatile("mbarrier.arrive.expect_tx.shared::cta.b64 _, [%0], %1;" :: "r"(bar), "r"(bytes) : "memory");
}
__device__ __forceinline__ void mbar_arrive(uint32_t bar) {
    asm volatile("mbarrier.arrive.shared::cta.b64 _, [%0];" :: "r"(bar) : "memory");
}
__device__ __forceinline__ void mbar_arrive_cluster(uint32_t bar) {
    asm volatile("mbarrier.arrive.shared::cluster.b64 _, [%0];" :: "r"(bar) : "memory");
}
__device__ __forceinline__ void mbar_wait(uint32_t bar, uint32_t parity = 0) {
    asm volatile("{\n.reg .pred p;\n.reg .u32 c;\n"
                 "mbarrier.try_wait.parity.shared::cta.b64 p, [%0], %1;\n"
                 "@p bra WAIT_DONE;\n"
                 "mov.u32 c, 0;\n"
                 "WAIT_LOOP:\n"
                 "mbarrier.try_wait.parity.shared::cta.b64 p, [%0], %1;\n"
                 "@p bra WAIT_DONE;\n"
                 "add.u32 c, c, 1;\nsetp.lt.u32 p, c, 0x100000;\n"
                 "@p bra WAIT_LOOP;\n"
                 "trap;\n"
                 "WAIT_DONE:\n}" :: "r"(bar), "r"(parity) : "memory");
}
__device__ __forceinline__ void mbar_wait2(uint32_t bar0, uint32_t bar1) {
    asm volatile("{\n.reg .pred p, q;\n.reg .u32 c;\nmov.u32 c, 0;\n"
                 "WAIT_LOOP:\n"
                 "mbarrier.try_wait.parity.shared::cta.b64 p, [%0], 0;\n"
                 "mbarrier.try_wait.parity.shared::cta.b64 q, [%1], 0;\n"
                 "and.pred p, p, q;\n"
                 "@p bra WAIT_DONE;\n"
                 "add.u32 c, c, 1;\nsetp.lt.u32 p, c, 0x100000;\n"
                 "@p bra WAIT_LOOP;\n"
                 "trap;\n"
                 "WAIT_DONE:\n}" :: "r"(bar0), "r"(bar1) : "memory");
}
__device__ __forceinline__ bool mbar_test(uint32_t bar) {
    uint32_t ok;
    asm volatile("{\n.reg .pred p;\nmbarrier.test_wait.parity.shared::cta.b64 p, [%1], 0;\nselp.u32 %0, 1, 0, p;\n}" : "=r"(ok) : "r"(bar) : "memory");
    return ok;
}
__device__ __forceinline__ bool mbar_test2(uint32_t bar0, uint32_t bar1) {
    uint32_t ok;
    asm volatile("{\n.reg .pred p, q;\nmbarrier.test_wait.parity.shared::cta.b64 p, [%1], 0;\n"
                 "mbarrier.test_wait.parity.shared::cta.b64 q, [%2], 0;\nand.pred p, p, q;\nselp.u32 %0, 1, 0, p;\n}"
                 : "=r"(ok) : "r"(bar0), "r"(bar1) : "memory");
    return ok;
}
__device__ __forceinline__ bool elect_one() {
    uint32_t ok;
    asm volatile("{\n.reg .pred p;\nelect.sync _|p, 0xffffffff;\nselp.u32 %0, 1, 0, p;\n}" : "=r"(ok));
    return ok;
}
__device__ __forceinline__ unsigned ld_flag(const unsigned* p) {
    unsigned v;
    asm volatile("ld.relaxed.gpu.global.u32 %0, [%1];" : "=r"(v) : "l"(p) : "memory");
    return v;
}
__device__ __forceinline__ uint4 lds128(uint32_t a) {
    uint4 v;
    asm volatile("ld.shared.v4.b32 {%0,%1,%2,%3}, [%4];" : "=r"(v.x), "=r"(v.y), "=r"(v.z), "=r"(v.w) : "r"(a) : "memory");
    return v;
}
__device__ __forceinline__ void sts128(uint32_t a, uint4 v) {
    asm volatile("st.shared.v4.b32 [%0], {%1,%2,%3,%4};" :: "r"(a), "r"(v.x), "r"(v.y), "r"(v.z), "r"(v.w) : "memory");
}
__device__ __forceinline__ uint32_t lds32(uint32_t a) {
    uint32_t v;
    asm volatile("ld.shared.b32 %0, [%1];" : "=r"(v) : "r"(a) : "memory");
    return v;
}
__device__ __forceinline__ void sts32(uint32_t a, uint32_t v) {
    asm volatile("st.shared.b32 [%0], %1;" :: "r"(a), "r"(v) : "memory");
}
__device__ __forceinline__ void stg128(void* p, uint4 v) {
    asm volatile("st.global.v4.b32 [%0], {%1,%2,%3,%4};" :: "l"(p), "r"(v.x), "r"(v.y), "r"(v.z), "r"(v.w) : "memory");
}
__device__ __forceinline__ unsigned pack4(unsigned a, unsigned b, unsigned c, unsigned d) {
    unsigned lo, r;
    asm("cvt.pack.sat.s8.s32.b32 %0, %1, %2, 0;" : "=r"(lo) : "r"(d), "r"(c));
    asm("cvt.pack.sat.s8.s32.b32 %0, %1, %2, %3;" : "=r"(r) : "r"(b), "r"(a), "r"(lo));
    return r;
}
__device__ __forceinline__ uint32_t mapa(uint32_t a, uint32_t r) {
    uint32_t o;
    asm("mapa.shared::cluster.u32 %0, %1, %2;" : "=r"(o) : "r"(a), "r"(r));
    return o;
}
__device__ __forceinline__ unsigned clk() {
    unsigned t;
    asm volatile("mov.u32 %0, %clock;" : "=r"(t));
    return t;
}
__device__ __forceinline__ void cluster_arrive() { asm volatile("barrier.cluster.arrive.relaxed.aligned;" ::: "memory"); }
__device__ __forceinline__ void cluster_wait() { asm volatile("barrier.cluster.wait.aligned;" ::: "memory"); }
__device__ __forceinline__ void fence_init() { asm volatile("fence.mbarrier_init.release.cluster;" ::: "memory"); }
__device__ __forceinline__ void flag_add(unsigned* p) { asm volatile("red.relaxed.gpu.global.add.u32 [%0], 1;" :: "l"(p) : "memory"); }
__device__ __forceinline__ void raw_load(const void* map, int y, int z, uint32_t dst, uint32_t bar) {
    asm volatile("cp.async.bulk.tensor.3d.shared::cluster.global.tile.mbarrier::complete_tx::bytes [%0], [%1, {0, %2, %3}], [%4];"
                 :: "r"(dst), "l"(map), "r"(y), "r"(z), "r"(bar) : "memory");
}
__device__ __forceinline__ void tile_load(Scratch* sc, uint32_t dst, int tile, uint32_t bar) {
    asm volatile("cp.async.bulk.shared::cluster.global.mbarrier::complete_tx::bytes [%0], [%1], %2, [%3];"
                 :: "r"(dst), "l"((const char*)sc->s8 + tile * 8192), "r"(8192), "r"(bar) : "memory");
}
__device__ __forceinline__ void tile_store(const void* map, int x, int y, uint32_t src) {
    asm volatile("cp.async.bulk.tensor.2d.global.shared::cta.tile.bulk_group [%0, {%1, %2}], [%3];"
                 :: "l"(map), "r"(x), "r"(y), "r"(src) : "memory");
}
__device__ __forceinline__ void st_async(uint32_t a, uint32_t v, uint32_t bar) {
    asm volatile("st.async.weak.shared::cluster.mbarrier::complete_tx::bytes.b32 [%0], %1, [%2];" :: "r"(a), "r"(v), "r"(bar) : "memory");
}
__device__ __forceinline__ void red_async(uint32_t a, int v, uint32_t bar) {
    asm volatile("red.async.relaxed.cluster.shared::cluster.mbarrier::complete_tx::bytes.add.s32 [%0], %1, [%2];" :: "r"(a), "r"(v), "r"(bar) : "memory");
}
__device__ __forceinline__ void red_shared(uint32_t a, int v) { asm volatile("red.shared.add.s32 [%0], %1;" :: "r"(a), "r"(v) : "memory"); }
__device__ __forceinline__ int sum4(unsigned v, int c) { return __dp4a((int)v, 0x01010101, c); }

constexpr uint32_t DESC_A_HI = 0x80000000u | (512 >> 4);
constexpr uint32_t DESC_B_HI = 512 >> 4;
template <int NR> __device__ __forceinline__ void wgmma_n160(int (&d)[NR], uint32_t alo, uint32_t blo, int scale_d) {
    asm volatile("{\n.reg .pred p;\n.reg .b64 da, db;\nsetp.ne.b32 p, %82, 0;\n"
        "mov.b64 da, {%80, %83};\nmov.b64 db, {%81, %84};\n"
        "wgmma.mma_async.sync.aligned.m64n160k32.s32.s8.s8 "
        "{%0, %1, %2, %3, %4, %5, %6, %7, %8, %9, %10, %11, %12, %13, %14, %15, "
        "%16, %17, %18, %19, %20, %21, %22, %23, %24, %25, %26, %27, %28, %29, %30, %31, "
        "%32, %33, %34, %35, %36, %37, %38, %39, %40, %41, %42, %43, %44, %45, %46, %47, "
        "%48, %49, %50, %51, %52, %53, %54, %55, %56, %57, %58, %59, %60, %61, %62, %63, "
        "%64, %65, %66, %67, %68, %69, %70, %71, %72, %73, %74, %75, %76, %77, %78, %79}, "
        "da, db, p;\n}\n"
        : "+r"(d[0]), "+r"(d[1]), "+r"(d[2]), "+r"(d[3]), "+r"(d[4]), "+r"(d[5]), "+r"(d[6]), "+r"(d[7]),
          "+r"(d[8]), "+r"(d[9]), "+r"(d[10]), "+r"(d[11]), "+r"(d[12]), "+r"(d[13]), "+r"(d[14]), "+r"(d[15]),
          "+r"(d[16]), "+r"(d[17]), "+r"(d[18]), "+r"(d[19]), "+r"(d[20]), "+r"(d[21]), "+r"(d[22]), "+r"(d[23]),
          "+r"(d[24]), "+r"(d[25]), "+r"(d[26]), "+r"(d[27]), "+r"(d[28]), "+r"(d[29]), "+r"(d[30]), "+r"(d[31]),
          "+r"(d[32]), "+r"(d[33]), "+r"(d[34]), "+r"(d[35]), "+r"(d[36]), "+r"(d[37]), "+r"(d[38]), "+r"(d[39]),
          "+r"(d[40]), "+r"(d[41]), "+r"(d[42]), "+r"(d[43]), "+r"(d[44]), "+r"(d[45]), "+r"(d[46]), "+r"(d[47]),
          "+r"(d[48]), "+r"(d[49]), "+r"(d[50]), "+r"(d[51]), "+r"(d[52]), "+r"(d[53]), "+r"(d[54]), "+r"(d[55]),
          "+r"(d[56]), "+r"(d[57]), "+r"(d[58]), "+r"(d[59]), "+r"(d[60]), "+r"(d[61]), "+r"(d[62]), "+r"(d[63]),
          "+r"(d[64]), "+r"(d[65]), "+r"(d[66]), "+r"(d[67]), "+r"(d[68]), "+r"(d[69]), "+r"(d[70]), "+r"(d[71]),
          "+r"(d[72]), "+r"(d[73]), "+r"(d[74]), "+r"(d[75]), "+r"(d[76]), "+r"(d[77]), "+r"(d[78]), "+r"(d[79])
        : "r"(alo), "r"(blo), "r"(scale_d), "r"(DESC_A_HI), "r"(DESC_B_HI));
}
template <int NR> __device__ __forceinline__ void wgmma_t128(int (&d)[NR], uint32_t alo, uint32_t blo, int scale_d) {
    asm volatile("{\n.reg .pred p;\n.reg .b64 da, db;\nsetp.ne.b32 p, %66, 0;\n"
        "mov.b64 da, {%64, %67};\nmov.b64 db, {%65, %68};\n"
        "wgmma.mma_async.sync.aligned.m64n128k32.s32.s8.s8 "
        "{%0, %1, %2, %3, %4, %5, %6, %7, %8, %9, %10, %11, %12, %13, %14, %15, "
        "%16, %17, %18, %19, %20, %21, %22, %23, %24, %25, %26, %27, %28, %29, %30, %31, "
        "%32, %33, %34, %35, %36, %37, %38, %39, %40, %41, %42, %43, %44, %45, %46, %47, "
        "%48, %49, %50, %51, %52, %53, %54, %55, %56, %57, %58, %59, %60, %61, %62, %63}, "
        "da, db, p;\n}\n"
        : "+r"(d[0]), "+r"(d[1]), "+r"(d[2]), "+r"(d[3]), "+r"(d[4]), "+r"(d[5]), "+r"(d[6]), "+r"(d[7]),
          "+r"(d[8]), "+r"(d[9]), "+r"(d[10]), "+r"(d[11]), "+r"(d[12]), "+r"(d[13]), "+r"(d[14]), "+r"(d[15]),
          "+r"(d[16]), "+r"(d[17]), "+r"(d[18]), "+r"(d[19]), "+r"(d[20]), "+r"(d[21]), "+r"(d[22]), "+r"(d[23]),
          "+r"(d[24]), "+r"(d[25]), "+r"(d[26]), "+r"(d[27]), "+r"(d[28]), "+r"(d[29]), "+r"(d[30]), "+r"(d[31]),
          "+r"(d[32]), "+r"(d[33]), "+r"(d[34]), "+r"(d[35]), "+r"(d[36]), "+r"(d[37]), "+r"(d[38]), "+r"(d[39]),
          "+r"(d[40]), "+r"(d[41]), "+r"(d[42]), "+r"(d[43]), "+r"(d[44]), "+r"(d[45]), "+r"(d[46]), "+r"(d[47]),
          "+r"(d[48]), "+r"(d[49]), "+r"(d[50]), "+r"(d[51]), "+r"(d[52]), "+r"(d[53]), "+r"(d[54]), "+r"(d[55]),
          "+r"(d[56]), "+r"(d[57]), "+r"(d[58]), "+r"(d[59]), "+r"(d[60]), "+r"(d[61]), "+r"(d[62]), "+r"(d[63])
        : "r"(alo), "r"(blo), "r"(scale_d), "r"(DESC_B_HI), "r"(DESC_A_HI));
}


__device__ __forceinline__ void wg_fence() { asm volatile("wgmma.fence.sync.aligned;" ::: "memory"); }
__device__ __forceinline__ void wg_commit() { asm volatile("wgmma.commit_group.sync.aligned;" ::: "memory"); }
template <int N> __device__ __forceinline__ void wg_wait() { asm volatile("wgmma.wait_group.sync.aligned %0;" :: "n"(N) : "memory"); }

__host__ __device__ constexpr int unit_of(int X1, int piece, int slab) {
    return piece < 2 ? (slab < X1 ? 2 * slab + piece : (piece ? 16 : X1) + slab) : 32 + (piece - 2) * 8 + (slab >> 1);
}
__host__ __device__ constexpr int col_of(int G) { return G == 4 ? 256 : (G > 4 && G < 9) ? 32 * G - 32 : 32 * G; }
struct BJob { int u, slab, G, pos; };
__host__ __device__ constexpr BJob decode_b(int X1, int q) {
    BJob j = {};
    if (q < 160) {
        j.u = q / 5; j.pos = q - j.u * 5;
        const int piece = j.u < 2 * X1 ? (j.u & 1) : (j.u >= X1 + 16);
        j.slab = j.u < 2 * X1 ? (j.u >> 1) : j.u - (piece ? 16 : X1);
        j.G = piece * 5 + j.pos;
    } else {
        q -= 160;
        j.u = 32 + (q >> 2); j.pos = q & 3;
        j.slab = (q >> 1) & 15;
        j.G = 10 + (q >> 5) * 2 + (q & 1);
    }
    return j;
}
__host__ __device__ constexpr int fb_of(int X1, int u) {
    return u < 2 * X1 ? (u & 1) * 32 + (u >> 1) : u < X1 + 16 ? u - X1 : u < 32 ? 16 + u : u < 40 ? u - 16 : u < 48 ? u + 8 : u - 24;
}
__host__ __device__ constexpr uint64_t slot_table(int X1, int piece) {
    uint64_t t = 0;
    for (int s = 0; s < 16; s++) t |= (uint64_t)(unit_of(X1, piece, s) % NSLOT) << (4 * s);
    return t;
}
template <bool k2> __device__ __forceinline__ int stage_w(int t) { return (k2 && t < 9) ? SM_A + (7 + t) * 8192 : SM_STG + (t % 3) * 8192; }
template <bool k2> __host__ __device__ constexpr int ford(int g, int m) {
    return k2 ? g * 5 + m : g ? (m ? 4 + m : 2) : (m < 2 ? m : m < 4 ? m + 1 : 9);
}
template <bool k2> __host__ __device__ constexpr int turn(int n) { return (n + (!k2 && n >= 5)) % 3; }
template <bool k2> __host__ __device__ constexpr uint64_t ford_table() {
    uint64_t t = 0;
    for (int g = 0; g < 2; g++) for (int m = 0; m < 5; m++) t |= (uint64_t)(g * 8 + m) << (4 * ford<k2>(g, m));
    return t;
}
struct Maps { CUtensorMap m[4]; };

__device__ __forceinline__ uint32_t bf2_mul(uint32_t a, uint32_t b) { asm("mul.rn.bf16x2 %0, %0, %1;" : "+r"(a) : "r"(b)); return a; }
__device__ __forceinline__ uint32_t epi(int a, int b, uint32_t zc, uint32_t sx, uint32_t sw, uint32_t bi) {
    uint32_t v;
    float fa = __int2float_rn(a), fb = __int2float_rn(b);
    asm("cvt.rn.bf16x2.f32 %0, %1, %2;" : "=r"(v) : "f"(fb), "f"(fa));
    if (CFG_EPI == 3) {
        asm("fma.rn.bf16x2 %0, %0, %1, %2;" : "+r"(v) : "r"(sw), "r"(zc));
        return v;
    }
    asm("sub.rn.bf16x2 %0, %0, %1;" : "+r"(v) : "r"(zc));
    if (CFG_EPI == 0) {
        v = bf2_mul(bf2_mul(v, sx), sw);
        asm("add.rn.bf16x2 %0, %0, %1;" : "+r"(v) : "r"(bi));
    } else {
        asm("fma.rn.bf16x2 %0, %0, %1, %2;" : "+r"(v) : "r"(sw), "r"(bi));
    }
    return v;
}
__device__ __forceinline__ uint32_t zero_term(int lo, int hi, float zx) {
    uint32_t z;
    asm("cvt.rn.bf16x2.f32 %0, %1, %2;" : "=r"(z) : "f"(__bfloat162float(__float2bfloat16_rn((float)hi)) * zx),
                                                    "f"(__bfloat162float(__float2bfloat16_rn((float)lo)) * zx));
    return z;
}
__device__ __forceinline__ uint32_t fold(uint32_t z, uint32_t sw, uint32_t bi) {
    if (CFG_EPI == 3) asm("fma.rn.bf16x2 %0, %1, %2, %3;" : "=r"(z) : "r"(z ^ 0x80008000u), "r"(sw), "r"(bi));
    return z;
}
__device__ __forceinline__ float ld_zx(const int* zero_x) { return __bfloat162float(__float2bfloat16_rn((float)__ldg(zero_x))); }
struct Par { uint4 zc, sw, bi; };
__device__ __forceinline__ Par ld_par(uint32_t p) { return {lds128(p), lds128(p + TN * 2), CFG_EPI == 3 ? uint4{} : lds128(p + TN * 4)}; }
__device__ __forceinline__ uint4 epi_row(const int (&a)[WA / 2], int o, const Par& p, uint32_t sx2) {
    uint4 r;
    r.x = epi(a[o + 0], a[o + 4], p.zc.x, sx2, p.sw.x, p.bi.x);
    r.y = epi(a[o + 8], a[o + 12], p.zc.y, sx2, p.sw.y, p.bi.y);
    r.z = epi(a[o + 1], a[o + 5], p.zc.z, sx2, p.sw.z, p.bi.z);
    r.w = epi(a[o + 9], a[o + 13], p.zc.w, sx2, p.sw.w, p.bi.w);
    return r;
}
__device__ __forceinline__ void scale_bias(const __nv_bfloat16* scale_x, const __nv_bfloat16* scale_w, const __nv_bfloat16* bias, uint32_t sb, int lane) {
    const uint32_t sx2 = (uint32_t)__ldg((const unsigned short*)scale_x) * 0x10001u;
#pragma unroll
    for (int i = lane; i < TN / 4; i += 32) {
        const bool hi = i >= TN / 8;
        uint4 v = __ldg((const uint4*)(hi ? bias : scale_w) + (hi ? i - TN / 8 : i));
        if (CFG_EPI && !hi) v = {bf2_mul(v.x, sx2), bf2_mul(v.y, sx2), bf2_mul(v.z, sx2), bf2_mul(v.w, sx2)};
        sts128(sb + SM_PAR + TN * 2 + i * 16, v);
    }
    __syncwarp();
    if (elect_one()) mbar_arrive(sb + SM_BAR + B_SW * 8);
}
template <bool k2> __device__ __forceinline__ int release_addr(uint32_t sb, int u, int lq) {
    const int v = u + NSLOT, q = (k2 ? (v >> 1) * 16 + (v & 1) : 5 * v - (v > 34 ? 3 : 0)) + lq;
    return mapa(sb | (q & 0x1F0), q & 15) | (q & 0x80000000);
}
__device__ __forceinline__ void release(int a) {
    asm volatile("{\n.reg .pred p;\nsetp.ge.s32 p, %0, 0;\n@p mbarrier.arrive.shared::cluster.b64 _, [%0 + %1];\n}" :: "r"(a), "n"(SM_BAR + B_GO * 8) : "memory");
}
__device__ __forceinline__ unsigned read_back(const uint4* d, int lane) { return ld_flag((const unsigned*)(d - lane + ((lane + 10) & 15) * 8 + 6)); }
__device__ __forceinline__ void publish(unsigned rb, unsigned mine, unsigned* flag) {
    asm volatile("{\n.reg .pred p, q;\n.reg .u32 l;\nmov.u32 l, %laneid;\nsetp.eq.u32 p, l, 6;\nsetp.ne.and.u32 q, %1, %2, p;\n"
                 "@q fence.acq_rel.gpu;\n@p red.relaxed.gpu.global.add.u32 [%0], 1;\n}" :: "l"(flag), "r"(rb), "r"(mine) : "memory");
}
#define CV_B(m, f)                                                                                                      \
    {                                                                                                                   \
        uint4 v0 = lds128(rdB + m * 512), v1 = lds128(rdB + m * 512 + 128);                                             \
        uint4 v2 = lds128(rdB + m * 512 + 256), v3 = lds128(rdB + m * 512 + 384);                                       \
        o[0].f = pack4(v0.x, v1.x, v2.x, v3.x); o[1].f = pack4(v0.y, v1.y, v2.y, v3.y);                                 \
        o[2].f = pack4(v0.z, v1.z, v2.z, v3.z); o[3].f = pack4(v0.w, v1.w, v2.w, v3.w);                                 \
    }

__device__ __forceinline__ void last_columns(Scratch* sc, const Maps& maps, const __nv_bfloat16* scale_x, const int* zero_x, const __nv_bfloat16* scale_w,
                                             const __nv_bfloat16* bias, uint32_t sb, int warp, int lane, unsigned t0) {
    constexpr int C_FULL = 0, C_EMPTY = 32, C_RAW = 64, C_GO = 80, C_PEER = 81, D3 = CFG_D3;
    const uint32_t bars = sb + SM_BAR;
    const int j = blockIdx.x & 3;
    while ((int)(t0 + CFG_T3 - clk()) > 0) ;
    const int s0 = (j & 1) * 8 + (warp >> 1) * 2;
    if (warp < 8) {
        if (elect_one()) {
#pragma unroll
            for (int i = 0; i < 2; i++) {
                const uint32_t bar = bars + (C_RAW + warp * 2 + i) * 8;
                mbar_init(bar, 1); mbar_expect_tx(bar, 8192);
                raw_load(maps.m + 1, (s0 + (i ^ (j >> 1))) * 64, N_ / 32 - 2 + (warp & 1), sb + SM_A + (warp * 2 + i) * 8192, bar);
            }
#pragma unroll
            for (int i = 0; i < 4; i++) { mbar_init(bars + (C_FULL + warp * 4 + i) * 8, 1); mbar_expect_tx(bars + (C_FULL + warp * 4 + i) * 8, 16384); }
#pragma unroll
            for (int i = 0; i < 4; i++) mbar_init(bars + (C_EMPTY + warp * 4 + i) * 8, 4);
            if (warp == 0) {
                mbar_init(bars + C_GO * 8, 8);
                mbar_init(bars + C_PEER * 8, 1); mbar_expect_tx(bars + C_PEER * 8, 32768 + 4096);
            }
        }
        if (warp < 2) sts32(sb + SM_PAR + threadIdx.x * 4, 0);
        fence_init();
    }
    __syncthreads();
    cluster_arrive();
    cluster_wait();
    if (warp >= 8) {
        asm volatile("setmaxnreg.dec.sync.aligned.u32 40;");
        if (warp < 12) {
            const unsigned ep = (ld_flag(epoch(sc, j * 4, 8)) + 1) * 4;
            const int mb = j * 4 + warp - 8, wg = (warp >> 1) & 1;
            unsigned rdy = 0;
            mbar_wait(bars + (wg ? C_EMPTY : C_GO) * 8);
#pragma unroll 1
            for (int s = 0; s < 16; s++) {
                for (int it = 0; !((rdy >> s) & 1); it++) {
                    rdy = __ballot_sync(~0u, (int)(ld_flag(sc->flag + mb * 32 + (lane & 15)) - ep) >= 0);
                    if (it > (1 << 22)) __trap();
                }
                if (s >= D3) mbar_wait(bars + (C_EMPTY + (s - (s < CFG_S3 ? D3 : CFG_D4)) * 2 + wg) * 8);
                if (elect_one()) tile_load(sc, sb + SM_A + ((s & 3) * 4 + warp - 8) * 8192, mb * 16 + s, bars + (C_FULL + s * 2 + wg) * 8);
            }
        }
    } else {
        asm volatile("setmaxnreg.inc.sync.aligned.u32 200;");
        const int wg = warp >> 2, w = warp & 3;
        const int c0 = (w >> 1) * 32 + (lane >> 2) * 4 + (w & 1) * 2, r0 = (lane & 3) * 2;
        const uint32_t sx2 = (uint32_t)__ldg((const unsigned short*)scale_x) * 0x10001u;
        uint32_t sw = __ldg((const unsigned*)(scale_w + N_ - WB + c0));
        const uint32_t bi = __ldg((const unsigned*)(bias + N_ - WB + c0));
        const float zxf = ld_zx(zero_x);
        int cs[4] = {0, 0, 0, 0};
        const uint32_t peer = mapa(sb, (j & 1) ^ 1);
#pragma unroll 1
        for (int i = 0; i < 2; i++) {
            const uint32_t rdB = sb + SM_A + (warp * 2 + i) * 8192 + (lane >> 3) * 2048 + (lane & 7) * 16;
            const uint32_t wr = SM_RING + (s0 + (i ^ (j >> 1))) * 4096 + (warp & 1) * 2048 + lane * 16;
            mbar_wait(bars + (C_RAW + warp * 2 + i) * 8);
            uint4 o[4];
            CV_B(0, x) CV_B(1, y) CV_B(2, z) CV_B(3, w)
#pragma unroll
            for (int k = 0; k < 4; k++) {
                sts128(sb + wr + k * 512, o[k]);
                asm volatile("st.async.weak.shared::cluster.mbarrier::complete_tx::bytes.v4.b32 [%0], {%1,%2,%3,%4}, [%5];"
                             :: "r"(peer + wr + k * 512), "r"(o[k].x), "r"(o[k].y), "r"(o[k].z), "r"(o[k].w), "r"(peer + SM_BAR + C_PEER * 8) : "memory");
                cs[k] = sum4(o[k].x, sum4(o[k].y, sum4(o[k].z, sum4(o[k].w, cs[k]))));
            }
        }
        __syncwarp();
        if (elect_one()) mbar_arrive(bars + C_GO * 8);
#pragma unroll
        for (int k = 0; k < 4; k++) {
            const uint32_t ca = SM_PAR + ((warp & 1) * 32 + (lane & 7) * 4 + k) * 4;
            red_shared(sb + ca, cs[k]);
            red_async(peer + ca, cs[k], peer + SM_BAR + C_PEER * 8);
        }
        mbar_wait(bars + C_PEER * 8);
        asm volatile("fence.proxy.async.shared::cta;" ::: "memory");
        asm volatile("bar.sync 1, 256;" ::: "memory");
        if (CFG_EPI) sw = bf2_mul(sw, sx2);
        const uint32_t zc = fold(zero_term(lds32(sb + SM_PAR + c0 * 4), lds32(sb + SM_PAR + c0 * 4 + 4), zxf), sw, bi);
        const uint32_t sd = (sb & 0x3FFFF) >> 4;
        int t[2][64];
        wg_fence();
#pragma unroll 1
        for (int s = 0; s < 16; s++) {
            const uint32_t db = ((sd + (SM_RING >> 4)) | (8 << 16)) + s * 256, da = ((sd + (SM_A >> 4)) | (1 << 16)) + ((s & 3) * 4 + wg * 2) * 512;
            mbar_wait(bars + (C_FULL + s * 2 + wg) * 8);
            wgmma_t128(t[0], db, da, s);
            wgmma_t128(t[1], db, da + 512, s);
            wgmma_t128(t[0], db + 16, da + 2, 1);
            wgmma_t128(t[1], db + 16, da + 514, 1);
            wg_commit();
            wg_wait<0>();
            if (elect_one()) mbar_arrive(bars + (C_EMPTY + s * 2 + wg) * 8);
        }
        asm volatile("bar.sync %0, 128;" :: "r"(3 + wg) : "memory");
        const uint32_t st0 = sb + SM_A + wg * 16384 + r0 * 128 + (((c0 >> 3) ^ r0) << 4) + (c0 & 7) * 2;
#pragma unroll
        for (int h = 0; h < 4; h++) {
            const uint32_t off = (h >> 1) * 32768 + (h & 1) * 8192;
#pragma unroll
            for (int q = 0; q < 8; q++) {
                const int o = (h & 1) * 32 + q * 4;
                sts32(st0 + off + q * 1024, epi(t[h >> 1][o], t[h >> 1][o + 2], zc, sx2, sw, bi));
                sts32((st0 ^ (5 * 128 + 5 * 16)) + off + q * 1024, epi(t[h >> 1][o + 1], t[h >> 1][o + 3], zc, sx2, sw, bi));
            }
            asm volatile("fence.proxy.async.shared::cta;" ::: "memory");
            asm volatile("bar.sync %0, 128;" :: "r"(3 + wg) : "memory");
            if (w == 0 && elect_one()) tile_store(maps.m + 2, N_ - WB, j * 512 + wg * 256 + h * 64, sb + SM_A + wg * 16384 + off);
        }
        if (w == 0) {
            asm volatile("cp.async.bulk.commit_group;" ::: "memory");
            asm volatile("cp.async.bulk.wait_group.read 0;" ::: "memory");
        }
        asm volatile("bar.sync 1, 256;" ::: "memory");
        if (threadIdx.x == 0) flag_add(epoch(sc, j * 4, 8));
    }
}

template <bool k2>
__global__ void __cluster_dims__(k2 ? 2 : CS, 1, 1) __launch_bounds__(512, 1)
w8a8_kernel(Scratch* sc, const char* __restrict__ qx, const char* __restrict__ qw, const __nv_bfloat16* __restrict__ scale_x, const int* __restrict__ zero_x,
            const __nv_bfloat16* __restrict__ scale_w, const __nv_bfloat16* __restrict__ bias, const __grid_constant__ Maps maps) {
    extern __shared__ __align__(1024) unsigned char smem_raw[];
    constexpr int NBJ = k2 ? 12 : 14, NF = NBJ, NU = k2 ? 40 : 48;
    constexpr int X1 = k2 ? CFG_X2 : CFG_X1;
    const int b = blockIdx.x + (k2 ? NCTA : 0), r = b & 15, c = k2 ? NCL : b >> 4;
    const unsigned tc = clk();
    if (!k2) {
        const int a = (r * NCL + c) ^ REV;
        const unsigned off = ((a & 63) * 32 + (threadIdx.x >> 1)) * (K_ * 4) + (a >> 6) * 256 + (threadIdx.x & 1) * 128;
        asm volatile("{\n.reg .pred p;\n.reg .b64 a;\nsetp.lt.u32 p, %2, 64;\n@!p bra PF_DONE;\ncvt.u64.u32 a, %1;\nadd.u64 a, a, %0;\nprefetch.global.L2 [a];\nPF_DONE:\n}"
                     :: "l"(qx), "r"(off), "r"(threadIdx.x));
    }
    const uint32_t sb = (uint32_t)__cvta_generic_to_shared(smem_raw);
    const uint32_t bars = sb + SM_BAR;
    const unsigned tw = __shfl_sync(~0u, (tc & ~15u) | threadIdx.x >> 5, 0), t0 = tw + (k2 ? 0 : T0);
    const int warp = tw & 15, lane = threadIdx.x & 31;

    if (!k2 && warp == 12) {
        const int a = r * NCL + c;
        if (elect_one()) {
            mbar_init(bars + (B_RAWA + 3) * 8, 1);
            mbar_expect_tx(bars + (B_RAWA + 3) * 8, 8192);
            raw_load(maps.m, (a >> 6) * 2, ((a ^ REV) & 63) * 32, sb + SM_A + (a < NAJ % NCTA ? 15 : 13) * 8192, bars + (B_RAWA + 3) * 8);
        }
        __syncwarp();
    }
    if (!k2 && (warp >> 1) == 1 && r < CFG_PG) {
        const int a = (NCTA + r * NCL + c) ^ REV;
        const char* p = qx + ((a & 63) * 32 + (warp & 1) * 16 + (lane >> 1)) * (K_ * 4) + (a >> 6) * 256 + (lane & 1) * 128;
        while ((int)(t0 + (16 + r) * P1 - clk()) > 0) ;
        asm volatile("prefetch.global.L2 [%0];" :: "l"(p));
    }
    if (warp == 9 && elect_one()) asm volatile("prefetch.tensormap [%0];" :: "l"(maps.m + 1) : "memory");
    if (k2 && blockIdx.x >= 16) {
        last_columns(sc, maps, scale_x, zero_x, scale_w, bias, sb, warp, lane, t0);
        return;
    }
    if (warp >= 12) {
        const int isw = k2 || warp == 14, t = k2 ? warp - 12 : isw ? 0 : (warp - 11) >> 1;
        const uint32_t bar = bars + ((isw ? B_RAWB : B_RAWA) + 3 + t) * 8;
        if ((k2 || warp != 12) && elect_one()) { mbar_init(bar, 1); mbar_expect_tx(bar, 8192); }
        __syncwarp();
        cluster_arrive();
        const int x = t * 16 + r, a = (x * NCL + c) ^ REV, sx = (x * 26) >> 8;
        static_assert(X1 >= 7, "");
        if ((k2 || warp != 12) && elect_one()) {
            const unsigned te = t0 + (k2 ? sched2(x) : (isw ? time_w(x) : time_x(x)) * P1);
            while ((int)(te - clk()) > 0) ;
            raw_load(maps.m + isw, isw ? sx * 64 : (a >> 6) * 2,
                     isw ? c * (TN / 32) + (int)((0x9765483210ull >> ((x - sx * 10) * 4)) & 15) : (a & 63) * 32,
                     sb + (k2 ? SM_A + 7 * 8192 : isw ? SM_STG : SM_A + 13 * 8192) + (t - (!isw && r * NCL + c < NAJ % NCTA)) * 8192, bar);
        }
        __syncwarp();
        if (!k2 && warp == 15) cluster_wait();
    }
    if (warp < 8) {
        const uint32_t p = bars + warp * 104;
        if (elect_one()) {
#pragma unroll
            for (int i = 0; i < 13; i++) mbar_init(p + i * 8, (!k2 && ((warp == 6 && i == 12) || (warp == 7 && i < 2))) ? 2 : 1);
            static_assert(B_FREE == 90, "");
        }
        __syncwarp();
        const int i = warp * 13 + lane;
        if (lane < 13 && i < B_SW) mbar_expect_tx(p + lane * 8, i >= B_PAR ? (i < B_PAR + 2 ? WA * 2 : WB * 2) : (i & 16) || i >= 48 ? 8192 : WA * 64);
        fence_init();
    }
    if (warp < 8 || warp == 10) cluster_arrive();
    if (!k2 && warp == 10 && lane < CFG_PF7) {
        const int n = b * CFG_PF7 + lane, row = n / 10;
        asm volatile("prefetch.global.L2 [%0];" :: "l"(qw + row * (N_ * 4) + NCL * TN * 4 + (n - row * 10) * 128));
    }

    if (warp < 8) {
        asm volatile("setmaxnreg.inc.sync.aligned.u32 200;");
        const int wg = warp >> 2;
        const uint32_t sd = (sb & 0x3FFFF) >> 4;
        const uint32_t sx2 = (uint32_t)__ldg((const unsigned short*)scale_x) * 0x10001u;
        const uint32_t par = sb + SM_PAR + (lane & 3) * 16 + wg * 256;
        const uint32_t go = bars + B_GO * 8;
        const int w = warp & 3, pq = (lane >> 2) ^ (lane & 4);
        uint32_t so = (w * 16 + pq) * 128 + (((lane & 3) ^ pq) << 4);
        const int c0 = (w >> 1) * 32 + (lane >> 2) * 4 + (w & 1) * 2, r0 = (lane & 3) * 2;
        uint32_t pp = sb + SM_PAR + (2 * WA + wg * WB + c0) * 2, st0 = r0 * 128 + (((c0 >> 3) ^ r0) << 4) + (c0 & 7) * 2;
        uint32_t rq = k2 ? mapa(go + 19 * 16, 1) : mapa(go + (12 + (lane >> 4)) * 16, lane & 15);
        int rk = k2 ? (lane ? 99 : 1) : (lane >> 2) + 1;
        asm volatile("" : "+r"(so), "+r"(pp), "+r"(st0), "+r"(rq), "+r"(rk));
        cluster_wait();
        int a0[WA / 2], a1[WA / 2];
        uint32_t barB = bars + (B_FULLB + wg * 32) * 8;
        int ra = -1;
        const int lq = lane < (k2 ? 1 : 5) ? lane : -1000;
        wg_fence();
        {
            uint64_t tbl = wg ? slot_table(X1, 1) : slot_table(X1, 0);
            uint32_t da = (sd + (SM_A >> 4)) | (1 << 16);
            bool rdy = false;
#pragma unroll 1
            for (int s = 0; s < 16; s++) {
                const uint32_t db = ((sd + (SM_RING >> 4)) | (8 << 16)) + ((uint32_t)tbl & 15) * (SLOT >> 4);
                const bool hold = wg && s == X1;
                if (hold || (!rdy && !mbar_test2(bars + (B_FULLA + s) * 8, barB))) {
                    wg_wait<0>();
                    release(ra); ra = -1;
                    mbar_wait2(bars + (B_FULLA + s) * 8, barB);
                    if (hold) asm volatile("bar.sync 7, 256;" ::: "memory");
                }
                wgmma_n160(a0, da, db, s);
                wgmma_n160(a1, da + 256, db, s);
                wg_commit();
                if (!wg && s == 15) asm volatile("bar.arrive 7, 256;" ::: "memory");
                wg_wait<1>();
                release(ra);
                wgmma_n160(a0, da + 2, db + 16, 1);
                wgmma_n160(a1, da + 258, db + 16, 1);
                wg_commit();
                ra = release_addr<k2>(sb, s < X1 ? 2 * s + wg : (wg ? 16 : X1) + s, lq);
                tbl >>= 4; da += 512; barB += 8;
                rdy = mbar_test2(bars + (B_FULLA + s + 1) * 8, barB);
                if (s < 15) wg_wait<1>();
            }
        }
        mbar_wait2(bars + (B_PAR + wg) * 8, bars + B_SW * 8);
        const Par P0 = ld_par(par), P1 = ld_par(par + 64);
        wg_wait<0>();
        release(ra);
        bool ready = mbar_test(barB);
#define FILL_BEGIN(n0, n1) mbar_wait(bars + (B_FREE + (wg ? n1 : n0)) * 8);                                             \
                           const uint32_t buf = sb + SM_STG + (wg ? (turn<k2>(n1) + NBJ) % 3 : (turn<k2>(n0) + NBJ) % 3) * 8192;
#define FILL_END(n0, n1) __syncwarp();                                                                                  \
                         if (elect_one()) mbar_arrive(bars + (B_FILL + (wg ? turn<k2>(n1) : turn<k2>(n0))) * 8);
#define FILL_PAIR(a, J, P, Q, m, MID)                                                                                   \
        {                                                                                                               \
            const uint4 v0 = epi_row(a, J * 16, P, sx2), v1 = epi_row(a, J * 16 + 2, P, sx2);                           \
            FILL_BEGIN(ford<k2>(0, m), ford<k2>(1, m))                                                                  \
            sts128(buf + so, v0); sts128(buf + so + 1024, v1);                                                          \
            MID                                                                                                         \
            sts128(buf + (so ^ 64), epi_row(a, J * 16 + 16, Q, sx2));                                                   \
            sts128(buf + (so ^ 64) + 1024, epi_row(a, J * 16 + 18, Q, sx2));                                            \
            FILL_END(ford<k2>(0, m), ford<k2>(1, m))                                                                    \
        }
#define NARROW(p)                                                                                                       \
        {                                                                                                               \
            if (!ready) mbar_wait(barB);                                                                                \
            wg_fence();                                                                                                 \
            _Pragma("unroll 1") for (int i = 0; i < 8; i++) {                                                           \
                const uint32_t db = ((sd + (SM_RING >> 4)) | (8 << 16)) + (k2 ? (i > 2 ? i - 3 : i + 4) * (SLOT >> 4) : ((i + 5) & 7) * 512); \
                _Pragma("unroll") for (int kk = 0; kk < 4; kk++)                                                        \
                    wgmma_t128(t, db + (kk >> 1) * 256 + (kk & 1) * 16,                                                 \
                               ((sd + (SM_A >> 4)) | (1 << 16)) + i * 1024 + (kk >> 1) * 512 + (kk & 1) * 2, kk ? 1 : i); \
                wg_commit();                                                                                            \
                barB += 8;                                                                                              \
                mbar_wait(i < 7 ? barB : bars + (B_PAR + p) * 8);                                                       \
                wg_wait<1>();                                                                                           \
                if (p == 2 && rk == i) mbar_arrive_cluster(rq);                                                         \
            }                                                                                                           \
            if (p == 3 || k2) { zc = lds32(pp); sw = lds32(pp + TN * 2); bi = CFG_EPI == 3 ? 0 : lds32(pp + TN * 4); }               \
            wg_wait<0>();                                                                                               \
            if (p == 2 && rk == 8) mbar_arrive_cluster(rq);                                                             \
        }
        Par P2, P3, P;
        FILL_PAIR(a0, 0, P0, P1, 0, P2 = ld_par(par + 128);)
        FILL_PAIR(a1, 0, P0, P1, 1, P3 = ld_par(par + 192);)
        FILL_PAIR(a0, 2, P2, P3, 2, P = ld_par(par + 512 - wg * 192);)
        FILL_PAIR(a1, 2, P2, P3, 3, )
        int t[64];
        uint32_t zc, sw, bi;
        if (!k2 && wg == 0) NARROW(2)
        {
            const uint4 v0 = epi_row(a0, 64, P, sx2), v1 = epi_row(a0, 66, P, sx2);
            FILL_BEGIN(ford<k2>(0, 4), ford<k2>(1, 4))
            const uint32_t s4 = buf + ((so >> 1) & ~63u) + (lane & 3) * 16;
            sts128(s4, v0); sts128(s4 + 512, v1);
            sts128(s4 + 4096, epi_row(a1, 64, P, sx2)); sts128(s4 + 4608, epi_row(a1, 66, P, sx2));
            FILL_END(ford<k2>(0, 4), ford<k2>(1, 4))
        }
        if (!(k2 && wg)) {
            if (k2) NARROW(2) else if (wg) NARROW(3) else { zc = lds32(pp); sw = lds32(pp + TN * 2); bi = CFG_EPI == 3 ? 0 : lds32(pp + TN * 4); }
#define FILL_T(h)                                                                                                       \
            {                                                                                                           \
                FILL_BEGIN((10 + h), (12 + h))                                                                          \
                _Pragma("unroll") for (int j = 0; j < 8; j++) {                                                         \
                    const int o = h * 32 + j * 4;                                                                       \
                    sts32(buf + st0 + j * 1024, epi(t[o], t[o + 2], zc, sx2, sw, bi));                                  \
                    sts32(buf + (st0 ^ (5 * 128 + 5 * 16)) + j * 1024, epi(t[o + 1], t[o + 3], zc, sx2, sw, bi));       \
                }                                                                                                       \
                FILL_END((10 + h), (12 + h))                                                                            \
            }
            FILL_T(0) FILL_T(1)
        }
        if (threadIdx.x == 0) flag_add(epoch(sc, r, c));
    } else {
        const int g = r * NCL + c, na = k2 ? 0 : NAJ / NCTA + (g < NAJ % NCTA);
        int cw = NF;
        if (warp >= 12) {
            asm volatile("setmaxnreg.dec.sync.aligned.u32 80;");
            if (warp < 14) {
                const int c4 = (lane ^ (lane >> 3)) & 3, ln = ((lane >> 2) ^ (lane & 4)) * 2 + (c4 >> 1);
                const uint32_t rd0 = sb + SM_A + 13 * 8192 + ln * 128 + ((((c4 & 1) << 2) ^ (ln & 7)) << 4);
#pragma unroll 1
                for (int t = warp - 12, sl = na == 9 ? t : 2 - 2 * t; t < na; t += 2, sl = sl ? sl - 1 : 2) {
                    const uint32_t rdA = rd0 + sl * 8192;
                    const int a = (t * NCTA + g) ^ REV, f = (a & 60) * 4 + (a >> 6);
                    uint4* const d = sc->s8 + (f * 4 + (a & 3)) * 128 + lane;
                    unsigned* fl = sc->flag + (a & 60) * 8 + (a >> 6);
                    uint32_t fb = bars + ((t < na - 3 ? B_RAWA : B_AFREE + 13) + sl) * 8;
                    asm volatile("" : "+l"(fl), "+r"(fb));
                    uint4 o[4];
                    mbar_wait(bars + (B_RAWA + 3 + t) * 8);
#pragma unroll
                    for (int i = 0; i < 4; i++) {
                        uint4 v0 = lds128(rdA + i * 2048), v1 = lds128((rdA ^ 16) + i * 2048);
                        uint4 v2 = lds128((rdA ^ 32) + i * 2048), v3 = lds128((rdA ^ 48) + i * 2048);
                        o[i].x = pack4(v0.x, v0.y, v0.z, v0.w); o[i].y = pack4(v1.x, v1.y, v1.z, v1.w);
                        o[i].z = pack4(v2.x, v2.y, v2.z, v2.w); o[i].w = pack4(v3.x, v3.y, v3.z, v3.w);
                    }
#pragma unroll
                    for (int i = 0; i < 4; i++) stg128(d + i * 32, o[i]);
                    if (t >= 2 && elect_one()) mbar_arrive(fb);
                    __syncwarp();
                    const unsigned rb = read_back(d, lane);
                    asm volatile("fence.proxy.async.global;" ::: "memory");
                    __syncwarp();
                    publish(rb, o[0].x, fl);
                    if (t < 2) { cluster_wait(); if (elect_one()) mbar_arrive(fb); }
                }
                cw = warp - 12;
            }
            if (!k2) {
                const int hw = warp & 1;
                const uint32_t rd0 = sb + SM_STG + hw * 4096 + (lane >> 3) * 1024 + (lane & 7) * 16;
                const int myG = decode_b(X1, (lane & 15) * 16 + r).G;
                const uint64_t gt = (uint64_t)__reduce_or_sync(~0u, lane < 8 ? myG << (4 * lane) : 0) |
                                    (uint64_t)__reduce_or_sync(~0u, (lane >> 3) == 1 ? myG << (4 * (lane & 7)) : 0) << 32;
#pragma unroll 1
                for (int t = warp < 14 ? TA : 0; t < NBJ; t += warp < 14 ? NBJ : t == TA - 1 ? 2 : 1) {
                    const int sl = t % 3;
                    const uint32_t rdB = rd0 + sl * 8192;
                    char* const d = (char*)sc->s8 + (1024 + c * 256 + t * 16 + r) * 2048 + hw * 256 + (lane >> 4) * 128 + (lane & 7) * 16 + (lane & 8);
                    uint32_t fb = bars + (t >= NBJ - 3 ? B_FREE + t - (NBJ - 3) : B_RAWB + sl) * 8;
                    asm volatile("" : "+r"(fb));
                    uint2 o[4];
                    mbar_wait(bars + (B_RAWB + 3 + t) * 8);
                    CV_B(0, x) CV_B(1, y)
#pragma unroll
                    for (int i = 0; i < 4; i++) asm volatile("st.global.v2.b32 [%0], {%1,%2};" :: "l"(d + i * 512), "r"(o[i].x), "r"(o[i].y) : "memory");
                    if (t == 0 && warp == 14) cluster_wait();
                    if (elect_one()) mbar_arrive(fb);
                    asm volatile("fence.proxy.async.global;" ::: "memory");
                    __syncwarp();
                    if (elect_one()) mbar_arrive(bars + (B_GO + t * 2) * 8);
                    int cs[4];
#pragma unroll
                    for (int i = 0; i < 4; i++) cs[i] = sum4(o[i].x, sum4(o[i].y, 0));
                    const int p01 = cs[0] + cs[1] * 65536, p23 = cs[2] + cs[3] * 65536;
                    const bool h = lane & 16;
                    int x = (h ? p23 : p01) + __shfl_xor_sync(~0u, h ? p01 : p23, 16);
                    x += __shfl_xor_sync(~0u, x, 8);
                    const int lo = (int)(short)x, v = (lane & 8) ? (x - lo) >> 16 : lo;
                    const int G = (int)(gt >> (4 * t)) & 15;
                    if (G != r) {
                        red_async(mapa(sb + SM_CS + lane * 4, G), v, mapa(bars + B_CS * 8, G));
                    } else {
                        red_shared(sb + SM_CS + lane * 4, v);
                        __syncwarp();
                        if (elect_one()) mbar_arrive(bars + B_CS * 8);
                    }
                }
            } else {
                const uint32_t rd0 = sb + (lane >> 3) * 2048 + (lane & 7) * 16;
                const BJob mb = decode_b(X1, (lane & 15) * 16 + r);
                const int myG = mb.G | mb.u << 8;
#pragma unroll 1
                for (int t = warp - 12; t < NBJ; t += 4) {
                    const uint32_t rdB = rd0 + stage_w<k2>(t);
                    uint4* const d = sc->s8 + (1024 + c * 256 + t * 16 + r) * 128 + lane;
                    const int gu = __shfl_sync(~0u, myG, t);
                    uint4 o[4];
                    mbar_wait(bars + (B_RAWB + 3 + t) * 8);
                    CV_B(0, x) CV_B(1, y) CV_B(2, z) CV_B(3, w)
#pragma unroll
                    for (int i = 0; i < 4; i++) stg128(d + i * 32, o[i]);
                    if (t < 4) cluster_wait();
                    if (elect_one()) mbar_arrive(bars + (B_FREE + t - (NBJ - 3)) * 8);
                    asm volatile("fence.proxy.async.global;" ::: "memory");
                    __syncwarp();
                    const unsigned rb = read_back(d, lane), ep = ld_flag(epoch(sc, r, c));
                    int cs[4];
#pragma unroll
                    for (int i = 0; i < 4; i++) cs[i] = sum4(o[i].x, sum4(o[i].y, sum4(o[i].z, sum4(o[i].w, 0))));
                    const bool h = lane & 16, odd = lane & 8;
                    int x = (h ? cs[2] : cs[0]) + __shfl_xor_sync(~0u, h ? cs[0] : cs[2], 16);
                    int y = (h ? cs[3] : cs[1]) + __shfl_xor_sync(~0u, h ? cs[1] : cs[3], 16);
                    const int v = (odd ? y : x) + __shfl_xor_sync(~0u, odd ? x : y, 8);
                    publish(rb, o[0].x, sc->flag + F_W + (gu >> 8));
                    const int old = atomicAdd(sc->cs[ep & 1] + col_of(gu & 255) + (lane & 7) * 4 + (lane >> 3), v);
                    if (old == 0x7FFFFFFF) sc->sink[0] = old;
                    __syncwarp();
                    if (elect_one()) flag_add(sc->flag + F_CS + (gu & 255) / 5);
                }
            }
        } else {
            asm volatile("setmaxnreg.dec.sync.aligned.u32 32;");
            if (warp == 11) {
                if (elect_one()) {
#pragma unroll
                    for (int i = 0; i < (k2 ? NU / 2 : NBJ); i++)
                        mbar_init(bars + (B_GO + i * 2) * 8, k2 ? (i * 2 + (r & 1) >= NSLOT ? 9 : 1)
                                                         : 2 + 4 * CS * ((i * 16 + r >= NSLOT * 5) + (i == 10 && r >= 12 && r < 15)));
#pragma unroll
                    for (int i = 0; i < 3; i++) mbar_init(bars + (B_FILL + i) * 8, 4);
                }
                const int u2 = lane * 2 + (r & 1), q = k2 ? (u2 < 32 ? 5 * u2 : 4 * u2 + 32) : (lane & 15) * 16 + r;
                const BJob bj = decode_b(X1, q);
                unsigned seen = 0;
                if (!k2) {
                    const int nself = __popc(__ballot_sync(~0u, lane < NBJ && bj.G == r));
                    sts32(sb + SM_CS + lane * 4, 0);
                    if (lane == 0) {
                        mbar_init(bars + B_CS * 8, 1 + 2 * nself);
                        mbar_expect_tx(bars + B_CS * 8, (16 - nself) * 256);
                    }
                    seen = lds32(sb + SM_CS + lane * 4);
                }
                fence_init();
                asm volatile("barrier.cluster.arrive.relaxed.aligned;" :: "r"(seen) : "memory");
                const char* src = (const char*)sc->s8 + (1024 + c * 256 + q) * 2048;
                const uint32_t dst = sb + SM_RING + ((!k2 && q >= 160) ? ((q + 20) & 31) * 2048 : (bj.u % NSLOT) * SLOT + bj.pos * 2048);
                const uint32_t fb = bars + (B_FULLB + fb_of(X1, bj.u)) * 8;
                cluster_wait();
                if (!k2) scale_bias(scale_x, scale_w + c * TN, bias + c * TN, sb, lane);
#pragma unroll 1
                for (int i = 0; i < (k2 ? NU / 2 : NBJ); i++) {
                    mbar_wait(bars + (B_GO + i * 2) * 8);
                    if (lane == i) {
                        asm volatile("cp.async.bulk.shared::cluster.global.mbarrier::complete_tx::bytes.multicast::cluster [%0], [%1], %2, [%3], %4;"
                                     :: "r"(dst), "l"(src), "r"(k2 ? (u2 < 32 ? SLOT : 8192) : 2048), "r"(fb), "h"((uint16_t)(k2 ? 3 : 0xFFFF)) : "memory");
                    }
                    __syncwarp();
                }
            } else if (warp == 10) {
                const unsigned ep = (__shfl_sync(~0u, ld_flag(sc->flag + r * 32 + (lane < 16 ? lane : 16 + c)), 16) + 1) * 4;
                const unsigned* f = sc->flag + r * 32 + (lane & 15);
                bool dn = lane >= 16;
                const bool fr = lane < (k2 ? 7 : 13);
                cluster_wait();
                for (int it = 0;; it++) {
                    const unsigned v = ld_flag(f);
                    if (!dn && (int)(v - ep) >= 0 && (fr || mbar_test(bars + (B_AFREE + lane) * 8))) {
                        dn = true;
                        tile_load(sc, sb + SM_A + lane * 8192, r * 16 + lane, bars + (B_FULLA + lane) * 8);
                    }
                    if (__all_sync(~0u, dn)) break;
                    if (it > (1 << 22)) __trap();
                }
            } else {
                const bool isw = warp == 9;
                const uint32_t rb = bars + (isw ? B_RAWB : B_RAWA) * 8;
                if (elect_one()) {
#pragma unroll
                    for (int i = 0; i < 13; i++) if (i < 3 || i >= (k2 ? 7 : 6)) mbar_init(rb + i * 8, (i < 3 && isw && !k2) ? 2 : 1);
                    if (isw) {
#pragma unroll
                        for (int i = 13; i < 17; i++) mbar_init(rb + i * 8, 1);
                        if (!k2) { mbar_init(rb + 4 * 8, 1); mbar_init(rb + 5 * 8, 1); }
                    }
                }
                __syncwarp();
                const int nj = isw ? NBJ : na, j0 = k2 ? 4 : isw ? 1 : 3;
                if (lane >= j0 && lane < nj) mbar_expect_tx(rb + (3 + lane) * 8, 8192);
                fence_init();
                cluster_arrive();
                const unsigned e0 = k2 ? ld_flag(epoch(sc, r, c)) : 0;
                const int k = lane / 3, x = lane * 16 + r;
                int sl = lane - k * 3, y, z, T;
                if (isw) {
                    const BJob bj = decode_b(X1, x & 255);
                    y = bj.slab * 64; z = (c * TN + col_of(bj.G)) >> 5; T = time_w(x);
                } else {
                    const int a = (lane * NCTA + g) ^ REV;
                    y = (a >> 6) * 2; z = (a & 63) * 32; T = time_x(x);
                    if (na == 10) sl = sl ? sl - 1 : 2;
                }
                const unsigned te = t0 + (k2 ? sched2(x) : sched(T));
                const uint32_t sd = sb + (isw ? stage_w<k2>(lane) : SM_A + (13 + sl) * 8192);
#pragma unroll 1
                for (int t = j0; t < nj; t++) {
                    if (lane == t) {
                        if (t >= 3 && !k2) mbar_wait(rb + sl * 8, (k & 1) ^ 1);
                        while ((int)(te - clk()) > 0) ;
                        raw_load(maps.m + isw, y, z, sd, rb + (3 + t) * 8);
                    }
                    __syncwarp();
                }
                cluster_wait();
                if (elect_one()) asm volatile("prefetch.tensormap [%0];" :: "l"(maps.m + 2 + isw) : "memory");
                if (!isw) cw = 2;
                if (k2) {
                    if (!isw) {
                        if (lane < TN / 16) sc->cs[(e0 & 1) ^ 1][r * (TN / 16) + lane] = 0;
                        const int u = lane * 2 + (r & 1);
                        const unsigned tg = (e0 + 1) * (u < 32 ? 5 : 4);
                        bool dn = u >= NU;
                        for (int it = 0;; it++) {
                            if (!dn && (int)(ld_flag(sc->flag + F_W + u) - tg) >= 0) {
                                dn = true;
                                mbar_arrive(bars + (B_GO + lane * 2) * 8);
                            }
                            if (__all_sync(~0u, dn)) break;
                            if (it > (1 << 22)) __trap();
                        }
                    } else {
                        const float zxf = ld_zx(zero_x);
                        scale_bias(scale_x, scale_w + c * TN, bias + c * TN, sb, lane);
#pragma unroll 1
                        for (int h = 0; h < 3; h++) {
                            for (int it = 0; (int)(ld_flag(sc->flag + F_CS + h) - (e0 + 1) * (h < 2 ? 80 : 32)) < 0; it++) if (it > (1 << 22)) __trap();
                            int2 v[3];
                            int i[3];
#pragma unroll
                            for (int j = 0; j < 3; j++) {
                                i[j] = (j < 2 ? h * 64 + j * 32 : 128 + h * 16) + lane;
                                v[j] = __ldcg((const int2*)sc->cs[e0 & 1] + i[j]);
                            }
#pragma unroll
                            for (int j = 0; j < 3; j++) {
                                const uint32_t pa = sb + SM_PAR + i[j] * 4;
                                const uint32_t z = fold(zero_term(v[j].x, v[j].y, zxf), lds32(pa + TN * 2), lds32(pa + TN * 4));
                                if (h < 2 ? (j < 2 || lane < 16) : j == 2) st_async(pa, z, bars + (B_PAR + h) * 8);
                            }
                        }
                    }
                }
            }
        }
        if (!k2 && r < NBJ && warp == (r < 10 ? 8 : 10)) {
            const float zxf = ld_zx(zero_x);
            const int w = lane & 15;
            uint32_t sw = 0, bi = 0;
            if (CFG_EPI == 3) { mbar_wait(bars + B_SW * 8); sw = lds32(sb + SM_PAR + TN * 2 + col_of(r) * 2 + w * 4); bi = lds32(sb + SM_PAR + TN * 4 + col_of(r) * 2 + w * 4); }
            mbar_wait(bars + B_CS * 8);
            const uint32_t ca = sb + SM_CS + ((w >> 1) + (w & 1) * 16) * 4;
            const uint32_t z = fold(zero_term(lds32(ca), lds32(ca + 32), zxf), sw, bi);
            const int piece = r < 10 ? (r >= 5) : (r - 6) >> 1;
#pragma unroll 1
            for (int i = lane >> 4; i < CS; i += 2) st_async(mapa(sb + SM_PAR + col_of(r) * 2 + w * 4, i), z, mapa(bars + (B_PAR + piece) * 8, i));
        }
#pragma unroll 1
        for (int n = cw, nn, k = 0; n < NF; n = nn, k ^= 1) {
            nn = n + 3;
            if (!k2 && n < 5 && nn >= 5) nn += nn == 5 ? 2 : -1;
            const int gm = (int)(ford_table<k2>() >> (4 * n)), g = (gm >> 3) & 1, m = gm & 7;
            const int x = n >= 10 ? (n >> 1) * 64 : m == 4 ? 256 + g * 32 : g * 128 + (m & 2) * 32;
            const int y = n >= 10 ? (n & 1) * 64 : (m & 1) * 64;
            mbar_wait(bars + (B_FILL + cw) * 8, k);
            asm volatile("fence.proxy.async.shared::cta;" ::: "memory");
            if (elect_one()) tile_store(maps.m + (n < 10 && m == 4 ? 3 : 2), c * TN + x, r * 128 + y, sb + SM_STG + ((cw + NBJ) % 3) * 8192);
            asm volatile("cp.async.bulk.commit_group;" ::: "memory");
            asm volatile("cp.async.bulk.wait_group.read 0;" ::: "memory");
            __syncwarp();
            if (nn < NF && elect_one()) mbar_arrive(bars + (B_FREE + nn) * 8);
        }
    }
}

__global__ void __launch_bounds__(256)
w8a8_plain(const int* __restrict__ qx, const int* __restrict__ qw, const __nv_bfloat16* __restrict__ scale_x, const int* __restrict__ zero_x,
           const __nv_bfloat16* __restrict__ scale_w, const __nv_bfloat16* __restrict__ bias, __nv_bfloat16* __restrict__ out) {
    __shared__ int xs[16][K_ / 4];
    const int n = (blockIdx.x * 256 + threadIdx.x) * 2, m0 = blockIdx.y * 16;
    for (int i = threadIdx.x; i < 16 * K_ / 4; i += 256) {
        const uint4 v = ((const uint4*)qx)[m0 * (K_ / 4) + i];
        xs[i / (K_ / 4)][i % (K_ / 4)] = pack4(v.x, v.y, v.z, v.w);
    }
    __syncthreads();
    int acc[16][2] = {}, cs[2] = {};
    for (int k = 0; k < K_ / 4; k++) {
        uint2 v[4];
#pragma unroll
        for (int i = 0; i < 4; i++) v[i] = *(const uint2*)(qw + (k * 4 + i) * N_ + n);
        const unsigned w0 = pack4(v[0].x, v[1].x, v[2].x, v[3].x), w1 = pack4(v[0].y, v[1].y, v[2].y, v[3].y);
        cs[0] = sum4(w0, cs[0]); cs[1] = sum4(w1, cs[1]);
#pragma unroll
        for (int i = 0; i < 16; i++) { acc[i][0] = __dp4a(xs[i][k], (int)w0, acc[i][0]); acc[i][1] = __dp4a(xs[i][k], (int)w1, acc[i][1]); }
    }
    const uint32_t sx2 = (uint32_t)*(const unsigned short*)scale_x * 0x10001u, bi = *(const unsigned*)(bias + n);
    uint32_t sw = *(const unsigned*)(scale_w + n);
    if (CFG_EPI) sw = bf2_mul(sw, sx2);
    const uint32_t zc = fold(zero_term(cs[0], cs[1], ld_zx(zero_x)), sw, bi);
#pragma unroll
    for (int i = 0; i < 16; i++) *(unsigned*)(out + (m0 + i) * N_ + n) = epi(acc[i][0], acc[i][1], zc, sx2, sw, bi);
}

}

typedef CUresult (*EncodeFn)(CUtensorMap*, CUtensorMapDataType, cuuint32_t, void*, const cuuint64_t*, const cuuint64_t*,
                             const cuuint32_t*, const cuuint32_t*, CUtensorMapInterleave, CUtensorMapSwizzle,
                             CUtensorMapL2promotion, CUtensorMapFloatOOBfill);

extern "C" void kernel_launch(void* const* d_in, const int* in_sizes, int n_in, void* d_out, int out_size) {
    using namespace w8;
    static EncodeFn encode = nullptr;
    static cudaStream_t side;
    static cudaEvent_t started, joined;
    static int clusters = -1;
    static Scratch* sc;
    cudaLaunchConfig_t cfg = {};
    cfg.gridDim = dim3(NCTA); cfg.blockDim = dim3(512); cfg.dynamicSmemBytes = SM_TOTAL; cfg.stream = cudaStreamPerThread;
    if (clusters < 0) {
        void* fn = nullptr;
        cudaDriverEntryPointQueryResult qr;
        cudaGetDriverEntryPoint("cuTensorMapEncodeTiled", &fn, cudaEnableDefault, &qr);
        encode = (EncodeFn)fn;
        cudaGetSymbolAddress((void**)&sc, g_scratch);
        cudaStreamCreateWithFlags(&side, cudaStreamNonBlocking);
        cudaEventCreateWithFlags(&started, cudaEventDisableTiming);
        cudaEventCreateWithFlags(&joined, cudaEventDisableTiming);
        cudaFuncSetAttribute(w8a8_kernel<false>, cudaFuncAttributeMaxDynamicSharedMemorySize, SM_TOTAL);
        cudaFuncSetAttribute(w8a8_kernel<true>, cudaFuncAttributeMaxDynamicSharedMemorySize, SM_TOTAL);
        cudaFuncSetAttribute(w8a8_kernel<false>, cudaFuncAttributeNonPortableClusterSizeAllowed, 1);
        if (cudaOccupancyMaxActiveClusters(&clusters, w8a8_kernel<false>, &cfg) != cudaSuccess) { clusters = 0; cudaGetLastError(); }
    }
    const __nv_bfloat16 *sx = (const __nv_bfloat16*)d_in[2], *sw = (const __nv_bfloat16*)d_in[4], *bias = (const __nv_bfloat16*)d_in[5];
    const int* zx = (const int*)d_in[3];
    if (clusters < NCL) {
        w8a8_plain<<<dim3(N_ / 512, M_ / 16), 256, 0, cudaStreamPerThread>>>((const int*)d_in[0], (const int*)d_in[1], sx, zx, sw, bias, (__nv_bfloat16*)d_out);
        return;
    }
    Maps maps;
    const cuuint32_t es[3] = {1, 1, 1};
    {
        const cuuint64_t dim[3] = {32, K_ / 32, M_}, str[2] = {128, K_ * 4};
        const cuuint32_t box[3] = {32, 2, 32};
        encode(&maps.m[0], CU_TENSOR_MAP_DATA_TYPE_INT32, 3, d_in[0], dim, str, box, es, CU_TENSOR_MAP_INTERLEAVE_NONE,
               CU_TENSOR_MAP_SWIZZLE_128B, CU_TENSOR_MAP_L2_PROMOTION_NONE, CU_TENSOR_MAP_FLOAT_OOB_FILL_NONE);
    }
    {
        const cuuint64_t dim[3] = {32, K_, N_ / 32}, str[2] = {N_ * 4, 128};
        const cuuint32_t box[3] = {32, 64, 1};
        encode(&maps.m[1], CU_TENSOR_MAP_DATA_TYPE_INT32, 3, d_in[1], dim, str, box, es, CU_TENSOR_MAP_INTERLEAVE_NONE,
               CU_TENSOR_MAP_SWIZZLE_NONE, CU_TENSOR_MAP_L2_PROMOTION_NONE, CU_TENSOR_MAP_FLOAT_OOB_FILL_NONE);
    }
    for (int i = 0; i < 2; i++) {
        const cuuint64_t dim[2] = {N_, M_}, str[1] = {N_ * 2};
        const cuuint32_t box[2] = {i ? 32u : 64u, i ? 128u : 64u};
        encode(&maps.m[2 + i], CU_TENSOR_MAP_DATA_TYPE_BFLOAT16, 2, d_out, dim, str, box, es, CU_TENSOR_MAP_INTERLEAVE_NONE,
               i ? CU_TENSOR_MAP_SWIZZLE_NONE : CU_TENSOR_MAP_SWIZZLE_128B, CU_TENSOR_MAP_L2_PROMOTION_NONE, CU_TENSOR_MAP_FLOAT_OOB_FILL_NONE);
    }
    cudaLaunchAttribute at;
    at.id = cudaLaunchAttributeProgrammaticEvent;
    at.val.programmaticEvent.event = started; at.val.programmaticEvent.flags = 0; at.val.programmaticEvent.triggerAtBlockStart = 1;
    cfg.attrs = &at; cfg.numAttrs = 1;
    cudaLaunchKernelEx(&cfg, w8a8_kernel<false>, sc, (const char*)d_in[0], (const char*)d_in[1], sx, zx, sw, bias, maps);
    cudaStreamWaitEvent(side, started, 0);
    cfg.gridDim = dim3(20); cfg.stream = side; cfg.numAttrs = 0;
    cudaLaunchKernelEx(&cfg, w8a8_kernel<true>, sc, (const char*)d_in[0], (const char*)d_in[1], sx, zx, sw, bias, maps);
    cudaEventRecord(joined, side);
    cudaStreamWaitEvent(cudaStreamPerThread, joined, 0);
}
```

```cpp
#include <cuda_runtime.h>
#include <cuda.h>
#include <cuda_bf16.h>
#include <stdint.h>
#include <stddef.h>

#define CFG_X1 13
#define CFG_P1 46
#define CFG_P2 39
#define CFG_PT 100
#define CFG_L0 35
#define CFG_RA 34
#define CFG_T0 -590
#define CFG_Q0 14
#define CFG_Q2 69
#define CFG_Q3 30
#define CFG_T3 400
#define CFG_D3 2
#define CFG_PF7 18
#define CFG_TA 10
#define CFG_EPI 3
#define CFG_X2 11
#define CFG_S3 10
#define CFG_D4 4
#define CFG_PG 8

namespace w8 {

constexpr int M_ = 2048, K_ = 1024, N_ = 3584;
constexpr int CS = 16, NCL = 7, NCTA = CS * NCL;
constexpr int WA = 160, WB = 64, TN = 2 * WA + 2 * WB;
constexpr int NSLOT = 7, SLOT = WA * 64;
constexpr int NAJ = 1024;
constexpr int REV = 60;
constexpr int TA = CFG_TA;

constexpr int L0 = CFG_L0, RA = CFG_RA, RB64 = 64 * RA / (RA - 16);
constexpr int P1 = CFG_P1, P2 = CFG_P2, PT = CFG_PT, T0 = CFG_T0;
__device__ __forceinline__ int time_x(int x) { return max(x, L0 + (((x - L0) * RA) >> 4)); }
__device__ __forceinline__ int time_w(int q) { return min(L0 + ((q * RB64) >> 6), NAJ / NCL + q); }
__device__ __forceinline__ unsigned sched(int T) { return T * P2 + min(T, PT) * (P1 - P2); }
__device__ __forceinline__ int sched2(int q) { return (min(q, 160) - CFG_Q0) * CFG_Q2 + max(q - 160, 0) * CFG_Q3; }

constexpr int SM_A = 0;
constexpr int SM_RING = 131072;
constexpr int SM_STG = SM_RING + NSLOT * SLOT;
constexpr int SM_PAR = SM_STG + 3 * 8192;
constexpr int SM_CS = SM_PAR + 3 * TN * 2;
constexpr int SM_BAR = SM_CS + 128;
constexpr int B_FULLB = 0, B_FULLA = 56, B_PAR = 72, B_SW = 77, B_AFREE = 74  , B_FREE = 90,
              B_FILL = 128, B_CS = 131, B_RAWA = 132, B_RAWB = 145, B_GO = 164  , B_END = 204;
constexpr int SM_TOTAL = SM_BAR + B_END * 8;
static_assert(SM_TOTAL <= 232448, "");

constexpr int F_W = 512, F_CS = 576;
struct Scratch {
    unsigned flag[768];
    int cs[2][TN];
    int sink[384];
    uint4 s8[(1024 + 8 * 256) * 128];
};
static_assert(offsetof(Scratch, s8) == 8192, "");
__device__ __align__(8192) Scratch g_scratch;
__device__ __forceinline__ unsigned* epoch(Scratch* sc, int r, int c) { return sc->flag + r * 32 + 16 + c; }

__device__ __forceinline__ void mbar_init(uint32_t bar, uint32_t cnt) {
    asm volatile("mbarrier.init.shared::cta.b64 [%0], %1;" :: "r"(bar), "r"(cnt) : "memory");
}
__device__ __forceinline__ void mbar_expect_tx(uint32_t bar, uint32_t bytes) {
    asm volatile("mbarrier.arrive.expect_tx.shared::cta.b64 _, [%0], %1;" :: "r"(bar), "r"(bytes) : "memory");
}
__device__ __forceinline__ void mbar_arrive(uint32_t bar) {
    asm volatile("mbarrier.arrive.shared::cta.b64 _, [%0];" :: "r"(bar) : "memory");
}
__device__ __forceinline__ void mbar_arrive_cluster(uint32_t bar) {
    asm volatile("mbarrier.arrive.shared::cluster.b64 _, [%0];" :: "r"(bar) : "memory");
}
__device__ __forceinline__ void mbar_wait(uint32_t bar, uint32_t parity = 0) {
    asm volatile("{\n.reg .pred p;\n.reg .u32 c;\n"
                 "mbarrier.try_wait.parity.shared::cta.b64 p, [%0], %1;\n"
                 "@p bra WAIT_DONE;\n"
                 "mov.u32 c, 0;\n"
                 "WAIT_LOOP:\n"
                 "mbarrier.try_wait.parity.shared::cta.b64 p, [%0], %1;\n"
                 "@p bra WAIT_DONE;\n"
                 "add.u32 c, c, 1;\nsetp.lt.u32 p, c, 0x100000;\n"
                 "@p bra WAIT_LOOP;\n"
                 "trap;\n"
                 "WAIT_DONE:\n}" :: "r"(bar), "r"(parity) : "memory");
}
__device__ __forceinline__ void mbar_wait2(uint32_t bar0, uint32_t bar1) {
    asm volatile("{\n.reg .pred p, q;\n.reg .u32 c;\nmov.u32 c, 0;\n"
                 "WAIT_LOOP:\n"
                 "mbarrier.try_wait.parity.shared::cta.b64 p, [%0], 0;\n"
                 "mbarrier.try_wait.parity.shared::cta.b64 q, [%1], 0;\n"
                 "and.pred p, p, q;\n"
                 "@p bra WAIT_DONE;\n"
                 "add.u32 c, c, 1;\nsetp.lt.u32 p, c, 0x100000;\n"
                 "@p bra WAIT_LOOP;\n"
                 "trap;\n"
                 "WAIT_DONE:\n}" :: "r"(bar0), "r"(bar1) : "memory");
}
__device__ __forceinline__ bool mbar_test(uint32_t bar) {
    uint32_t ok;
    asm volatile("{\n.reg .pred p;\nmbarrier.test_wait.parity.shared::cta.b64 p, [%1], 0;\nselp.u32 %0, 1, 0, p;\n}" : "=r"(ok) : "r"(bar) : "memory");
    return ok;
}
__device__ __forceinline__ bool mbar_test2(uint32_t bar0, uint32_t bar1) {
    uint32_t ok;
    asm volatile("{\n.reg .pred p, q;\nmbarrier.test_wait.parity.shared::cta.b64 p, [%1], 0;\n"
                 "mbarrier.test_wait.parity.shared::cta.b64 q, [%2], 0;\nand.pred p, p, q;\nselp.u32 %0, 1, 0, p;\n}"
                 : "=r"(ok) : "r"(bar0), "r"(bar1) : "memory");
    return ok;
}
__device__ __forceinline__ bool elect_one() {
    uint32_t ok;
    asm volatile("{\n.reg .pred p;\nelect.sync _|p, 0xffffffff;\nselp.u32 %0, 1, 0, p;\n}" : "=r"(ok));
    return ok;
}
__device__ __forceinline__ unsigned ld_flag(const unsigned* p) {
    unsigned v;
    asm volatile("ld.relaxed.gpu.global.u32 %0, [%1];" : "=r"(v) : "l"(p) : "memory");
    return v;
}
__device__ __forceinline__ uint4 lds128(uint32_t a) {
    uint4 v;
    asm volatile("ld.shared.v4.b32 {%0,%1,%2,%3}, [%4];" : "=r"(v.x), "=r"(v.y), "=r"(v.z), "=r"(v.w) : "r"(a) : "memory");
    return v;
}
__device__ __forceinline__ void sts128(uint32_t a, uint4 v) {
    asm volatile("st.shared.v4.b32 [%0], {%1,%2,%3,%4};" :: "r"(a), "r"(v.x), "r"(v.y), "r"(v.z), "r"(v.w) : "memory");
}
__device__ __forceinline__ uint32_t lds32(uint32_t a) {
    uint32_t v;
    asm volatile("ld.shared.b32 %0, [%1];" : "=r"(v) : "r"(a) : "memory");
    return v;
}
__device__ __forceinline__ void sts32(uint32_t a, uint32_t v) {
    asm volatile("st.shared.b32 [%0], %1;" :: "r"(a), "r"(v) : "memory");
}
__device__ __forceinline__ void stg128(void* p, uint4 v) {
    asm volatile("st.global.v4.b32 [%0], {%1,%2,%3,%4};" :: "l"(p), "r"(v.x), "r"(v.y), "r"(v.z), "r"(v.w) : "memory");
}
__device__ __forceinline__ unsigned pack4(unsigned a, unsigned b, unsigned c, unsigned d) {
    unsigned lo, r;
    asm("cvt.pack.sat.s8.s32.b32 %0, %1, %2, 0;" : "=r"(lo) : "r"(d), "r"(c));
    asm("cvt.pack.sat.s8.s32.b32 %0, %1, %2, %3;" : "=r"(r) : "r"(b), "r"(a), "r"(lo));
    return r;
}
__device__ __forceinline__ uint32_t mapa(uint32_t a, uint32_t r) {
    uint32_t o;
    asm("mapa.shared::cluster.u32 %0, %1, %2;" : "=r"(o) : "r"(a), "r"(r));
    return o;
}
__device__ __forceinline__ unsigned clk() {
    unsigned t;
    asm volatile("mov.u32 %0, %clock;" : "=r"(t));
    return t;
}
__device__ __forceinline__ void cluster_arrive() { asm volatile("barrier.cluster.arrive.relaxed.aligned;" ::: "memory"); }
__device__ __forceinline__ void cluster_wait() { asm volatile("barrier.cluster.wait.aligned;" ::: "memory"); }
__device__ __forceinline__ void fence_init() { asm volatile("fence.mbarrier_init.release.cluster;" ::: "memory"); }
__device__ __forceinline__ void flag_add(unsigned* p) { asm volatile("red.relaxed.gpu.global.add.u32 [%0], 1;" :: "l"(p) : "memory"); }
__device__ __forceinline__ void raw_load(const void* map, int y, int z, uint32_t dst, uint32_t bar) {
    asm volatile("cp.async.bulk.tensor.3d.shared::cluster.global.tile.mbarrier::complete_tx::bytes [%0], [%1, {0, %2, %3}], [%4];"
                 :: "r"(dst), "l"(map), "r"(y), "r"(z), "r"(bar) : "memory");
}
__device__ __forceinline__ void tile_load(Scratch* sc, uint32_t dst, int tile, uint32_t bar) {
    asm volatile("cp.async.bulk.shared::cluster.global.mbarrier::complete_tx::bytes [%0], [%1], %2, [%3];"
                 :: "r"(dst), "l"((const char*)sc->s8 + tile * 8192), "r"(8192), "r"(bar) : "memory");
}
__device__ __forceinline__ void tile_store(const void* map, int x, int y, uint32_t src) {
    asm volatile("cp.async.bulk.tensor.2d.global.shared::cta.tile.bulk_group [%0, {%1, %2}], [%3];"
                 :: "l"(map), "r"(x), "r"(y), "r"(src) : "memory");
}
__device__ __forceinline__ void st_async(uint32_t a, uint32_t v, uint32_t bar) {
    asm volatile("st.async.weak.shared::cluster.mbarrier::complete_tx::bytes.b32 [%0], %1, [%2];" :: "r"(a), "r"(v), "r"(bar) : "memory");
}
__device__ __forceinline__ void red_async(uint32_t a, int v, uint32_t bar) {
    asm volatile("red.async.relaxed.cluster.shared::cluster.mbarrier::complete_tx::bytes.add.s32 [%0], %1, [%2];" :: "r"(a), "r"(v), "r"(bar) : "memory");
}
__device__ __forceinline__ void red_shared(uint32_t a, int v) { asm volatile("red.shared.add.s32 [%0], %1;" :: "r"(a), "r"(v) : "memory"); }
__device__ __forceinline__ int sum4(unsigned v, int c) { return __dp4a((int)v, 0x01010101, c); }

constexpr uint32_t DESC_A_HI = 0x80000000u | (512 >> 4);
constexpr uint32_t DESC_B_HI = 512 >> 4;
template <int NR> __device__ __forceinline__ void wgmma_n160(int (&d)[NR], uint32_t alo, uint32_t blo, int scale_d) {
    asm volatile("{\n.reg .pred p;\n.reg .b64 da, db;\nsetp.ne.b32 p, %82, 0;\n"
        "mov.b64 da, {%80, %83};\nmov.b64 db, {%81, %84};\n"
        "wgmma.mma_async.sync.aligned.m64n160k32.s32.s8.s8 "
        "{%0, %1, %2, %3, %4, %5, %6, %7, %8, %9, %10, %11, %12, %13, %14, %15, "
        "%16, %17, %18, %19, %20, %21, %22, %23, %24, %25, %26, %27, %28, %29, %30, %31, "
        "%32, %33, %34, %35, %36, %37, %38, %39, %40, %41, %42, %43, %44, %45, %46, %47, "
        "%48, %49, %50, %51, %52, %53, %54, %55, %56, %57, %58, %59, %60, %61, %62, %63, "
        "%64, %65, %66, %67, %68, %69, %70, %71, %72, %73, %74, %75, %76, %77, %78, %79}, "
        "da, db, p;\n}\n"
        : "+r"(d[0]), "+r"(d[1]), "+r"(d[2]), "+r"(d[3]), "+r"(d[4]), "+r"(d[5]), "+r"(d[6]), "+r"(d[7]),
          "+r"(d[8]), "+r"(d[9]), "+r"(d[10]), "+r"(d[11]), "+r"(d[12]), "+r"(d[13]), "+r"(d[14]), "+r"(d[15]),
          "+r"(d[16]), "+r"(d[17]), "+r"(d[18]), "+r"(d[19]), "+r"(d[20]), "+r"(d[21]), "+r"(d[22]), "+r"(d[23]),
          "+r"(d[24]), "+r"(d[25]), "+r"(d[26]), "+r"(d[27]), "+r"(d[28]), "+r"(d[29]), "+r"(d[30]), "+r"(d[31]),
          "+r"(d[32]), "+r"(d[33]), "+r"(d[34]), "+r"(d[35]), "+r"(d[36]), "+r"(d[37]), "+r"(d[38]), "+r"(d[39]),
          "+r"(d[40]), "+r"(d[41]), "+r"(d[42]), "+r"(d[43]), "+r"(d[44]), "+r"(d[45]), "+r"(d[46]), "+r"(d[47]),
          "+r"(d[48]), "+r"(d[49]), "+r"(d[50]), "+r"(d[51]), "+r"(d[52]), "+r"(d[53]), "+r"(d[54]), "+r"(d[55]),
          "+r"(d[56]), "+r"(d[57]), "+r"(d[58]), "+r"(d[59]), "+r"(d[60]), "+r"(d[61]), "+r"(d[62]), "+r"(d[63]),
          "+r"(d[64]), "+r"(d[65]), "+r"(d[66]), "+r"(d[67]), "+r"(d[68]), "+r"(d[69]), "+r"(d[70]), "+r"(d[71]),
          "+r"(d[72]), "+r"(d[73]), "+r"(d[74]), "+r"(d[75]), "+r"(d[76]), "+r"(d[77]), "+r"(d[78]), "+r"(d[79])
        : "r"(alo), "r"(blo), "r"(scale_d), "r"(DESC_A_HI), "r"(DESC_B_HI));
}
template <int NR> __device__ __forceinline__ void wgmma_t128(int (&d)[NR], uint32_t alo, uint32_t blo, int scale_d) {
    asm volatile("{\n.reg .pred p;\n.reg .b64 da, db;\nsetp.ne.b32 p, %66, 0;\n"
        "mov.b64 da, {%64, %67};\nmov.b64 db, {%65, %68};\n"
        "wgmma.mma_async.sync.aligned.m64n128k32.s32.s8.s8 "
        "{%0, %1, %2, %3, %4, %5, %6, %7, %8, %9, %10, %11, %12, %13, %14, %15, "
        "%16, %17, %18, %19, %20, %21, %22, %23, %24, %25, %26, %27, %28, %29, %30, %31, "
        "%32, %33, %34, %35, %36, %37, %38, %39, %40, %41, %42, %43, %44, %45, %46, %47, "
        "%48, %49, %50, %51, %52, %53, %54, %55, %56, %57, %58, %59, %60, %61, %62, %63}, "
        "da, db, p;\n}\n"
        : "+r"(d[0]), "+r"(d[1]), "+r"(d[2]), "+r"(d[3]), "+r"(d[4]), "+r"(d[5]), "+r"(d[6]), "+r"(d[7]),
          "+r"(d[8]), "+r"(d[9]), "+r"(d[10]), "+r"(d[11]), "+r"(d[12]), "+r"(d[13]), "+r"(d[14]), "+r"(d[15]),
          "+r"(d[16]), "+r"(d[17]), "+r"(d[18]), "+r"(d[19]), "+r"(d[20]), "+r"(d[21]), "+r"(d[22]), "+r"(d[23]),
          "+r"(d[24]), "+r"(d[25]), "+r"(d[26]), "+r"(d[27]), "+r"(d[28]), "+r"(d[29]), "+r"(d[30]), "+r"(d[31]),
          "+r"(d[32]), "+r"(d[33]), "+r"(d[34]), "+r"(d[35]), "+r"(d[36]), "+r"(d[37]), "+r"(d[38]), "+r"(d[39]),
          "+r"(d[40]), "+r"(d[41]), "+r"(d[42]), "+r"(d[43]), "+r"(d[44]), "+r"(d[45]), "+r"(d[46]), "+r"(d[47]),
          "+r"(d[48]), "+r"(d[49]), "+r"(d[50]), "+r"(d[51]), "+r"(d[52]), "+r"(d[53]), "+r"(d[54]), "+r"(d[55]),
          "+r"(d[56]), "+r"(d[57]), "+r"(d[58]), "+r"(d[59]), "+r"(d[60]), "+r"(d[61]), "+r"(d[62]), "+r"(d[63])
        : "r"(alo), "r"(blo), "r"(scale_d), "r"(DESC_B_HI), "r"(DESC_A_HI));
}


__device__ __forceinline__ void wg_fence() { asm volatile("wgmma.fence.sync.aligned;" ::: "memory"); }
__device__ __forceinline__ void wg_commit() { asm volatile("wgmma.commit_group.sync.aligned;" ::: "memory"); }
template <int N> __device__ __forceinline__ void wg_wait() { asm volatile("wgmma.wait_group.sync.aligned %0;" :: "n"(N) : "memory"); }

__host__ __device__ constexpr int unit_of(int X1, int piece, int slab) {
    return piece < 2 ? (slab < X1 ? 2 * slab + piece : (piece ? 16 : X1) + slab) : 32 + (piece - 2) * 8 + (slab >> 1);
}
__host__ __device__ constexpr int col_of(int G) { return G == 4 ? 256 : (G > 4 && G < 9) ? 32 * G - 32 : 32 * G; }
struct BJob { int u, slab, G, pos; };
__host__ __device__ constexpr BJob decode_b(int X1, int q) {
    BJob j = {};
    if (q < 160) {
        j.u = q / 5; j.pos = q - j.u * 5;
        const int piece = j.u < 2 * X1 ? (j.u & 1) : (j.u >= X1 + 16);
        j.slab = j.u < 2 * X1 ? (j.u >> 1) : j.u - (piece ? 16 : X1);
        j.G = piece * 5 + j.pos;
    } else {
        q -= 160;
        j.u = 32 + (q >> 2); j.pos = q & 3;
        j.slab = (q >> 1) & 15;
        j.G = 10 + (q >> 5) * 2 + (q & 1);
    }
    return j;
}
__host__ __device__ constexpr int fb_of(int X1, int u) {
    return u < 2 * X1 ? (u & 1) * 32 + (u >> 1) : u < X1 + 16 ? u - X1 : u < 32 ? 16 + u : u < 40 ? u - 16 : u < 48 ? u + 8 : u - 24;
}
__host__ __device__ constexpr uint64_t slot_table(int X1, int piece) {
    uint64_t t = 0;
    for (int s = 0; s < 16; s++) t |= (uint64_t)(unit_of(X1, piece, s) % NSLOT) << (4 * s);
    return t;
}
template <bool k2> __device__ __forceinline__ int stage_w(int t) { return (k2 && t < 9) ? SM_A + (7 + t) * 8192 : SM_STG + (t % 3) * 8192; }
template <bool k2> __host__ __device__ constexpr int ford(int g, int m) {
    return k2 ? g * 5 + m : g ? (m ? 4 + m : 2) : (m < 2 ? m : m < 4 ? m + 1 : 9);
}
template <bool k2> __host__ __device__ constexpr int turn(int n) { return (n + (!k2 && n >= 5)) % 3; }
template <bool k2> __host__ __device__ constexpr uint64_t ford_table() {
    uint64_t t = 0;
    for (int g = 0; g < 2; g++) for (int m = 0; m < 5; m++) t |= (uint64_t)(g * 8 + m) << (4 * ford<k2>(g, m));
    return t;
}
struct Maps { CUtensorMap m[4]; };

__device__ __forceinline__ uint32_t bf2_mul(uint32_t a, uint32_t b) { asm("mul.rn.bf16x2 %0, %0, %1;" : "+r"(a) : "r"(b)); return a; }
__device__ __forceinline__ uint32_t epi(int a, int b, uint32_t zc, uint32_t sx, uint32_t sw, uint32_t bi) {
    uint32_t v;
    float fa = __int2float_rn(a), fb = __int2float_rn(b);
    asm("cvt.rn.bf16x2.f32 %0, %1, %2;" : "=r"(v) : "f"(fb), "f"(fa));
    if (CFG_EPI == 3) {
        asm("fma.rn.bf16x2 %0, %0, %1, %2;" : "+r"(v) : "r"(sw), "r"(zc));
        return v;
    }
    asm("sub.rn.bf16x2 %0, %0, %1;" : "+r"(v) : "r"(zc));
    if (CFG_EPI == 0) {
        v = bf2_mul(bf2_mul(v, sx), sw);
        asm("add.rn.bf16x2 %0, %0, %1;" : "+r"(v) : "r"(bi));
    } else {
        asm("fma.rn.bf16x2 %0, %0, %1, %2;" : "+r"(v) : "r"(sw), "r"(bi));
    }
    return v;
}
__device__ __forceinline__ uint32_t zero_term(int lo, int hi, float zx) {
    uint32_t z;
    asm("cvt.rn.bf16x2.f32 %0, %1, %2;" : "=r"(z) : "f"(__bfloat162float(__float2bfloat16_rn((float)hi)) * zx),
                                                    "f"(__bfloat162float(__float2bfloat16_rn((float)lo)) * zx));
    return z;
}
__device__ __forceinline__ uint32_t fold(uint32_t z, uint32_t sw, uint32_t bi) {
    if (CFG_EPI == 3) asm("fma.rn.bf16x2 %0, %1, %2, %3;" : "=r"(z) : "r"(z ^ 0x80008000u), "r"(sw), "r"(bi));
    return z;
}
__device__ __forceinline__ float ld_zx(const int* zero_x) { return __bfloat162float(__float2bfloat16_rn((float)__ldg(zero_x))); }
struct Par { uint4 zc, sw, bi; };
__device__ __forceinline__ Par ld_par(uint32_t p) { return {lds128(p), lds128(p + TN * 2), CFG_EPI == 3 ? uint4{} : lds128(p + TN * 4)}; }
__device__ __forceinline__ uint4 epi_row(const int (&a)[WA / 2], int o, const Par& p, uint32_t sx2) {
    uint4 r;
    r.x = epi(a[o + 0], a[o + 4], p.zc.x, sx2, p.sw.x, p.bi.x);
    r.y = epi(a[o + 8], a[o + 12], p.zc.y, sx2, p.sw.y, p.bi.y);
    r.z = epi(a[o + 1], a[o + 5], p.zc.z, sx2, p.sw.z, p.bi.z);
    r.w = epi(a[o + 9], a[o + 13], p.zc.w, sx2, p.sw.w, p.bi.w);
    return r;
}
__device__ __forceinline__ void scale_bias(const __nv_bfloat16* scale_x, const __nv_bfloat16* scale_w, const __nv_bfloat16* bias, uint32_t sb, int lane) {
    const uint32_t sx2 = (uint32_t)__ldg((const unsigned short*)scale_x) * 0x10001u;
#pragma unroll
    for (int i = lane; i < TN / 4; i += 32) {
        const bool hi = i >= TN / 8;
        uint4 v = __ldg((const uint4*)(hi ? bias : scale_w) + (hi ? i - TN / 8 : i));
        if (CFG_EPI && !hi) v = {bf2_mul(v.x, sx2), bf2_mul(v.y, sx2), bf2_mul(v.z, sx2), bf2_mul(v.w, sx2)};
        sts128(sb + SM_PAR + TN * 2 + i * 16, v);
    }
    __syncwarp();
    if (elect_one()) mbar_arrive(sb + SM_BAR + B_SW * 8);
}
template <bool k2> __device__ __forceinline__ int release_addr(uint32_t sb, int u, int lq) {
    const int v = u + NSLOT, q = (k2 ? (v >> 1) * 16 + (v & 1) : 5 * v - (v > 34 ? 3 : 0)) + lq;
    return mapa(sb | (q & 0x1F0), q & 15) | (q & 0x80000000);
}
__device__ __forceinline__ void release(int a) {
    asm volatile("{\n.reg .pred p;\nsetp.ge.s32 p, %0, 0;\n@p mbarrier.arrive.shared::cluster.b64 _, [%0 + %1];\n}" :: "r"(a), "n"(SM_BAR + B_GO * 8) : "memory");
}
__device__ __forceinline__ unsigned read_back(const uint4* d, int lane) { return ld_flag((const unsigned*)(d - lane + ((lane + 10) & 15) * 8 + 6)); }
__device__ __forceinline__ void publish(unsigned rb, unsigned mine, unsigned* flag) {
    asm volatile("{\n.reg .pred p, q;\n.reg .u32 l;\nmov.u32 l, %laneid;\nsetp.eq.u32 p, l, 6;\nsetp.ne.and.u32 q, %1, %2, p;\n"
                 "@q fence.acq_rel.gpu;\n@p red.relaxed.gpu.global.add.u32 [%0], 1;\n}" :: "l"(flag), "r"(rb), "r"(mine) : "memory");
}
#define CV_B(m, f)                                                                                                      \
    {                                                                                                                   \
        uint4 v0 = lds128(rdB + m * 512), v1 = lds128(rdB + m * 512 + 128);                                             \
        uint4 v2 = lds128(rdB + m * 512 + 256), v3 = lds128(rdB + m * 512 + 384);                                       \
        o[0].f = pack4(v0.x, v1.x, v2.x, v3.x); o[1].f = pack4(v0.y, v1.y, v2.y, v3.y);                                 \
        o[2].f = pack4(v0.z, v1.z, v2.z, v3.z); o[3].f = pack4(v0.w, v1.w, v2.w, v3.w);                                 \
    }

__device__ __forceinline__ void last_columns(Scratch* sc, const Maps& maps, const __nv_bfloat16* scale_x, const int* zero_x, const __nv_bfloat16* scale_w,
                                             const __nv_bfloat16* bias, uint32_t sb, int warp, int lane, unsigned t0) {
    constexpr int C_FULL = 0, C_EMPTY = 32, C_RAW = 64, C_GO = 80, C_PEER = 81, D3 = CFG_D3;
    const uint32_t bars = sb + SM_BAR;
    const int j = blockIdx.x & 3;
    while ((int)(t0 + CFG_T3 - clk()) > 0) ;
    const int s0 = (j & 1) * 8 + (warp >> 1) * 2;
    if (warp < 8) {
        if (elect_one()) {
#pragma unroll
            for (int i = 0; i < 2; i++) {
                const uint32_t bar = bars + (C_RAW + warp * 2 + i) * 8;
                mbar_init(bar, 1); mbar_expect_tx(bar, 8192);
                raw_load(maps.m + 1, (s0 + (i ^ (j >> 1))) * 64, N_ / 32 - 2 + (warp & 1), sb + SM_A + (warp * 2 + i) * 8192, bar);
            }
#pragma unroll
            for (int i = 0; i < 4; i++) { mbar_init(bars + (C_FULL + warp * 4 + i) * 8, 1); mbar_expect_tx(bars + (C_FULL + warp * 4 + i) * 8, 16384); }
#pragma unroll
            for (int i = 0; i < 4; i++) mbar_init(bars + (C_EMPTY + warp * 4 + i) * 8, 4);
            if (warp == 0) {
                mbar_init(bars + C_GO * 8, 8);
                mbar_init(bars + C_PEER * 8, 1); mbar_expect_tx(bars + C_PEER * 8, 32768 + 4096);
            }
        }
        if (warp < 2) sts32(sb + SM_PAR + threadIdx.x * 4, 0);
        fence_init();
    }
    __syncthreads();
    cluster_arrive();
    cluster_wait();
    if (warp >= 8) {
        asm volatile("setmaxnreg.dec.sync.aligned.u32 40;");
        if (warp < 12) {
            const unsigned ep = (ld_flag(epoch(sc, j * 4, 8)) + 1) * 4;
            const int mb = j * 4 + warp - 8, wg = (warp >> 1) & 1;
            unsigned rdy = 0;
            mbar_wait(bars + (wg ? C_EMPTY : C_GO) * 8);
#pragma unroll 1
            for (int s = 0; s < 16; s++) {
                for (int it = 0; !((rdy >> s) & 1); it++) {
                    rdy = __ballot_sync(~0u, (int)(ld_flag(sc->flag + mb * 32 + (lane & 15)) - ep) >= 0);
                    if (it > (1 << 22)) __trap();
                }
                if (s >= D3) mbar_wait(bars + (C_EMPTY + (s - (s < CFG_S3 ? D3 : CFG_D4)) * 2 + wg) * 8);
                if (elect_one()) tile_load(sc, sb + SM_A + ((s & 3) * 4 + warp - 8) * 8192, mb * 16 + s, bars + (C_FULL + s * 2 + wg) * 8);
            }
        }
    } else {
        asm volatile("setmaxnreg.inc.sync.aligned.u32 200;");
        const int wg = warp >> 2, w = warp & 3;
        const int c0 = (w >> 1) * 32 + (lane >> 2) * 4 + (w & 1) * 2, r0 = (lane & 3) * 2;
        const uint32_t sx2 = (uint32_t)__ldg((const unsigned short*)scale_x) * 0x10001u;
        uint32_t sw = __ldg((const unsigned*)(scale_w + N_ - WB + c0));
        const uint32_t bi = __ldg((const unsigned*)(bias + N_ - WB + c0));
        const float zxf = ld_zx(zero_x);
        int cs[4] = {0, 0, 0, 0};
        const uint32_t peer = mapa(sb, (j & 1) ^ 1);
#pragma unroll 1
        for (int i = 0; i < 2; i++) {
            const uint32_t rdB = sb + SM_A + (warp * 2 + i) * 8192 + (lane >> 3) * 2048 + (lane & 7) * 16;
            const uint32_t wr = SM_RING + (s0 + (i ^ (j >> 1))) * 4096 + (warp & 1) * 2048 + lane * 16;
            mbar_wait(bars + (C_RAW + warp * 2 + i) * 8);
            uint4 o[4];
            CV_B(0, x) CV_B(1, y) CV_B(2, z) CV_B(3, w)
#pragma unroll
            for (int k = 0; k < 4; k++) {
                sts128(sb + wr + k * 512, o[k]);
                asm volatile("st.async.weak.shared::cluster.mbarrier::complete_tx::bytes.v4.b32 [%0], {%1,%2,%3,%4}, [%5];"
                             :: "r"(peer + wr + k * 512), "r"(o[k].x), "r"(o[k].y), "r"(o[k].z), "r"(o[k].w), "r"(peer + SM_BAR + C_PEER * 8) : "memory");
                cs[k] = sum4(o[k].x, sum4(o[k].y, sum4(o[k].z, sum4(o[k].w, cs[k]))));
            }
        }
        __syncwarp();
        if (elect_one()) mbar_arrive(bars + C_GO * 8);
#pragma unroll
        for (int k = 0; k < 4; k++) {
            const uint32_t ca = SM_PAR + ((warp & 1) * 32 + (lane & 7) * 4 + k) * 4;
            red_shared(sb + ca, cs[k]);
            red_async(peer + ca, cs[k], peer + SM_BAR + C_PEER * 8);
        }
        mbar_wait(bars + C_PEER * 8);
        asm volatile("fence.proxy.async.shared::cta;" ::: "memory");
        asm volatile("bar.sync 1, 256;" ::: "memory");
        if (CFG_EPI) sw = bf2_mul(sw, sx2);
        const uint32_t zc = fold(zero_term(lds32(sb + SM_PAR + c0 * 4), lds32(sb + SM_PAR + c0 * 4 + 4), zxf), sw, bi);
        const uint32_t sd = (sb & 0x3FFFF) >> 4;
        int t[2][64];
        wg_fence();
#pragma unroll 1
        for (int s = 0; s < 16; s++) {
            const uint32_t db = ((sd + (SM_RING >> 4)) | (8 << 16)) + s * 256, da = ((sd + (SM_A >> 4)) | (1 << 16)) + ((s & 3) * 4 + wg * 2) * 512;
            mbar_wait(bars + (C_FULL + s * 2 + wg) * 8);
            wgmma_t128(t[0], db, da, s);
            wgmma_t128(t[1], db, da + 512, s);
            wgmma_t128(t[0], db + 16, da + 2, 1);
            wgmma_t128(t[1], db + 16, da + 514, 1);
            wg_commit();
            wg_wait<0>();
            if (elect_one()) mbar_arrive(bars + (C_EMPTY + s * 2 + wg) * 8);
        }
        asm volatile("bar.sync %0, 128;" :: "r"(3 + wg) : "memory");
        const uint32_t st0 = sb + SM_A + wg * 16384 + r0 * 128 + (((c0 >> 3) ^ r0) << 4) + (c0 & 7) * 2;
#pragma unroll
        for (int h = 0; h < 4; h++) {
            const uint32_t off = (h >> 1) * 32768 + (h & 1) * 8192;
#pragma unroll
            for (int q = 0; q < 8; q++) {
                const int o = (h & 1) * 32 + q * 4;
                sts32(st0 + off + q * 1024, epi(t[h >> 1][o], t[h >> 1][o + 2], zc, sx2, sw, bi));
                sts32((st0 ^ (5 * 128 + 5 * 16)) + off + q * 1024, epi(t[h >> 1][o + 1], t[h >> 1][o + 3], zc, sx2, sw, bi));
            }
            asm volatile("fence.proxy.async.shared::cta;" ::: "memory");
            asm volatile("bar.sync %0, 128;" :: "r"(3 + wg) : "memory");
            if (w == 0 && elect_one()) tile_store(maps.m + 2, N_ - WB, j * 512 + wg * 256 + h * 64, sb + SM_A + wg * 16384 + off);
        }
        if (w == 0) {
            asm volatile("cp.async.bulk.commit_group;" ::: "memory");
            asm volatile("cp.async.bulk.wait_group.read 0;" ::: "memory");
        }
        asm volatile("bar.sync 1, 256;" ::: "memory");
        if (threadIdx.x == 0) flag_add(epoch(sc, j * 4, 8));
    }
}

template <bool k2>
__global__ void __cluster_dims__(k2 ? 2 : CS, 1, 1) __launch_bounds__(512, 1)
w8a8_kernel(Scratch* sc, const char* __restrict__ qx, const char* __restrict__ qw, const __nv_bfloat16* __restrict__ scale_x, const int* __restrict__ zero_x,
            const __nv_bfloat16* __restrict__ scale_w, const __nv_bfloat16* __restrict__ bias, const __grid_constant__ Maps maps) {
    extern __shared__ __align__(1024) unsigned char smem_raw[];
    constexpr int NBJ = k2 ? 12 : 14, NF = NBJ, NU = k2 ? 40 : 48;
    constexpr int X1 = k2 ? CFG_X2 : CFG_X1;
    const int b = blockIdx.x + (k2 ? NCTA : 0), r = b & 15, c = k2 ? NCL : b >> 4;
    const unsigned tc = clk();
    if (!k2) {
        const int a = (r * NCL + c) ^ REV;
        const unsigned off = ((a & 63) * 32 + (threadIdx.x >> 1)) * (K_ * 4) + (a >> 6) * 256 + (threadIdx.x & 1) * 128;
        asm volatile("{\n.reg .pred p;\n.reg .b64 a;\nsetp.lt.u32 p, %2, 64;\n@!p bra PF_DONE;\ncvt.u64.u32 a, %1;\nadd.u64 a, a, %0;\nprefetch.global.L2 [a];\nPF_DONE:\n}"
                     :: "l"(qx), "r"(off), "r"(threadIdx.x));
    }
    const uint32_t sb = (uint32_t)__cvta_generic_to_shared(smem_raw);
    const uint32_t bars = sb + SM_BAR;
    const unsigned tw = __shfl_sync(~0u, (tc & ~15u) | threadIdx.x >> 5, 0), t0 = tw + (k2 ? 0 : T0);
    const int warp = tw & 15, lane = threadIdx.x & 31;

    if (!k2 && warp == 12) {
        const int a = r * NCL + c;
        if (elect_one()) {
            mbar_init(bars + (B_RAWA + 3) * 8, 1);
            mbar_expect_tx(bars + (B_RAWA + 3) * 8, 8192);
            raw_load(maps.m, (a >> 6) * 2, ((a ^ REV) & 63) * 32, sb + SM_A + (a < NAJ % NCTA ? 15 : 13) * 8192, bars + (B_RAWA + 3) * 8);
        }
        __syncwarp();
    }
    if (!k2 && (warp >> 1) == 1 && r < CFG_PG) {
        const int a = (NCTA + r * NCL + c) ^ REV;
        const char* p = qx + ((a & 63) * 32 + (warp & 1) * 16 + (lane >> 1)) * (K_ * 4) + (a >> 6) * 256 + (lane & 1) * 128;
        while ((int)(t0 + (16 + r) * P1 - clk()) > 0) ;
        asm volatile("prefetch.global.L2 [%0];" :: "l"(p));
    }
    if (warp == 9 && elect_one()) asm volatile("prefetch.tensormap [%0];" :: "l"(maps.m + 1) : "memory");
    if (k2 && blockIdx.x >= 16) {
        last_columns(sc, maps, scale_x, zero_x, scale_w, bias, sb, warp, lane, t0);
        return;
    }
    if (warp >= 12) {
        const int isw = k2 || warp == 14, t = k2 ? warp - 12 : isw ? 0 : (warp - 11) >> 1;
        const uint32_t bar = bars + ((isw ? B_RAWB : B_RAWA) + 3 + t) * 8;
        if ((k2 || warp != 12) && elect_one()) { mbar_init(bar, 1); mbar_expect_tx(bar, 8192); }
        __syncwarp();
        cluster_arrive();
        const int x = t * 16 + r, a = (x * NCL + c) ^ REV, sx = (x * 26) >> 8;
        static_assert(X1 >= 7, "");
        if ((k2 || warp != 12) && elect_one()) {
            const unsigned te = t0 + (k2 ? sched2(x) : (isw ? time_w(x) : time_x(x)) * P1);
            while ((int)(te - clk()) > 0) ;
            raw_load(maps.m + isw, isw ? sx * 64 : (a >> 6) * 2,
                     isw ? c * (TN / 32) + (int)((0x9765483210ull >> ((x - sx * 10) * 4)) & 15) : (a & 63) * 32,
                     sb + (k2 ? SM_A + 7 * 8192 : isw ? SM_STG : SM_A + 13 * 8192) + (t - (!isw && r * NCL + c < NAJ % NCTA)) * 8192, bar);
        }
        __syncwarp();
        if (!k2 && warp == 15) cluster_wait();
    }
    if (warp < 8) {
        const uint32_t p = bars + warp * 104;
        if (elect_one()) {
#pragma unroll
            for (int i = 0; i < 13; i++) mbar_init(p + i * 8, (!k2 && ((warp == 6 && i == 12) || (warp == 7 && i < 2))) ? 2 : 1);
            static_assert(B_FREE == 90, "");
        }
        __syncwarp();
        const int i = warp * 13 + lane;
        if (lane < 13 && i < B_SW) mbar_expect_tx(p + lane * 8, i >= B_PAR ? (i < B_PAR + 2 ? WA * 2 : WB * 2) : (i & 16) || i >= 48 ? 8192 : WA * 64);
        fence_init();
    }
    if (warp < 8 || warp == 10) cluster_arrive();
    if (!k2 && warp == 10 && lane < CFG_PF7) {
        const int n = b * CFG_PF7 + lane, row = n / 10;
        asm volatile("prefetch.global.L2 [%0];" :: "l"(qw + row * (N_ * 4) + NCL * TN * 4 + (n - row * 10) * 128));
    }

    if (warp < 8) {
        asm volatile("setmaxnreg.inc.sync.aligned.u32 200;");
        const int wg = warp >> 2;
        const uint32_t sd = (sb & 0x3FFFF) >> 4;
        const uint32_t sx2 = (uint32_t)__ldg((const unsigned short*)scale_x) * 0x10001u;
        const uint32_t par = sb + SM_PAR + (lane & 3) * 16 + wg * 256;
        const uint32_t go = bars + B_GO * 8;
        const int w = warp & 3, pq = (lane >> 2) ^ (lane & 4);
        uint32_t so = (w * 16 + pq) * 128 + (((lane & 3) ^ pq) << 4);
        const int c0 = (w >> 1) * 32 + (lane >> 2) * 4 + (w & 1) * 2, r0 = (lane & 3) * 2;
        uint32_t pp = sb + SM_PAR + (2 * WA + wg * WB + c0) * 2, st0 = r0 * 128 + (((c0 >> 3) ^ r0) << 4) + (c0 & 7) * 2;
        uint32_t rq = k2 ? mapa(go + 19 * 16, 1) : mapa(go + (12 + (lane >> 4)) * 16, lane & 15);
        int rk = k2 ? (lane ? 99 : 1) : (lane >> 2) + 1;
        asm volatile("" : "+r"(so), "+r"(pp), "+r"(st0), "+r"(rq), "+r"(rk));
        cluster_wait();
        int a0[WA / 2], a1[WA / 2];
        uint32_t barB = bars + (B_FULLB + wg * 32) * 8;
        int ra = -1;
        const int lq = lane < (k2 ? 1 : 5) ? lane : -1000;
        wg_fence();
        {
            uint64_t tbl = wg ? slot_table(X1, 1) : slot_table(X1, 0);
            uint32_t da = (sd + (SM_A >> 4)) | (1 << 16);
            bool rdy = false;
#pragma unroll 1
            for (int s = 0; s < 16; s++) {
                const uint32_t db = ((sd + (SM_RING >> 4)) | (8 << 16)) + ((uint32_t)tbl & 15) * (SLOT >> 4);
                const bool hold = wg && s == X1;
                if (hold || (!rdy && !mbar_test2(bars + (B_FULLA + s) * 8, barB))) {
                    wg_wait<0>();
                    release(ra); ra = -1;
                    mbar_wait2(bars + (B_FULLA + s) * 8, barB);
                    if (hold) asm volatile("bar.sync 7, 256;" ::: "memory");
                }
                wgmma_n160(a0, da, db, s);
                wgmma_n160(a1, da + 256, db, s);
                wg_commit();
                if (!wg && s == 15) asm volatile("bar.arrive 7, 256;" ::: "memory");
                wg_wait<1>();
                release(ra);
                wgmma_n160(a0, da + 2, db + 16, 1);
                wgmma_n160(a1, da + 258, db + 16, 1);
                wg_commit();
                ra = release_addr<k2>(sb, s < X1 ? 2 * s + wg : (wg ? 16 : X1) + s, lq);
                tbl >>= 4; da += 512; barB += 8;
                rdy = mbar_test2(bars + (B_FULLA + s + 1) * 8, barB);
                if (s < 15) wg_wait<1>();
            }
        }
        mbar_wait2(bars + (B_PAR + wg) * 8, bars + B_SW * 8);
        const Par P0 = ld_par(par), P1 = ld_par(par + 64);
        wg_wait<0>();
        release(ra);
        bool ready = mbar_test(barB);
#define FILL_BEGIN(n0, n1) mbar_wait(bars + (B_FREE + (wg ? n1 : n0)) * 8);                                             \
                           const uint32_t buf = sb + SM_STG + (wg ? (turn<k2>(n1) + NBJ) % 3 : (turn<k2>(n0) + NBJ) % 3) * 8192;
#define FILL_END(n0, n1) __syncwarp();                                                                                  \
                         if (elect_one()) mbar_arrive(bars + (B_FILL + (wg ? turn<k2>(n1) : turn<k2>(n0))) * 8);
#define FILL_PAIR(a, J, P, Q, m, MID)                                                                                   \
        {                                                                                                               \
            const uint4 v0 = epi_row(a, J * 16, P, sx2), v1 = epi_row(a, J * 16 + 2, P, sx2);                           \
            FILL_BEGIN(ford<k2>(0, m), ford<k2>(1, m))                                                                  \
            sts128(buf + so, v0); sts128(buf + so + 1024, v1);                                                          \
            MID                                                                                                         \
            sts128(buf + (so ^ 64), epi_row(a, J * 16 + 16, Q, sx2));                                                   \
            sts128(buf + (so ^ 64) + 1024, epi_row(a, J * 16 + 18, Q, sx2));                                            \
            FILL_END(ford<k2>(0, m), ford<k2>(1, m))                                                                    \
        }
#define NARROW(p)                                                                                                       \
        {                                                                                                               \
            if (!ready) mbar_wait(barB);                                                                                \
            wg_fence();                                                                                                 \
            _Pragma("unroll 1") for (int i = 0; i < 8; i++) {                                                           \
                const uint32_t db = ((sd + (SM_RING >> 4)) | (8 << 16)) + (k2 ? (i > 2 ? i - 3 : i + 4) * (SLOT >> 4) : ((i + 5) & 7) * 512); \
                _Pragma("unroll") for (int kk = 0; kk < 4; kk++)                                                        \
                    wgmma_t128(t, db + (kk >> 1) * 256 + (kk & 1) * 16,                                                 \
                               ((sd + (SM_A >> 4)) | (1 << 16)) + i * 1024 + (kk >> 1) * 512 + (kk & 1) * 2, kk ? 1 : i); \
                wg_commit();                                                                                            \
                barB += 8;                                                                                              \
                mbar_wait(i < 7 ? barB : bars + (B_PAR + p) * 8);                                                       \
                wg_wait<1>();                                                                                           \
                if (p == 2 && rk == i) mbar_arrive_cluster(rq);                                                         \
            }                                                                                                           \
            if (p == 3 || k2) { zc = lds32(pp); sw = lds32(pp + TN * 2); bi = CFG_EPI == 3 ? 0 : lds32(pp + TN * 4); }               \
            wg_wait<0>();                                                                                               \
            if (p == 2 && rk == 8) mbar_arrive_cluster(rq);                                                             \
        }
        Par P2, P3, P;
        FILL_PAIR(a0, 0, P0, P1, 0, P2 = ld_par(par + 128);)
        FILL_PAIR(a1, 0, P0, P1, 1, P3 = ld_par(par + 192);)
        FILL_PAIR(a0, 2, P2, P3, 2, P = ld_par(par + 512 - wg * 192);)
        FILL_PAIR(a1, 2, P2, P3, 3, )
        int t[64];
        uint32_t zc, sw, bi;
        if (!k2 && wg == 0) NARROW(2)
        {
            const uint4 v0 = epi_row(a0, 64, P, sx2), v1 = epi_row(a0, 66, P, sx2);
            FILL_BEGIN(ford<k2>(0, 4), ford<k2>(1, 4))
            const uint32_t s4 = buf + ((so >> 1) & ~63u) + (lane & 3) * 16;
            sts128(s4, v0); sts128(s4 + 512, v1);
            sts128(s4 + 4096, epi_row(a1, 64, P, sx2)); sts128(s4 + 4608, epi_row(a1, 66, P, sx2));
            FILL_END(ford<k2>(0, 4), ford<k2>(1, 4))
        }
        if (!(k2 && wg)) {
            if (k2) NARROW(2) else if (wg) NARROW(3) else { zc = lds32(pp); sw = lds32(pp + TN * 2); bi = CFG_EPI == 3 ? 0 : lds32(pp + TN * 4); }
#define FILL_T(h)                                                                                                       \
            {                                                                                                           \
                FILL_BEGIN((10 + h), (12 + h))                                                                          \
                _Pragma("unroll") for (int j = 0; j < 8; j++) {                                                         \
                    const int o = h * 32 + j * 4;                                                                       \
                    sts32(buf + st0 + j * 1024, epi(t[o], t[o + 2], zc, sx2, sw, bi));                                  \
                    sts32(buf + (st0 ^ (5 * 128 + 5 * 16)) + j * 1024, epi(t[o + 1], t[o + 3], zc, sx2, sw, bi));       \
                }                                                                                                       \
                FILL_END((10 + h), (12 + h))                                                                            \
            }
            FILL_T(0) FILL_T(1)
        }
        if (threadIdx.x == 0) flag_add(epoch(sc, r, c));
    } else {
        const int g = r * NCL + c, na = k2 ? 0 : NAJ / NCTA + (g < NAJ % NCTA);
        int cw = NF;
        if (warp >= 12) {
            asm volatile("setmaxnreg.dec.sync.aligned.u32 80;");
            if (warp < 14) {
                const int c4 = (lane ^ (lane >> 3)) & 3, ln = ((lane >> 2) ^ (lane & 4)) * 2 + (c4 >> 1);
                const uint32_t rd0 = sb + SM_A + 13 * 8192 + ln * 128 + ((((c4 & 1) << 2) ^ (ln & 7)) << 4);
#pragma unroll 1
                for (int t = warp - 12, sl = na == 9 ? t : 2 - 2 * t; t < na; t += 2, sl = sl ? sl - 1 : 2) {
                    const uint32_t rdA = rd0 + sl * 8192;
                    const int a = (t * NCTA + g) ^ REV, f = (a & 60) * 4 + (a >> 6);
                    uint4* const d = sc->s8 + (f * 4 + (a & 3)) * 128 + lane;
                    unsigned* fl = sc->flag + (a & 60) * 8 + (a >> 6);
                    uint32_t fb = bars + ((t < na - 3 ? B_RAWA : B_AFREE + 13) + sl) * 8;
                    asm volatile("" : "+l"(fl), "+r"(fb));
                    uint4 o[4];
                    mbar_wait(bars + (B_RAWA + 3 + t) * 8);
#pragma unroll
                    for (int i = 0; i < 4; i++) {
                        uint4 v0 = lds128(rdA + i * 2048), v1 = lds128((rdA ^ 16) + i * 2048);
                        uint4 v2 = lds128((rdA ^ 32) + i * 2048), v3 = lds128((rdA ^ 48) + i * 2048);
                        o[i].x = pack4(v0.x, v0.y, v0.z, v0.w); o[i].y = pack4(v1.x, v1.y, v1.z, v1.w);
                        o[i].z = pack4(v2.x, v2.y, v2.z, v2.w); o[i].w = pack4(v3.x, v3.y, v3.z, v3.w);
                    }
#pragma unroll
                    for (int i = 0; i < 4; i++) stg128(d + i * 32, o[i]);
                    if (t >= 2 && elect_one()) mbar_arrive(fb);
                    __syncwarp();
                    const unsigned rb = read_back(d, lane);
                    asm volatile("fence.proxy.async.global;" ::: "memory");
                    __syncwarp();
                    publish(rb, o[0].x, fl);
                    if (t < 2) { cluster_wait(); if (elect_one()) mbar_arrive(fb); }
                }
                cw = warp - 12;
            }
            if (!k2) {
                const int hw = warp & 1;
                const uint32_t rd0 = sb + SM_STG + hw * 4096 + (lane >> 3) * 1024 + (lane & 7) * 16;
                const int myG = decode_b(X1, (lane & 15) * 16 + r).G;
                const uint64_t gt = (uint64_t)__reduce_or_sync(~0u, lane < 8 ? myG << (4 * lane) : 0) |
                                    (uint64_t)__reduce_or_sync(~0u, (lane >> 3) == 1 ? myG << (4 * (lane & 7)) : 0) << 32;
#pragma unroll 1
                for (int t = warp < 14 ? TA : 0; t < NBJ; t += warp < 14 ? NBJ : t == TA - 1 ? 2 : 1) {
                    const int sl = t % 3;
                    const uint32_t rdB = rd0 + sl * 8192;
                    char* const d = (char*)sc->s8 + (1024 + c * 256 + t * 16 + r) * 2048 + hw * 256 + (lane >> 4) * 128 + (lane & 7) * 16 + (lane & 8);
                    uint32_t fb = bars + (t >= NBJ - 3 ? B_FREE + t - (NBJ - 3) : B_RAWB + sl) * 8;
                    asm volatile("" : "+r"(fb));
                    uint2 o[4];
                    mbar_wait(bars + (B_RAWB + 3 + t) * 8);
                    CV_B(0, x) CV_B(1, y)
#pragma unroll
                    for (int i = 0; i < 4; i++) asm volatile("st.global.v2.b32 [%0], {%1,%2};" :: "l"(d + i * 512), "r"(o[i].x), "r"(o[i].y) : "memory");
                    if (t == 0 && warp == 14) cluster_wait();
                    if (elect_one()) mbar_arrive(fb);
                    asm volatile("fence.proxy.async.global;" ::: "memory");
                    __syncwarp();
                    if (elect_one()) mbar_arrive(bars + (B_GO + t * 2) * 8);
                    int cs[4];
#pragma unroll
                    for (int i = 0; i < 4; i++) cs[i] = sum4(o[i].x, sum4(o[i].y, 0));
                    const int p01 = cs[0] + cs[1] * 65536, p23 = cs[2] + cs[3] * 65536;
                    const bool h = lane & 16;
                    int x = (h ? p23 : p01) + __shfl_xor_sync(~0u, h ? p01 : p23, 16);
                    x += __shfl_xor_sync(~0u, x, 8);
                    const int lo = (int)(short)x, v = (lane & 8) ? (x - lo) >> 16 : lo;
                    const int G = (int)(gt >> (4 * t)) & 15;
                    if (G != r) {
                        red_async(mapa(sb + SM_CS + lane * 4, G), v, mapa(bars + B_CS * 8, G));
                    } else {
                        red_shared(sb + SM_CS + lane * 4, v);
                        __syncwarp();
                        if (elect_one()) mbar_arrive(bars + B_CS * 8);
                    }
                }
            } else {
                const uint32_t rd0 = sb + (lane >> 3) * 2048 + (lane & 7) * 16;
                const BJob mb = decode_b(X1, (lane & 15) * 16 + r);
                const int myG = mb.G | mb.u << 8;
#pragma unroll 1
                for (int t = warp - 12; t < NBJ; t += 4) {
                    const uint32_t rdB = rd0 + stage_w<k2>(t);
                    uint4* const d = sc->s8 + (1024 + c * 256 + t * 16 + r) * 128 + lane;
                    const int gu = __shfl_sync(~0u, myG, t);
                    uint4 o[4];
                    mbar_wait(bars + (B_RAWB + 3 + t) * 8);
                    CV_B(0, x) CV_B(1, y) CV_B(2, z) CV_B(3, w)
#pragma unroll
                    for (int i = 0; i < 4; i++) stg128(d + i * 32, o[i]);
                    if (t < 4) cluster_wait();
                    if (elect_one()) mbar_arrive(bars + (B_FREE + t - (NBJ - 3)) * 8);
                    asm volatile("fence.proxy.async.global;" ::: "memory");
                    __syncwarp();
                    const unsigned rb = read_back(d, lane), ep = ld_flag(epoch(sc, r, c));
                    int cs[4];
#pragma unroll
                    for (int i = 0; i < 4; i++) cs[i] = sum4(o[i].x, sum4(o[i].y, sum4(o[i].z, sum4(o[i].w, 0))));
                    const bool h = lane & 16, odd = lane & 8;
                    int x = (h ? cs[2] : cs[0]) + __shfl_xor_sync(~0u, h ? cs[0] : cs[2], 16);
                    int y = (h ? cs[3] : cs[1]) + __shfl_xor_sync(~0u, h ? cs[1] : cs[3], 16);
                    const int v = (odd ? y : x) + __shfl_xor_sync(~0u, odd ? x : y, 8);
                    publish(rb, o[0].x, sc->flag + F_W + (gu >> 8));
                    const int old = atomicAdd(sc->cs[ep & 1] + col_of(gu & 255) + (lane & 7) * 4 + (lane >> 3), v);
                    if (old == 0x7FFFFFFF) sc->sink[0] = old;
                    __syncwarp();
                    if (elect_one()) flag_add(sc->flag + F_CS + (gu & 255) / 5);
                }
            }
        } else {
            asm volatile("setmaxnreg.dec.sync.aligned.u32 32;");
            if (warp == 11) {
                if (elect_one()) {
#pragma unroll
                    for (int i = 0; i < (k2 ? NU / 2 : NBJ); i++)
                        mbar_init(bars + (B_GO + i * 2) * 8, k2 ? (i * 2 + (r & 1) >= NSLOT ? 9 : 1)
                                                         : 2 + 4 * CS * ((i * 16 + r >= NSLOT * 5) + (i == 10 && r >= 12 && r < 15)));
#pragma unroll
                    for (int i = 0; i < 3; i++) mbar_init(bars + (B_FILL + i) * 8, 4);
                }
                const int u2 = lane * 2 + (r & 1), q = k2 ? (u2 < 32 ? 5 * u2 : 4 * u2 + 32) : (lane & 15) * 16 + r;
                const BJob bj = decode_b(X1, q);
                unsigned seen = 0;
                if (!k2) {
                    const int nself = __popc(__ballot_sync(~0u, lane < NBJ && bj.G == r));
                    sts32(sb + SM_CS + lane * 4, 0);
                    if (lane == 0) {
                        mbar_init(bars + B_CS * 8, 1 + 2 * nself);
                        mbar_expect_tx(bars + B_CS * 8, (16 - nself) * 256);
                    }
                    seen = lds32(sb + SM_CS + lane * 4);
                }
                fence_init();
                asm volatile("barrier.cluster.arrive.relaxed.aligned;" :: "r"(seen) : "memory");
                const uint32_t df = (SM_RING + ((!k2 && q >= 160) ? ((q + 20) & 31) * 2048 : (bj.u % NSLOT) * SLOT + bj.pos * 2048))
                                  | (B_FULLB + fb_of(X1, bj.u)) * 8 << 18;
                cluster_wait();
                if (!k2) scale_bias(scale_x, scale_w + c * TN, bias + c * TN, sb, lane);
#pragma unroll 1
                for (int i = 0; i < (k2 ? NU / 2 : NBJ); i++) {
                    const uint32_t w = __shfl_sync(~0u, df, i);
                    const int u = i * 2 + (r & 1);
                    uint32_t d = sb + (w & 0x3FFFF), f = bars + (w >> 18), n = k2 ? (u < 32 ? SLOT : 8192) : 2048;
                    const char* p = (const char*)sc->s8 + (1024 + c * 256 + (k2 ? (u < 32 ? 5 * u : 4 * u + 32) : i * 16 + r)) * 2048;
                    asm volatile("" : "+l"(p), "+r"(d), "+r"(f), "+r"(n));
                    mbar_wait(bars + (B_GO + i * 2) * 8);
                    if (elect_one())
                        asm volatile("cp.async.bulk.shared::cluster.global.mbarrier::complete_tx::bytes.multicast::cluster [%0], [%1], %2, [%3], %4;"
                                     :: "r"(d), "l"(p), "r"(n), "r"(f), "h"((uint16_t)(k2 ? 3 : 0xFFFF)) : "memory");
                }
            } else if (warp == 10) {
                const unsigned ep = (__shfl_sync(~0u, ld_flag(sc->flag + r * 32 + (lane < 16 ? lane : 16 + c)), 16) + 1) * 4;
                const unsigned* f = sc->flag + r * 32 + (lane & 15);
                cluster_wait();
                unsigned m = 0;
#pragma unroll 1
                for (int s = 0; s < 16; s++, m >>= 1) {
                    uint32_t d = sb + SM_A + s * 8192, fa = bars + (B_FULLA + s) * 8;
                    const char* p = (const char*)sc->s8 + (r * 16 + s) * 8192;
                    asm volatile("" : "+l"(p), "+r"(d), "+r"(fa));
                    if (s >= (k2 ? 7 : 13)) mbar_wait(bars + (B_AFREE + s) * 8);
                    for (int it = 0; !(m & 1); it++) {
                        m = __ballot_sync(~0u, (int)(ld_flag(f) - ep) >= 0) >> s;
                        if (it > (1 << 22)) __trap();
                    }
                    if (elect_one())
                        asm volatile("cp.async.bulk.shared::cluster.global.mbarrier::complete_tx::bytes [%0], [%1], 8192, [%2];" :: "r"(d), "l"(p), "r"(fa) : "memory");
                }
            } else {
                const bool isw = warp == 9;
                const uint32_t rb = bars + (isw ? B_RAWB : B_RAWA) * 8;
                if (elect_one()) {
#pragma unroll
                    for (int i = 0; i < 13; i++) if (i < 3 || i >= (k2 ? 7 : 6)) mbar_init(rb + i * 8, (i < 3 && isw && !k2) ? 2 : 1);
                    if (isw) {
#pragma unroll
                        for (int i = 13; i < 17; i++) mbar_init(rb + i * 8, 1);
                        if (!k2) { mbar_init(rb + 4 * 8, 1); mbar_init(rb + 5 * 8, 1); }
                    }
                }
                __syncwarp();
                const int nj = isw ? NBJ : na, j0 = k2 ? 4 : isw ? 1 : 3;
                if (lane >= j0 && lane < nj) mbar_expect_tx(rb + (3 + lane) * 8, 8192);
                fence_init();
                cluster_arrive();
                const unsigned e0 = k2 ? ld_flag(epoch(sc, r, c)) : 0;
                const int k = lane / 3, x = lane * 16 + r;
                int sl = lane - k * 3, y, z, T;
                if (isw) {
                    const BJob bj = decode_b(X1, x & 255);
                    y = bj.slab * 64; z = (c * TN + col_of(bj.G)) >> 5; T = time_w(x);
                } else {
                    const int a = (lane * NCTA + g) ^ REV;
                    y = (a >> 6) * 2; z = (a & 63) * 32; T = time_x(x);
                    if (na == 10) sl = sl ? sl - 1 : 2;
                }
                const unsigned te = t0 + (k2 ? sched2(x) : sched(T));
                const uint32_t sd = sb + (isw ? stage_w<k2>(lane) : SM_A + (13 + sl) * 8192);
#pragma unroll 1
                for (int t = j0; t < nj; t++) {
                    if (lane == t) {
                        if (t >= 3 && !k2) mbar_wait(rb + sl * 8, (k & 1) ^ 1);
                        while ((int)(te - clk()) > 0) ;
                        raw_load(maps.m + isw, y, z, sd, rb + (3 + t) * 8);
                    }
                    __syncwarp();
                }
                cluster_wait();
                if (elect_one()) asm volatile("prefetch.tensormap [%0];" :: "l"(maps.m + 2 + isw) : "memory");
                if (!isw) cw = 2;
                if (k2) {
                    if (!isw) {
                        if (lane < TN / 16) sc->cs[(e0 & 1) ^ 1][r * (TN / 16) + lane] = 0;
                        const int u = lane * 2 + (r & 1);
                        const unsigned tg = (e0 + 1) * (u < 32 ? 5 : 4);
                        bool dn = u >= NU;
                        for (int it = 0;; it++) {
                            if (!dn && (int)(ld_flag(sc->flag + F_W + u) - tg) >= 0) {
                                dn = true;
                                mbar_arrive(bars + (B_GO + lane * 2) * 8);
                            }
                            if (__all_sync(~0u, dn)) break;
                            if (it > (1 << 22)) __trap();
                        }
                    } else {
                        const float zxf = ld_zx(zero_x);
                        scale_bias(scale_x, scale_w + c * TN, bias + c * TN, sb, lane);
#pragma unroll 1
                        for (int h = 0; h < 3; h++) {
                            for (int it = 0; (int)(ld_flag(sc->flag + F_CS + h) - (e0 + 1) * (h < 2 ? 80 : 32)) < 0; it++) if (it > (1 << 22)) __trap();
                            int2 v[3];
                            int i[3];
#pragma unroll
                            for (int j = 0; j < 3; j++) {
                                i[j] = (j < 2 ? h * 64 + j * 32 : 128 + h * 16) + lane;
                                v[j] = __ldcg((const int2*)sc->cs[e0 & 1] + i[j]);
                            }
#pragma unroll
                            for (int j = 0; j < 3; j++) {
                                const uint32_t pa = sb + SM_PAR + i[j] * 4;
                                const uint32_t z = fold(zero_term(v[j].x, v[j].y, zxf), lds32(pa + TN * 2), lds32(pa + TN * 4));
                                if (h < 2 ? (j < 2 || lane < 16) : j == 2) st_async(pa, z, bars + (B_PAR + h) * 8);
                            }
                        }
                    }
                }
            }
        }
        if (!k2 && r < NBJ && warp == (r < 10 ? 8 : 10)) {
            const float zxf = ld_zx(zero_x);
            const int w = lane & 15;
            uint32_t sw = 0, bi = 0;
            if (CFG_EPI == 3) { mbar_wait(bars + B_SW * 8); sw = lds32(sb + SM_PAR + TN * 2 + col_of(r) * 2 + w * 4); bi = lds32(sb + SM_PAR + TN * 4 + col_of(r) * 2 + w * 4); }
            mbar_wait(bars + B_CS * 8);
            const uint32_t ca = sb + SM_CS + ((w >> 1) + (w & 1) * 16) * 4;
            const uint32_t z = fold(zero_term(lds32(ca), lds32(ca + 32), zxf), sw, bi);
            const int piece = r < 10 ? (r >= 5) : (r - 6) >> 1;
#pragma unroll 1
            for (int i = lane >> 4; i < CS; i += 2) st_async(mapa(sb + SM_PAR + col_of(r) * 2 + w * 4, i), z, mapa(bars + (B_PAR + piece) * 8, i));
        }
#pragma unroll 1
        for (int n = cw, nn, k = 0; n < NF; n = nn, k ^= 1) {
            nn = n + 3;
            if (!k2 && n < 5 && nn >= 5) nn += nn == 5 ? 2 : -1;
            const int gm = (int)(ford_table<k2>() >> (4 * n)), g = (gm >> 3) & 1, m = gm & 7;
            const int x = n >= 10 ? (n >> 1) * 64 : m == 4 ? 256 + g * 32 : g * 128 + (m & 2) * 32;
            const int y = n >= 10 ? (n & 1) * 64 : (m & 1) * 64;
            const CUtensorMap* mp = maps.m + (n < 10 && m == 4 ? 3 : 2);
            int gx = c * TN + x, gy = r * 128 + y;
            uint32_t src = sb + SM_STG + ((cw + NBJ) % 3) * 8192, nf = bars + (B_FREE + nn) * 8;
            asm volatile("" : "+l"(mp), "+r"(gx), "+r"(gy), "+r"(src), "+r"(nf));
            mbar_wait(bars + (B_FILL + cw) * 8, k);
            asm volatile("fence.proxy.async.shared::cta;" ::: "memory");
            if (elect_one()) tile_store(mp, gx, gy, src);
            asm volatile("cp.async.bulk.commit_group;" ::: "memory");
            asm volatile("cp.async.bulk.wait_group.read 0;" ::: "memory");
            __syncwarp();
            if (nn < NF && elect_one()) mbar_arrive(nf);
        }
    }
}

__global__ void __launch_bounds__(256)
w8a8_plain(const int* __restrict__ qx, const int* __restrict__ qw, const __nv_bfloat16* __restrict__ scale_x, const int* __restrict__ zero_x,
           const __nv_bfloat16* __restrict__ scale_w, const __nv_bfloat16* __restrict__ bias, __nv_bfloat16* __restrict__ out) {
    __shared__ int xs[16][K_ / 4];
    const int n = (blockIdx.x * 256 + threadIdx.x) * 2, m0 = blockIdx.y * 16;
    for (int i = threadIdx.x; i < 16 * K_ / 4; i += 256) {
        const uint4 v = ((const uint4*)qx)[m0 * (K_ / 4) + i];
        xs[i / (K_ / 4)][i % (K_ / 4)] = pack4(v.x, v.y, v.z, v.w);
    }
    __syncthreads();
    int acc[16][2] = {}, cs[2] = {};
    for (int k = 0; k < K_ / 4; k++) {
        uint2 v[4];
#pragma unroll
        for (int i = 0; i < 4; i++) v[i] = *(const uint2*)(qw + (k * 4 + i) * N_ + n);
        const unsigned w0 = pack4(v[0].x, v[1].x, v[2].x, v[3].x), w1 = pack4(v[0].y, v[1].y, v[2].y, v[3].y);
        cs[0] = sum4(w0, cs[0]); cs[1] = sum4(w1, cs[1]);
#pragma unroll
        for (int i = 0; i < 16; i++) { acc[i][0] = __dp4a(xs[i][k], (int)w0, acc[i][0]); acc[i][1] = __dp4a(xs[i][k], (int)w1, acc[i][1]); }
    }
    const uint32_t sx2 = (uint32_t)*(const unsigned short*)scale_x * 0x10001u, bi = *(const unsigned*)(bias + n);
    uint32_t sw = *(const unsigned*)(scale_w + n);
    if (CFG_EPI) sw = bf2_mul(sw, sx2);
    const uint32_t zc = fold(zero_term(cs[0], cs[1], ld_zx(zero_x)), sw, bi);
#pragma unroll
    for (int i = 0; i < 16; i++) *(unsigned*)(out + (m0 + i) * N_ + n) = epi(acc[i][0], acc[i][1], zc, sx2, sw, bi);
}

}

typedef CUresult (*EncodeFn)(CUtensorMap*, CUtensorMapDataType, cuuint32_t, void*, const cuuint64_t*, const cuuint64_t*,
                             const cuuint32_t*, const cuuint32_t*, CUtensorMapInterleave, CUtensorMapSwizzle,
                             CUtensorMapL2promotion, CUtensorMapFloatOOBfill);

extern "C" void kernel_launch(void* const* d_in, const int* in_sizes, int n_in, void* d_out, int out_size) {
    using namespace w8;
    static EncodeFn encode = nullptr;
    static cudaStream_t side;
    static cudaEvent_t started, joined;
    static int clusters = -1;
    static Scratch* sc;
    cudaLaunchConfig_t cfg = {};
    cfg.gridDim = dim3(NCTA); cfg.blockDim = dim3(512); cfg.dynamicSmemBytes = SM_TOTAL; cfg.stream = cudaStreamPerThread;
    if (clusters < 0) {
        void* fn = nullptr;
        cudaDriverEntryPointQueryResult qr;
        cudaGetDriverEntryPoint("cuTensorMapEncodeTiled", &fn, cudaEnableDefault, &qr);
        encode = (EncodeFn)fn;
        cudaGetSymbolAddress((void**)&sc, g_scratch);
        cudaStreamCreateWithFlags(&side, cudaStreamNonBlocking);
        cudaEventCreateWithFlags(&started, cudaEventDisableTiming);
        cudaEventCreateWithFlags(&joined, cudaEventDisableTiming);
        cudaFuncSetAttribute(w8a8_kernel<false>, cudaFuncAttributeMaxDynamicSharedMemorySize, SM_TOTAL);
        cudaFuncSetAttribute(w8a8_kernel<true>, cudaFuncAttributeMaxDynamicSharedMemorySize, SM_TOTAL);
        cudaFuncSetAttribute(w8a8_kernel<false>, cudaFuncAttributeNonPortableClusterSizeAllowed, 1);
        if (cudaOccupancyMaxActiveClusters(&clusters, w8a8_kernel<false>, &cfg) != cudaSuccess) { clusters = 0; cudaGetLastError(); }
    }
    const __nv_bfloat16 *sx = (const __nv_bfloat16*)d_in[2], *sw = (const __nv_bfloat16*)d_in[4], *bias = (const __nv_bfloat16*)d_in[5];
    const int* zx = (const int*)d_in[3];
    if (clusters < NCL) {
        w8a8_plain<<<dim3(N_ / 512, M_ / 16), 256, 0, cudaStreamPerThread>>>((const int*)d_in[0], (const int*)d_in[1], sx, zx, sw, bias, (__nv_bfloat16*)d_out);
        return;
    }
    Maps maps;
    const cuuint32_t es[3] = {1, 1, 1};
    {
        const cuuint64_t dim[3] = {32, K_ / 32, M_}, str[2] = {128, K_ * 4};
        const cuuint32_t box[3] = {32, 2, 32};
        encode(&maps.m[0], CU_TENSOR_MAP_DATA_TYPE_INT32, 3, d_in[0], dim, str, box, es, CU_TENSOR_MAP_INTERLEAVE_NONE,
               CU_TENSOR_MAP_SWIZZLE_128B, CU_TENSOR_MAP_L2_PROMOTION_NONE, CU_TENSOR_MAP_FLOAT_OOB_FILL_NONE);
    }
    {
        const cuuint64_t dim[3] = {32, K_, N_ / 32}, str[2] = {N_ * 4, 128};
        const cuuint32_t box[3] = {32, 64, 1};
        encode(&maps.m[1], CU_TENSOR_MAP_DATA_TYPE_INT32, 3, d_in[1], dim, str, box, es, CU_TENSOR_MAP_INTERLEAVE_NONE,
               CU_TENSOR_MAP_SWIZZLE_NONE, CU_TENSOR_MAP_L2_PROMOTION_NONE, CU_TENSOR_MAP_FLOAT_OOB_FILL_NONE);
    }
    for (int i = 0; i < 2; i++) {
        const cuuint64_t dim[2] = {N_, M_}, str[1] = {N_ * 2};
        const cuuint32_t box[2] = {i ? 32u : 64u, i ? 128u : 64u};
        encode(&maps.m[2 + i], CU_TENSOR_MAP_DATA_TYPE_BFLOAT16, 2, d_out, dim, str, box, es, CU_TENSOR_MAP_INTERLEAVE_NONE,
               i ? CU_TENSOR_MAP_SWIZZLE_NONE : CU_TENSOR_MAP_SWIZZLE_128B, CU_TENSOR_MAP_L2_PROMOTION_NONE, CU_TENSOR_MAP_FLOAT_OOB_FILL_NONE);
    }
    cudaLaunchAttribute at;
    at.id = cudaLaunchAttributeProgrammaticEvent;
    at.val.programmaticEvent.event = started; at.val.programmaticEvent.flags = 0; at.val.programmaticEvent.triggerAtBlockStart = 1;
    cfg.attrs = &at; cfg.numAttrs = 1;
    cudaLaunchKernelEx(&cfg, w8a8_kernel<false>, sc, (const char*)d_in[0], (const char*)d_in[1], sx, zx, sw, bias, maps);
    cudaStreamWaitEvent(side, started, 0);
    cfg.gridDim = dim3(20); cfg.stream = side; cfg.numAttrs = 0;
    cudaLaunchKernelEx(&cfg, w8a8_kernel<true>, sc, (const char*)d_in[0], (const char*)d_in[1], sx, zx, sw, bias, maps);
    cudaEventRecord(joined, side);
    cudaStreamWaitEvent(cudaStreamPerThread, joined, 0);
}
```
